```python
import torch

def _softmax(x, axis=-1):
    return torch.softmax(x, dim=axis)
def _gelu(x):
    return torch.nn.functional.gelu(x, approximate="tanh")
def _silu(x):
    return torch.nn.functional.silu(x)
def _sigmoid(x):
    return torch.sigmoid(x)
def _layernorm(x, axis=-1, eps=1e-5):
    m = x.mean(dim=axis, keepdim=True)
    v = x.var(dim=axis, keepdim=True, unbiased=False)
    return (x - m) / torch.sqrt(v + eps)
def _scatter_add(tgt, idx, src, axis=0):
    return tgt.clone().index_add_(axis, idx, src)
def _segment_sum(src, seg, n):
    out = torch.zeros((n,) + src.shape[1:], dtype=src.dtype)
    return out.index_add_(0, seg, src)
def _pad(x, pw):
    flat = tuple(v for pair in reversed(pw) for v in pair)
    return torch.nn.functional.pad(x, flat)

kernel_name = 'concat_heads__gqa_block_cached__mha_block_cached__near_ridge'

def setup_inputs():

    _w = (lambda a: (lambda t: t.to(torch.bfloat16) if t.is_floating_point() else t)(torch.as_tensor(a)))
    def _A_setup():
        B, Sq, D = 16, 160, 640
        Hq, Hkv, Sk, Dh = 32, 32, 512, 192
        assert Hq % Hkv == 0, (Hq, Hkv)
        return {
            "x": _w((lambda *s: torch.randn(*s, dtype=torch.bfloat16) * 0.8)(B, Sq, D)),
            "k_cache": _w((lambda *s: torch.randn(*s, dtype=torch.bfloat16) * 0.8)(B, Hkv, Sk, Dh)),
            "v_cache": _w((lambda *s: torch.randn(*s, dtype=torch.bfloat16) * 0.05)(B, Hkv, Sk, Dh)),
            "wq": _w((lambda *s: torch.randn(*s, dtype=torch.bfloat16) * 0.8)(D, Hq * Dh) * (D ** -0.5)),
            "wo": _w((lambda *s: torch.randn(*s, dtype=torch.bfloat16) * 0.05)(Hq * Dh, D) * ((Hq * Dh) ** -0.5)),
        }
    _A_in = _A_setup()

    def _B_setup():
        B, Sq, D = 16, 160, 640
        H, Sk, Dh = 32, 512, 192
        return {
            "x": _w((lambda *s: torch.randn(*s, dtype=torch.bfloat16) * 0.8)(B, Sq, D)),
            "k_cache": _w((lambda *s: torch.randn(*s, dtype=torch.bfloat16) * 0.8)(B, H, Sk, Dh)),
            "v_cache": _w((lambda *s: torch.randn(*s, dtype=torch.bfloat16) * 0.05)(B, H, Sk, Dh)),
            "wq": _w((lambda *s: torch.randn(*s, dtype=torch.bfloat16) * 0.8)(D, H * Dh) * (D ** -0.5)),
            "wo": _w((lambda *s: torch.randn(*s, dtype=torch.bfloat16) * 0.05)(H * Dh, D) * ((H * Dh) ** -0.5)),
        }
    _B_in = _B_setup()

    return {
        "A_x": _A_in["x"],
        "A_k_cache": _A_in["k_cache"],
        "A_v_cache": _A_in["v_cache"],
        "A_wq": _A_in["wq"],
        "A_wo": _A_in["wo"],
        "B_x": _B_in["x"],
        "B_k_cache": _B_in["k_cache"],
        "B_v_cache": _B_in["v_cache"],
        "B_wq": _B_in["wq"],
        "B_wo": _B_in["wo"],
    }

def reference(A_x, A_k_cache, A_v_cache, A_wq, A_wo, B_x, B_k_cache, B_v_cache, B_wq, B_wo):
    def _A_ref(x, k_cache, v_cache, wq, wo):
        B, Sq, D = x.shape
        Hq, Dh = 32, 192
        Hkv = k_cache.shape[1]
        rep = Hq // Hkv
        q = (lambda x, *d: x.permute(*d))((x @ wq).reshape(B, Sq, Hq, Dh), 0, 2, 1, 3)
        k = (lambda x, n, axis: torch.repeat_interleave(x, n, dim=axis))(k_cache, rep, axis=1)
        v = (lambda x, n, axis: torch.repeat_interleave(x, n, dim=axis))(v_cache, rep, axis=1)
        scores = torch.einsum("bhqd,bhkd->bhqk", q, k) * (Dh ** -0.5)
        p = _softmax(scores, axis=-1)
        o = torch.einsum("bhqk,bhkd->bhqd", p, v)
        return (lambda x, *d: x.permute(*d))(o, 0, 2, 1, 3).reshape(B, Sq, Hq * Dh) @ wo

    def _B_ref(x, k_cache, v_cache, wq, wo):
        B, Sq, D = x.shape
        H, Dh = 32, 192
        q = (lambda x, *d: x.permute(*d))((x @ wq).reshape(B, Sq, H, Dh), 0, 2, 1, 3)
        scores = torch.einsum("bhqd,bhkd->bhqk", q, k_cache) * (Dh ** -0.5)
        p = _softmax(scores, axis=-1)
        o = torch.einsum("bhqk,bhkd->bhqd", p, v_cache)
        return (lambda x, *d: x.permute(*d))(o, 0, 2, 1, 3).reshape(B, Sq, H * Dh) @ wo

    a = _A_ref(A_x, A_k_cache, A_v_cache, A_wq, A_wo)
    b = _B_ref(B_x, B_k_cache, B_v_cache, B_wq, B_wo)
    return torch.concatenate([a, b], axis=-1)
```

```cpp
#include <cuda_runtime.h>
#include <cuda_bf16.h>
#include <cuda.h>
#include <stdint.h>

#define DEBUG_TIMEOUT 1

namespace {

constexpr int SQ = 160, DM = 640, NH = 32, SK = 512, DH = 192, NB = 16;
constexpr int NITEMS = 2 * NB * NH;
constexpr int A_SLOT = 24576, B_SLOT = 20480, NSLOT = 5;
constexpr int OFF_A = 0;
constexpr int OFF_B = NSLOT * A_SLOT;
constexpr int OFF_L = OFF_B + NSLOT * B_SLOT;
constexpr int OFF_BAR = OFF_L + 160 * 4;
constexpr int SMEM_BYTES = OFF_BAR + 256;
constexpr uint32_t SB = 1024;
constexpr int BAR_FULLA = 0, BAR_EMPTYA = 40, BAR_FULLB = 80, BAR_EMPTYB = 120, BAR_XDONE = 160, BAR_QFULL = 168,
              BAR_PFULL = 176, BAR_PFREE = 192, BAR_LFULL = 208;
constexpr int O_ITEM_BYTES = SQ * DH * 2;

struct alignas(64) Params {
  CUtensorMap x[2], wq[2], k[2], v[2], wo[2], out;
  const __nv_bfloat16* kp[2];
  const __nv_bfloat16* vp[2];
};

__device__ uint4 g_o[(size_t)NITEMS * O_ITEM_BYTES / 16];
__device__ int g_bad[NITEMS * 4];

__device__ __forceinline__ uint32_t smem_u32(const void* p) { return (uint32_t)__cvta_generic_to_shared(p); }
__device__ __forceinline__ void wg_fence() { asm volatile("wgmma.fence.sync.aligned;" ::: "memory"); }
__device__ __forceinline__ void wg_commit() { asm volatile("wgmma.commit_group.sync.aligned;" ::: "memory"); }
template <int N> __device__ __forceinline__ void wg_wait() { asm volatile("wgmma.wait_group.sync.aligned %0;" ::"n"(N) : "memory"); }
template <int N> __device__ __forceinline__ void reg_fence(float (&d)[N]) {
#pragma unroll
  for (int i = 0; i < N; i++) asm volatile("" : "+f"(d[i])::"memory");
}
template <int N> __device__ __forceinline__ void zero_regs(float (&d)[N]) {
#pragma unroll
  for (int i = 0; i < N; i++) d[i] = 0.f;
}
__device__ __forceinline__ void proxy_fence() { asm volatile("fence.proxy.async.shared::cta;" ::: "memory"); }
__device__ __forceinline__ void mbar_init(uint32_t bar, int cnt) { asm volatile("mbarrier.init.shared::cta.b64 [%0], %1;" ::"r"(bar), "r"(cnt) : "memory"); }
__device__ __forceinline__ void mbar_arrive(uint32_t bar) { asm volatile("mbarrier.arrive.shared::cta.b64 _, [%0];" ::"r"(bar) : "memory"); }
__device__ __forceinline__ void mbar_arrive_if0(uint32_t bar, uint32_t sel) {
  asm volatile("{\n.reg .pred p;\nsetp.eq.u32 p, %1, 0;\n@p mbarrier.arrive.shared::cta.b64 _, [%0];\n}\n" ::"r"(bar), "r"(sel) : "memory");
}
__device__ __forceinline__ void mbar_arrive2_if0(uint32_t bar, uint32_t sel) {
  asm volatile("{\n.reg .pred p;\nsetp.eq.u32 p, %1, 0;\n@p mbarrier.arrive.shared::cta.b64 _, [%0], 2;\n}\n" ::"r"(bar), "r"(sel) : "memory");
}
__device__ __forceinline__ void mbar_expect(uint32_t bar, uint32_t bytes) {
  asm volatile("mbarrier.arrive.expect_tx.shared::cta.b64 _, [%0], %1;" ::"r"(bar), "r"(bytes) : "memory");
}
__device__ __forceinline__ void mbar_wait(int& bud, uint32_t bar, uint32_t parity) {
  asm volatile(
      "{\n.reg .pred p, q;\n"
      "LW:\n"
      "mbarrier.try_wait.parity.shared::cta.b64 p, [%1], %2;\n"
      "@!p add.s32 %0, %0, -1;\n"
      "setp.gt.and.s32 q, %0, 0, !p;\n"
      "@q bra LW;\n}\n" : "+r"(bud) : "r"(bar), "r"(parity) : "memory");
}
constexpr int WAIT_BUDGET = 1 << 20;
__device__ __forceinline__ bool elect_one() {
  uint32_t p;
  asm volatile("{\n.reg .pred p;\nelect.sync _|p, 0xffffffff;\nselp.u32 %0, 1, 0, p;\n}\n" : "=r"(p));
  return p;
}
__device__ __forceinline__ void tma2d(uint32_t dst, const CUtensorMap* m, uint32_t bar, int c0, int c1) {
  asm volatile("cp.async.bulk.tensor.2d.shared::cluster.global.mbarrier::complete_tx::bytes [%0], [%1, {%3, %4}], [%2];"
               ::"r"(dst), "l"(m), "r"(bar), "r"(c0), "r"(c1) : "memory");
}
__device__ __forceinline__ void tma3d(uint32_t dst, const CUtensorMap* m, uint32_t bar, int c0, int c1, int c2) {
  asm volatile("cp.async.bulk.tensor.3d.shared::cluster.global.mbarrier::complete_tx::bytes [%0], [%1, {%3, %4, %5}], [%2];"
               ::"r"(dst), "l"(m), "r"(bar), "r"(c0), "r"(c1), "r"(c2) : "memory");
}
__device__ __forceinline__ void tma3d_hint(uint32_t dst, const CUtensorMap* m, uint32_t bar, int c0, int c1, int c2, uint64_t pol) {
  asm volatile("cp.async.bulk.tensor.3d.shared::cluster.global.mbarrier::complete_tx::bytes.L2::cache_hint [%0], [%1, {%3, %4, %5}], [%2], %6;"
               ::"r"(dst), "l"(m), "r"(bar), "r"(c0), "r"(c1), "r"(c2), "l"(pol) : "memory");
}
__device__ __forceinline__ void bulk_load(uint32_t dst, const void* src, uint32_t bytes, uint32_t bar) {
  asm volatile("cp.async.bulk.shared::cluster.global.mbarrier::complete_tx::bytes [%0], [%1], %2, [%3];"
               ::"r"(dst), "l"(src), "r"(bytes), "r"(bar) : "memory");
}
__device__ __forceinline__ void l2_prefetch(const void* src, uint32_t bytes) {
  asm volatile("cp.async.bulk.prefetch.L2.global [%0], %1;" ::"l"(src), "r"(bytes) : "memory");
}
__device__ __forceinline__ void tma_store2d(const CUtensorMap* m, uint32_t src, int c0, int c1) {
  asm volatile("cp.async.bulk.tensor.2d.global.shared::cta.bulk_group [%0, {%2, %3}], [%1];" ::"l"(m), "r"(src), "r"(c0), "r"(c1) : "memory");
}
__device__ __forceinline__ void bar_sync(int id, int n) { asm volatile("bar.sync %0, %1;" ::"r"(id), "r"(n) : "memory"); }
__device__ __forceinline__ void bar_arrive(int id, int n) { asm volatile("bar.arrive %0, %1;" ::"r"(id), "r"(n) : "memory"); }
__device__ __forceinline__ float ex2(float x) { float y; asm("ex2.approx.ftz.f32 %0, %1;" : "=f"(y) : "f"(x)); return y; }
__device__ __forceinline__ uint32_t pack2(float lo, float hi) { uint32_t r; asm("cvt.rn.bf16x2.f32 %0, %1, %2;" : "=r"(r) : "f"(hi), "f"(lo)); return r; }
__device__ __forceinline__ void stsm_t(uint32_t a, uint32_t r0, uint32_t r1, uint32_t r2, uint32_t r3) {
  asm volatile("stmatrix.sync.aligned.m8n8.x4.trans.shared.b16 [%0], {%1,%2,%3,%4};" ::"r"(a), "r"(r0), "r"(r1), "r"(r2), "r"(r3) : "memory");
}
constexpr uint32_t HI_SW = 0x40000040u;
__device__ __forceinline__ uint32_t lo_sw(uint32_t addr) { return (addr >> 4) | (1u << 16); }
constexpr uint32_t HI_O = 8u;
__device__ __forceinline__ uint32_t lo_o(uint32_t addr) { return (addr >> 4) | (160u << 16); }
__device__ __forceinline__ uint32_t opaque(uint32_t x) { uint32_t y; asm volatile("mov.u32 %0, %1;" : "=r"(y) : "r"(x)); return y; }

template <int TA, int TB, uint32_t OA, uint32_t OB, uint32_t HB>
__device__ __forceinline__ void mma160(float (&d)[80], uint32_t la, uint32_t lb, int sc) {
  asm volatile(
      "{\n.reg .pred p;\n.reg .b32 a, b;\n.reg .b64 da, db;\nsetp.ne.b32 p, %82, 0;\n"
      "add.u32 a, %80, %85;\nadd.u32 b, %81, %86;\nmov.b64 da, {a, 0x40000040};\nmov.b64 db, {b, %87};\n"
      "wgmma.mma_async.sync.aligned.m64n160k16.f32.bf16.bf16 {"
      "%0,%1,%2,%3,%4,%5,%6,%7,%8,%9,%10,%11,%12,%13,%14,%15,%16,%17,%18,%19,%20,%21,%22,%23,%24,%25,%26,%27,%28,%29,%30,%31,%32,%33,%34,%35,%36,"
      "%37,%38,%39,%40,%41,%42,%43,%44,%45,%46,%47,%48,%49,%50,%51,%52,%53,%54,%55,%56,%57,%58,%59,%60,%61,%62,%63,%64,%65,%66,%67,%68,%69,%70,%71,"
      "%72,%73,%74,%75,%76,%77,%78,%79"
      "}, da, db, p, 1, 1, %83, %84;\n}\n"
      :
      "+f"(d[0]),"+f"(d[1]),"+f"(d[2]),"+f"(d[3]),"+f"(d[4]),"+f"(d[5]),"+f"(d[6]),"+f"(d[7]),"+f"(d[8]),"+f"(d[9]),"+f"(d[10]),"+f"(d[11]),
      "+f"(d[12]),"+f"(d[13]),"+f"(d[14]),"+f"(d[15]),"+f"(d[16]),"+f"(d[17]),"+f"(d[18]),"+f"(d[19]),"+f"(d[20]),"+f"(d[21]),"+f"(d[22]),
      "+f"(d[23]),"+f"(d[24]),"+f"(d[25]),"+f"(d[26]),"+f"(d[27]),"+f"(d[28]),"+f"(d[29]),"+f"(d[30]),"+f"(d[31]),"+f"(d[32]),"+f"(d[33]),
      "+f"(d[34]),"+f"(d[35]),"+f"(d[36]),"+f"(d[37]),"+f"(d[38]),"+f"(d[39]),"+f"(d[40]),"+f"(d[41]),"+f"(d[42]),"+f"(d[43]),"+f"(d[44]),
      "+f"(d[45]),"+f"(d[46]),"+f"(d[47]),"+f"(d[48]),"+f"(d[49]),"+f"(d[50]),"+f"(d[51]),"+f"(d[52]),"+f"(d[53]),"+f"(d[54]),"+f"(d[55]),
      "+f"(d[56]),"+f"(d[57]),"+f"(d[58]),"+f"(d[59]),"+f"(d[60]),"+f"(d[61]),"+f"(d[62]),"+f"(d[63]),"+f"(d[64]),"+f"(d[65]),"+f"(d[66]),
      "+f"(d[67]),"+f"(d[68]),"+f"(d[69]),"+f"(d[70]),"+f"(d[71]),"+f"(d[72]),"+f"(d[73]),"+f"(d[74]),"+f"(d[75]),"+f"(d[76]),"+f"(d[77]),
      "+f"(d[78]),"+f"(d[79])
      : "r"(la), "r"(lb), "r"(sc), "n"(TA), "n"(TB), "n"(OA >> 4), "n"(OB >> 4), "n"(HB));
}

template <int TA, int TB, uint32_t OA, uint32_t OB, uint32_t HB>
__device__ __forceinline__ void mma80(float (&d)[40], uint32_t la, uint32_t lb, int sc) {
  asm volatile(
      "{\n.reg .pred p;\n.reg .b32 a, b;\n.reg .b64 da, db;\nsetp.ne.b32 p, %42, 0;\n"
      "add.u32 a, %40, %45;\nadd.u32 b, %41, %46;\nmov.b64 da, {a, 0x40000040};\nmov.b64 db, {b, %47};\n"
      "wgmma.mma_async.sync.aligned.m64n80k16.f32.bf16.bf16 {"
      "%0,%1,%2,%3,%4,%5,%6,%7,%8,%9,%10,%11,%12,%13,%14,%15,%16,%17,%18,%19,%20,%21,%22,%23,%24,%25,%26,%27,%28,%29,%30,%31,%32,%33,%34,%35,%36,"
      "%37,%38,%39"
      "}, da, db, p, 1, 1, %43, %44;\n}\n"
      :
      "+f"(d[0]),"+f"(d[1]),"+f"(d[2]),"+f"(d[3]),"+f"(d[4]),"+f"(d[5]),"+f"(d[6]),"+f"(d[7]),"+f"(d[8]),"+f"(d[9]),"+f"(d[10]),"+f"(d[11]),
      "+f"(d[12]),"+f"(d[13]),"+f"(d[14]),"+f"(d[15]),"+f"(d[16]),"+f"(d[17]),"+f"(d[18]),"+f"(d[19]),"+f"(d[20]),"+f"(d[21]),"+f"(d[22]),
      "+f"(d[23]),"+f"(d[24]),"+f"(d[25]),"+f"(d[26]),"+f"(d[27]),"+f"(d[28]),"+f"(d[29]),"+f"(d[30]),"+f"(d[31]),"+f"(d[32]),"+f"(d[33]),
      "+f"(d[34]),"+f"(d[35]),"+f"(d[36]),"+f"(d[37]),"+f"(d[38]),"+f"(d[39])
      : "r"(la), "r"(lb), "r"(sc), "n"(TA), "n"(TB), "n"(OA >> 4), "n"(OB >> 4), "n"(HB));
}

struct Ring { uint32_t s0, ph0; };
__device__ __forceinline__ void ring_pos(const Ring& r, int i, uint32_t& slot, uint32_t& ph) {
  uint32_t s = opaque(r.s0) + (i % NSLOT);
  uint32_t wrap = s >= NSLOT;
  slot = s - (wrap ? NSLOT : 0);
  ph = r.ph0 ^ ((i / NSLOT) & 1) ^ wrap;
}
__device__ __forceinline__ void ring_advance(Ring& r, int n) {
  uint32_t s, p;
  ring_pos(r, n, s, p);
  r.s0 = s; r.ph0 = p;
}
__host__ __device__ constexpr int idxK(int j) { return j == 0 ? 10 : 9 + 2 * j; }
__host__ __device__ constexpr int idxV(int j) { return j == 7 ? 25 : 12 + 2 * j; }

__device__ __forceinline__ void item_coords(int item, int& blk, int& h, int& b) { blk = item >> 9; h = (item >> 4) & 31; b = item & 15; }

template <int W>
__device__ __forceinline__ void pv_mma(float (&om)[80], float (&oh)[40], uint32_t vaddr, uint32_t paddr, int first) {
  const uint32_t la = lo_sw(vaddr), lb = lo_sw(paddr);
#define PV_STEP(ks, sc)                                                        \
  mma160<1, 0, W * 2 * 8192 + ks * 2048, ks * 32, HI_SW>(om, la, lb, sc);      \
  mma80<1, 0, 8192 + ks * 2048, W * 10240 + ks * 32, HI_SW>(oh, la, lb, sc);
  PV_STEP(0, !first) PV_STEP(1, 1) PV_STEP(2, 1) PV_STEP(3, 1)
#undef PV_STEP
}

__device__ __forceinline__ void s_mma(float (&sacc)[80], uint32_t kaddr, uint32_t qaddr) {
  const uint32_t la = lo_sw(kaddr), lb = lo_sw(qaddr);
#define S_STEP(ks) mma160<0, 0, (ks >> 2) * 8192 + (ks & 3) * 32, (ks >> 2) * B_SLOT + (ks & 3) * 32, HI_SW>(sacc, la, lb, ks != 0);
  S_STEP(0) S_STEP(1) S_STEP(2) S_STEP(3) S_STEP(4) S_STEP(5) S_STEP(6) S_STEP(7) S_STEP(8) S_STEP(9) S_STEP(10) S_STEP(11)
#undef S_STEP
}

template <int W>
__device__ __forceinline__ void attn_consumer(uint32_t sb, int first_item, int step, int nitems) {
  const uint32_t bars = sb + OFF_BAR;
  int bud = WAIT_BUDGET;
  const int tid = threadIdx.x & 127, lane = tid & 31, warp = tid >> 5;
  const uint32_t st_off = ((lane & 7) + 8 * (lane >> 4)) * 128 + (((2 * warp + ((lane >> 3) & 1)) ^ (lane & 7)) << 4);
  float om[80], oh[40], sacc[80];
  zero_regs(om); zero_regs(oh); zero_regs(sacc);
  Ring ring{0u, 0u};
  uint32_t itpar = 0;
  const float qscale = 0.07216878364870322f * 1.4426950408889634f;

  for (int item = first_item; item < nitems; item += step) {
    {
      uint32_t sa = ring.s0, pa = ring.ph0, prev_a = 0;
#pragma unroll 1
      for (int c = 0; c < 10; c++) {
        const uint32_t sbi = c >= 5 ? c - 5 : c;
        mbar_wait(bud, bars + BAR_FULLA + sa * 8, pa);
        mbar_wait(bud, bars + BAR_FULLB + sbi * 8, c >= 5);
        wg_fence();
        pv_mma<W>(om, oh, sb + OFF_A + sa * A_SLOT, sb + OFF_B + sbi * B_SLOT, c == 0);
        wg_commit();
        if (c > 0) {
          wg_wait<1>();
          mbar_arrive_if0(bars + BAR_EMPTYA + prev_a * 8, tid);
          mbar_arrive_if0(bars + BAR_EMPTYB + (c - 1) * 8, tid | (c > 5));
          mbar_arrive_if0(bars + BAR_XDONE, tid | (c != 8));
        }
        prev_a = sa;
        if (++sa == NSLOT) { sa = 0; pa ^= 1; }
      }
      wg_wait<0>();
      reg_fence(om); reg_fence(oh);
      mbar_arrive_if0(bars + BAR_EMPTYA + prev_a * 8, tid);
    }
    mbar_wait(bud, bars + BAR_XDONE, itpar);
    {
      const uint32_t qm = sb + OFF_B + (W * 2) * B_SLOT + st_off;
      const uint32_t qh = sb + OFF_B + B_SLOT + W * 10240 + st_off;
#pragma unroll
      for (int J = 0; J < 5; J++)
        stsm_t(qh + J * 2048, pack2(oh[8 * J] * qscale, oh[8 * J + 1] * qscale), pack2(oh[8 * J + 2] * qscale, oh[8 * J + 3] * qscale),
               pack2(oh[8 * J + 4] * qscale, oh[8 * J + 5] * qscale), pack2(oh[8 * J + 6] * qscale, oh[8 * J + 7] * qscale));
#pragma unroll
      for (int J = 0; J < 10; J++)
        stsm_t(qm + J * 2048, pack2(om[8 * J] * qscale, om[8 * J + 1] * qscale), pack2(om[8 * J + 2] * qscale, om[8 * J + 3] * qscale),
               pack2(om[8 * J + 4] * qscale, om[8 * J + 5] * qscale), pack2(om[8 * J + 6] * qscale, om[8 * J + 7] * qscale));
      proxy_fence();
      __syncwarp();
      mbar_arrive_if0(bars + BAR_QFULL, lane);
    }
    mbar_wait(bud, bars + BAR_QFULL, itpar);

    const uint32_t pown = sb + OFF_B + (3 + W) * B_SLOT, poth = sb + OFF_B + (4 - W) * B_SLOT;
#pragma unroll
    for (int jj = 0; jj < 4; jj++) {
      const int j = 2 * jj + W;
      uint32_t sK, pK, sV2 = 0, pV2 = 0, sV1 = 0, pV1 = 0;
      ring_pos(ring, idxK(j), sK, pK);
      if (j >= 2) ring_pos(ring, idxV(j >= 2 ? j - 2 : 0), sV2, pV2);
      if (j >= 1) ring_pos(ring, idxV(j >= 1 ? j - 1 : 0), sV1, pV1);
      if (j >= 2) mbar_wait(bud, bars + BAR_FULLA + sV2 * 8, pV2);
      mbar_wait(bud, bars + BAR_FULLA + sK * 8, pK);
      if (j >= 1) bar_sync(1 + W, 256);
      wg_fence();
      if (j >= 2) pv_mma<W>(om, oh, sb + OFF_A + sV2 * A_SLOT, pown, j == 2);
      s_mma(sacc, sb + OFF_A + sK * A_SLOT, sb + OFF_B);
      wg_commit();
      if (j >= 1) {
        mbar_wait(bud, bars + BAR_PFULL + (1 - W) * 8, ((j - 1) >> 1) & 1);
        mbar_wait(bud, bars + BAR_FULLA + sV1 * 8, pV1);
        wg_fence();
        pv_mma<W>(om, oh, sb + OFF_A + sV1 * A_SLOT, poth, j == 1);
        wg_commit();
      }
      bar_arrive(2 - W, 256);
      if (j >= 1) wg_wait<1>(); else wg_wait<0>();
      reg_fence(sacc);
      mbar_arrive2_if0(bars + BAR_EMPTYA + sK * 8, tid);
      if (j >= 2) mbar_arrive_if0(bars + BAR_EMPTYA + sV2 * 8, tid);
      if (jj == 3) mbar_arrive_if0(bars + BAR_EMPTYB + tid * 8, tid >= 3);
      if (jj >= 1) mbar_wait(bud, bars + BAR_PFREE + W * 8, (jj - 1) & 1);
#pragma unroll
      for (int J = 0; J < 10; J++)
        stsm_t(pown + st_off + J * 2048, pack2(ex2(sacc[8 * J]), ex2(sacc[8 * J + 1])), pack2(ex2(sacc[8 * J + 2]), ex2(sacc[8 * J + 3])),
               pack2(ex2(sacc[8 * J + 4]), ex2(sacc[8 * J + 5])), pack2(ex2(sacc[8 * J + 6]), ex2(sacc[8 * J + 7])));
      if (j >= 1) {
        wg_wait<0>();
        mbar_arrive_if0(bars + BAR_EMPTYA + sV1 * 8, tid);
      }
      proxy_fence();
      __syncwarp();
      mbar_arrive_if0(bars + BAR_PFULL + W * 8, lane);
    }
    {
      uint32_t sV6, pV6, sV7, pV7;
      ring_pos(ring, idxV(6), sV6, pV6);
      ring_pos(ring, idxV(7), sV7, pV7);
      if (W == 0) {
        mbar_wait(bud, bars + BAR_FULLA + sV6 * 8, pV6);
        bar_sync(1, 256);
        wg_fence();
        pv_mma<0>(om, oh, sb + OFF_A + sV6 * A_SLOT, pown, 0);
        wg_commit();
        mbar_wait(bud, bars + BAR_PFULL + 8, 1);
        mbar_wait(bud, bars + BAR_FULLA + sV7 * 8, pV7);
        wg_fence();
        pv_mma<0>(om, oh, sb + OFF_A + sV7 * A_SLOT, poth, 0);
        wg_commit();
        bar_arrive(2, 256);
        wg_wait<1>();
        mbar_arrive_if0(bars + BAR_EMPTYA + sV6 * 8, tid);
      } else {
        mbar_wait(bud, bars + BAR_FULLA + sV7 * 8, pV7);
        bar_sync(2, 256);
        wg_fence();
        pv_mma<1>(om, oh, sb + OFF_A + sV7 * A_SLOT, pown, 0);
        wg_commit();
      }
      wg_wait<0>();
      reg_fence(om); reg_fence(oh);
      mbar_wait(bud, bars + BAR_LFULL, itpar);
      mbar_arrive_if0(bars + BAR_EMPTYA + sV7 * 8, tid);
      mbar_arrive_if0(bars + BAR_EMPTYB + 24 + tid * 8, tid >= 2);
    }
    {
      int blk, h, b;
      item_coords(item, blk, h, b);
      const int g = lane >> 2, t = lane & 3;
      char* ob = (char*)g_o + (size_t)((blk * NB + b) * NH + h) * O_ITEM_BYTES + (2 * warp) * 2560 + (t >> 1) * 128 + g * 16 + (t & 1) * 8;
      char* omp = ob + (W * 2) * 8 * 2560;
      char* ohp = ob + 8 * 2560;
      const uint32_t la = sb + OFF_L + t * 160;
#pragma unroll
      for (int J = 0; J < 10; J++) {
        float i0, i1, i2, i3;
        asm volatile("ld.shared.v4.f32 {%0,%1,%2,%3}, [%4];" : "=f"(i0), "=f"(i1), "=f"(i2), "=f"(i3) : "r"(la + J * 16) : "memory");
        *(uint2*)(omp + J * 256) = make_uint2(pack2(om[8 * J] * i0, om[8 * J + 1] * i1), pack2(om[8 * J + 4] * i2, om[8 * J + 5] * i3));
        *(uint2*)(omp + J * 256 + 2560) = make_uint2(pack2(om[8 * J + 2] * i0, om[8 * J + 3] * i1), pack2(om[8 * J + 6] * i2, om[8 * J + 7] * i3));
        if (J >= 5 * W && J < 5 * W + 5) {
          const int H = J - 5 * W >= 0 && J - 5 * W < 5 ? J - 5 * W : 0;
          *(uint2*)(ohp + J * 256) = make_uint2(pack2(oh[8 * H] * i0, oh[8 * H + 1] * i1), pack2(oh[8 * H + 4] * i2, oh[8 * H + 5] * i3));
          *(uint2*)(ohp + J * 256 + 2560) = make_uint2(pack2(oh[8 * H + 2] * i0, oh[8 * H + 3] * i1), pack2(oh[8 * H + 6] * i2, oh[8 * H + 7] * i3));
        }
      }
    }
    ring_advance(ring, 26);
    itpar ^= 1;
  }
}

__device__ __forceinline__ float sum8(uint32_t a) {
  uint32_t w0, w1, w2, w3;
  asm volatile("ld.shared.v4.b32 {%0,%1,%2,%3}, [%4];" : "=r"(w0), "=r"(w1), "=r"(w2), "=r"(w3) : "r"(a) : "memory");
  float s = __uint_as_float(w0 << 16) + __uint_as_float(w0 & 0xffff0000u);
  float t = __uint_as_float(w1 << 16) + __uint_as_float(w1 & 0xffff0000u);
  s += __uint_as_float(w2 << 16); t += __uint_as_float(w2 & 0xffff0000u);
  s += __uint_as_float(w3 << 16); t += __uint_as_float(w3 & 0xffff0000u);
  return s + t;
}
__device__ __forceinline__ void attn_helper(uint32_t sb, int hw, int first_item, int step, int nitems) {
  const uint32_t bars = sb + OFF_BAR;
  int bud = WAIT_BUDGET;
  const int lane = threadIdx.x & 31, r = lane >> 1, hb = lane & 1;
  const uint32_t base = sb + OFF_B + 3 * B_SLOT + (16 * hw + r) * 128 + hb * 16;
  for (int item = first_item; item < nitems; item += step) {
    float acc[4] = {0.f, 0.f, 0.f, 0.f};
#pragma unroll 1
    for (int j = 0; j < 8; j++) {
      mbar_wait(bud, bars + BAR_PFULL + (j & 1) * 8, (j >> 1) & 1);
      const uint32_t pb = base + (j & 1) * B_SLOT;
#pragma unroll
      for (int u = 0; u < 4; u++) {
        if (u < 3 || hw == 0) {
          const uint32_t a = pb + u * 3 * 2048;
          acc[u] += (sum8(a + (((0 + r) & 3) << 5)) + sum8(a + (((1 + r) & 3) << 5))) + (sum8(a + (((2 + r) & 3) << 5)) + sum8(a + (((3 + r) & 3) << 5)));
        }
      }
      __syncwarp();
      mbar_arrive_if0(bars + BAR_PFREE + (j & 1) * 8, lane);
    }
    bool bad = false;
#pragma unroll
    for (int u = 0; u < 4; u++) {
      if (u < 3 || hw == 0) {
        const float l = acc[u] + __shfl_xor_sync(0xffffffffu, acc[u], 1);
        bad |= !(l >= 5.421010862427522e-20f && l <= 1.8446744073709552e19f);
        const int n = 16 * (hw + 3 * u) + r;
        if (hb == 0) asm volatile("st.shared.f32 [%0], %1;" ::"r"(sb + OFF_L + (((n & 7) >> 1) * 40 + 2 * (n >> 3) + (n & 1)) * 4), "f"(__frcp_rn(l)) : "memory");
      }
    }
    const bool anybad = __any_sync(0xffffffffu, bad);
    if (lane == 0) {
      mbar_arrive(bars + BAR_LFULL);
      g_bad[item * 4 + hw] = anybad;
    }
  }
}

__device__ __forceinline__ void attn_producer(const Params& p, uint32_t sb, int first_item, int step, int nitems) {
  const uint32_t bars = sb + OFF_BAR;
  int bud = WAIT_BUDGET;
  uint32_t sa = 0, pa = 1;
  uint64_t pol;
  asm volatile("createpolicy.fractional.L2::evict_first.b64 %0, 1.0;" : "=l"(pol));
  for (int item = first_item; item < nitems; item += step) {
    int blk, h, b;
    item_coords(item, blk, h, b);
    const int row0 = (b * NH + h) * SK;
    const char* kg = (const char*)p.kp[blk] + (size_t)row0 * DH * 2;
    const char* vg = (const char*)p.vp[blk] + (size_t)row0 * DH * 2;
#pragma unroll 1
    for (int c = 0; c < 10; c++) {
      const uint32_t sbi = c >= 5 ? c - 5 : c;
      mbar_wait(bud, bars + BAR_EMPTYA + sa * 8, pa);
      mbar_expect(bars + BAR_FULLA + sa * 8, A_SLOT);
      tma3d(sb + OFF_A + sa * A_SLOT, &p.wq[blk], bars + BAR_FULLA + sa * 8, 0, c * 64, h * 3);
      if (++sa == NSLOT) { sa = 0; pa ^= 1; }
      mbar_wait(bud, bars + BAR_EMPTYB + sbi * 8, c < 5);
      mbar_expect(bars + BAR_FULLB + sbi * 8, B_SLOT);
      tma2d(sb + OFF_B + sbi * B_SLOT, &p.x[blk], bars + BAR_FULLB + sbi * 8, c * 64, b * SQ);
      if (c < 8) l2_prefetch(((c & 1) ? vg : kg) + (c >> 1) * A_SLOT, A_SLOT);
    }
#pragma unroll 1
    for (int i = 0; i < 16; i++) {
      const bool isK = (i == 0) || ((i & 1) && i < 15);
      const int j = i == 0 ? 0 : (i == 15 ? 7 : (isK ? (i + 1) >> 1 : (i - 2) >> 1));
      mbar_wait(bud, bars + BAR_EMPTYA + sa * 8, pa);
      mbar_expect(bars + BAR_FULLA + sa * 8, A_SLOT);
      tma3d_hint(sb + OFF_A + sa * A_SLOT, isK ? &p.k[blk] : &p.v[blk], bars + BAR_FULLA + sa * 8, 0, row0 + j * 64, 0, pol);
      if (++sa == NSLOT) { sa = 0; pa ^= 1; }
      if (i < 8) l2_prefetch(((i & 1) ? vg : kg) + (4 + (i >> 1)) * A_SLOT, A_SLOT);
    }
  }
}

__global__ void __launch_bounds__(384, 1) attn_kernel(const __grid_constant__ Params p) {
  extern __shared__ __align__(1024) char smem_raw[];
  if ((smem_u32(smem_raw) & 0xFFFFFFu) != SB) return;
  constexpr uint32_t sb = SB;
  const uint32_t bars = sb + OFF_BAR;
  if (threadIdx.x == 0) {
    for (int i = 0; i < NSLOT; i++) {
      mbar_init(bars + BAR_FULLA + i * 8, 1); mbar_init(bars + BAR_EMPTYA + i * 8, 2);
      mbar_init(bars + BAR_FULLB + i * 8, 1); mbar_init(bars + BAR_EMPTYB + i * 8, 2);
    }
    mbar_init(bars + BAR_XDONE, 2); mbar_init(bars + BAR_QFULL, 8);
    mbar_init(bars + BAR_PFULL, 4); mbar_init(bars + BAR_PFULL + 8, 4);
    mbar_init(bars + BAR_PFREE, 3); mbar_init(bars + BAR_PFREE + 8, 3);
    mbar_init(bars + BAR_LFULL, 3);
    asm volatile("fence.mbarrier_init.release.cluster;" ::: "memory");
    proxy_fence();
  }
  __syncthreads();
  const int warp = __shfl_sync(0xffffffffu, threadIdx.x >> 5, 0);
  if (warp >= 8) {
    asm volatile("setmaxnreg.dec.sync.aligned.u32 40;");
    if (warp == 8) {
      if (elect_one()) attn_producer(p, sb, blockIdx.x, gridDim.x, NITEMS);
    } else {
      attn_helper(sb, warp - 9, blockIdx.x, gridDim.x, NITEMS);
    }
  } else {
    asm volatile("setmaxnreg.inc.sync.aligned.u32 232;");
    if (warp < 4) attn_consumer<0>(sb, blockIdx.x, gridDim.x, NITEMS);
    else attn_consumer<1>(sb, blockIdx.x, gridDim.x, NITEMS);
  }
}

constexpr int OA_SLOT = 40960, ONA = 3;
template <int W>
__device__ __forceinline__ void oproj_consumer(const Params& p, uint32_t sb, int tile) {
  const uint32_t bars = sb + OFF_BAR;
  int bud = WAIT_BUDGET;
  const int tid = threadIdx.x & 127, lane = tid & 31, warp = tid >> 5;
  const bool leader = (tid == 0);
  float a0[80], a1[80], ah[40];
  zero_regs(a0); zero_regs(a1); zero_regs(ah);
  uint32_t sa = 0, pa = 0, sbi = 0, pb = 0, prev_a = 0, prev_b = 0;
#pragma unroll 1
  for (int c = 0; c < 96; c++) {
    mbar_wait(bud, bars + BAR_FULLA + sa * 8, pa);
    mbar_wait(bud, bars + BAR_FULLB + sbi * 8, pb);
    wg_fence();
    const uint32_t la = lo_sw(sb + OFF_A + sa * OA_SLOT), lb = lo_o(sb + OFF_B + sbi * B_SLOT);
#define O_STEP(ks, sc)                                                             \
  mma160<1, 1, (W * 3) * 8192 + ks * 2048, ks * 5120, HI_O>(a0, la, lb, sc);       \
  mma160<1, 1, (W * 3 + 1) * 8192 + ks * 2048, ks * 5120, HI_O>(a1, la, lb, sc);   \
  mma80<1, 1, 2 * 8192 + ks * 2048, ks * 5120 + W * 1280, HI_O>(ah, la, lb, sc);
    O_STEP(0, c != 0) O_STEP(1, 1) O_STEP(2, 1) O_STEP(3, 1)
#undef O_STEP
    wg_commit();
    if (c > 0) {
      wg_wait<1>();
      mbar_arrive_if0(bars + BAR_EMPTYA + prev_a * 8, tid); mbar_arrive_if0(bars + BAR_EMPTYB + prev_b * 8, tid);
    }
    prev_a = sa; prev_b = sbi;
    if (++sa == ONA) { sa = 0; pa ^= 1; }
    if (++sbi == NSLOT) { sbi = 0; pb ^= 1; }
  }
  wg_wait<0>();
  reg_fence(a0); reg_fence(a1); reg_fence(ah);
  bar_sync(1, 256);
  const int i = lane & 7, m = lane >> 4;
  const int qrow = 8 * ((i >> 1) & 1) + 4 * m + 2 * (i >> 2) + (i & 1);
  const uint32_t st_off = qrow * 128 + (((2 * warp + ((lane >> 3) & 1)) ^ (qrow & 7)) << 4);
  const uint32_t s0 = sb + OFF_B + (W * 3) * B_SLOT + st_off, s1 = s0 + B_SLOT, sh = sb + OFF_B + 2 * B_SLOT + W * 10240 + st_off;
#pragma unroll
  for (int J = 0; J < 10; J++) {
    stsm_t(s0 + J * 2048, pack2(a0[8 * J], a0[8 * J + 1]), pack2(a0[8 * J + 2], a0[8 * J + 3]), pack2(a0[8 * J + 4], a0[8 * J + 5]), pack2(a0[8 * J + 6], a0[8 * J + 7]));
    stsm_t(s1 + J * 2048, pack2(a1[8 * J], a1[8 * J + 1]), pack2(a1[8 * J + 2], a1[8 * J + 3]), pack2(a1[8 * J + 4], a1[8 * J + 5]), pack2(a1[8 * J + 6], a1[8 * J + 7]));
  }
#pragma unroll
  for (int J = 0; J < 5; J++)
    stsm_t(sh + J * 2048, pack2(ah[8 * J], ah[8 * J + 1]), pack2(ah[8 * J + 2], ah[8 * J + 3]), pack2(ah[8 * J + 4], ah[8 * J + 5]), pack2(ah[8 * J + 6], ah[8 * J + 7]));
  proxy_fence();
  bar_sync(1, 256);
  if (W == 0 && leader) {
    const int half = tile & 1, bb = tile >> 1, blk = bb >> 4, b = bb & 15;
    for (int k = 0; k < 5; k++) tma_store2d(&p.out, sb + OFF_B + k * B_SLOT, blk * DM + half * 320 + k * 64, b * SQ);
    asm volatile("cp.async.bulk.commit_group;" ::: "memory");
    asm volatile("cp.async.bulk.wait_group 0;" ::: "memory");
  }
}

__global__ void __launch_bounds__(384, 1) oproj_kernel(const __grid_constant__ Params p) {
  extern __shared__ __align__(1024) char smem_raw[];
  if ((smem_u32(smem_raw) & 0xFFFFFFu) != SB) return;
  constexpr uint32_t sb = SB;
  const uint32_t bars = sb + OFF_BAR;
  if (threadIdx.x == 0) {
    for (int i = 0; i < NSLOT; i++) {
      mbar_init(bars + BAR_FULLA + i * 8, 1); mbar_init(bars + BAR_EMPTYA + i * 8, 2);
      mbar_init(bars + BAR_FULLB + i * 8, 1); mbar_init(bars + BAR_EMPTYB + i * 8, 2);
    }
    asm volatile("fence.mbarrier_init.release.cluster;" ::: "memory");
    proxy_fence();
  }
  __syncthreads();
  const int warp = __shfl_sync(0xffffffffu, threadIdx.x >> 5, 0);
  const int tile = blockIdx.x;
  if (warp >= 8) {
    asm volatile("setmaxnreg.dec.sync.aligned.u32 40;");
    if (warp == 8 && elect_one()) {
      const int half = tile & 1, bb = tile >> 1, blk = bb >> 4;
      const char* og = (const char*)g_o + (size_t)bb * NH * O_ITEM_BYTES;
      int bud = WAIT_BUDGET;
      uint32_t sa = 0, pa = 1, sbi = 0, pb = 1;
#pragma unroll 1
      for (int c = 0; c < 96; c++) {
        mbar_wait(bud, bars + BAR_EMPTYB + sbi * 8, pb);
        mbar_expect(bars + BAR_FULLB + sbi * 8, B_SLOT);
        bulk_load(sb + OFF_B + sbi * B_SLOT, og + (size_t)c * B_SLOT, B_SLOT, bars + BAR_FULLB + sbi * 8);
        mbar_wait(bud, bars + BAR_EMPTYA + sa * 8, pa);
        mbar_expect(bars + BAR_FULLA + sa * 8, OA_SLOT);
        tma3d(sb + OFF_A + sa * OA_SLOT, &p.wo[blk], bars + BAR_FULLA + sa * 8, 0, c * 64, half * 5);
        if (++sa == ONA) { sa = 0; pa ^= 1; }
        if (++sbi == NSLOT) { sbi = 0; pb ^= 1; }
      }
    }
  } else {
    asm volatile("setmaxnreg.inc.sync.aligned.u32 232;");
    if (warp < 4) oproj_consumer<0>(p, sb, tile);
    else oproj_consumer<1>(p, sb, tile);
  }
}

typedef CUresult (*EncodeFn)(CUtensorMap*, CUtensorMapDataType, cuuint32_t, void*, const cuuint64_t*, const cuuint64_t*, const cuuint32_t*,
                             const cuuint32_t*, CUtensorMapInterleave, CUtensorMapSwizzle, CUtensorMapL2promotion, CUtensorMapFloatOOBfill);

void make3d(EncodeFn enc, CUtensorMap* m, const void* ptr, uint64_t rows, uint64_t cols, uint32_t box_rows, uint32_t box_blocks) {
  cuuint64_t gd[3] = {64, rows, cols / 64};
  cuuint64_t gs[2] = {cols * 2, 128};
  cuuint32_t bd[3] = {64, box_rows, box_blocks}, es[3] = {1, 1, 1};
  enc(m, CU_TENSOR_MAP_DATA_TYPE_BFLOAT16, 3, (void*)ptr, gd, gs, bd, es, CU_TENSOR_MAP_INTERLEAVE_NONE, CU_TENSOR_MAP_SWIZZLE_128B,
      CU_TENSOR_MAP_L2_PROMOTION_L2_128B, CU_TENSOR_MAP_FLOAT_OOB_FILL_NONE);
}
void make2d(EncodeFn enc, CUtensorMap* m, const void* ptr, uint64_t rows, uint64_t cols, uint32_t box_rows) {
  cuuint64_t gd[2] = {cols, rows};
  cuuint64_t gs[1] = {cols * 2};
  cuuint32_t bd[2] = {64, box_rows}, es[2] = {1, 1};
  enc(m, CU_TENSOR_MAP_DATA_TYPE_BFLOAT16, 2, (void*)ptr, gd, gs, bd, es, CU_TENSOR_MAP_INTERLEAVE_NONE, CU_TENSOR_MAP_SWIZZLE_128B,
      CU_TENSOR_MAP_L2_PROMOTION_L2_128B, CU_TENSOR_MAP_FLOAT_OOB_FILL_NONE);
}

}

extern "C" void kernel_launch(void* const* d_in, const int* in_sizes, int n_in, void* d_out, int out_size) {
  static EncodeFn enc = nullptr;
  if (!enc) {
    cudaDriverEntryPointQueryResult qr;
    cudaGetDriverEntryPoint("cuTensorMapEncodeTiled", (void**)&enc, cudaEnableDefault, &qr);
    cudaFuncSetAttribute(attn_kernel, cudaFuncAttributeMaxDynamicSharedMemorySize, SMEM_BYTES);
    cudaFuncSetAttribute(oproj_kernel, cudaFuncAttributeMaxDynamicSharedMemorySize, SMEM_BYTES);
  }
  Params p;
  for (int s = 0; s < 2; s++) {
    make2d(enc, &p.x[s], d_in[5 * s + 0], NB * SQ, DM, SQ);
    make3d(enc, &p.k[s], d_in[5 * s + 1], (uint64_t)NB * NH * SK, DH, 64, 3);
    make3d(enc, &p.v[s], d_in[5 * s + 2], (uint64_t)NB * NH * SK, DH, 64, 3);
    make3d(enc, &p.wq[s], d_in[5 * s + 3], DM, NH * DH, 64, 3);
    make3d(enc, &p.wo[s], d_in[5 * s + 4], NH * DH, DM, 64, 5);
    p.kp[s] = (const __nv_bfloat16*)d_in[5 * s + 1];
    p.vp[s] = (const __nv_bfloat16*)d_in[5 * s + 2];
  }
  make2d(enc, &p.out, d_out, NB * SQ, 2 * DM, SQ);
  attn_kernel<<<128, 384, SMEM_BYTES>>>(p);
  oproj_kernel<<<64, 384, SMEM_BYTES>>>(p);
}
```

```cpp
#include <cuda_runtime.h>
#include <cuda_bf16.h>
#include <cuda.h>
#include <stdint.h>

#define DEBUG_TIMEOUT 1

namespace {

constexpr int SQ = 160, DM = 640, NH = 32, SK = 512, DH = 192, NB = 16;
constexpr int NITEMS = 2 * NB * NH;
constexpr int NCTA = 132, N_OCTA = 40, N_G2 = 28, N_G1 = 64, N_ATT = N_G1 + N_G2;
#define ORING 192
#define G2_DELAY 13000
constexpr int A_SLOT = 24576, B_SLOT = 20480, NSLOT = 5;
constexpr int OFF_A = 0;
constexpr int OFF_B = NSLOT * A_SLOT;
constexpr int O_STAGE = 57344, O_AB = 40960, O_NST = 4;
constexpr int OFF_L = O_NST * O_STAGE;
constexpr int OFF_BAR = OFF_L + 160 * 4;
constexpr int SMEM_BYTES = OFF_BAR + 384;
static_assert(OFF_B + NSLOT * B_SLOT <= OFF_L, "smem layout");
constexpr uint32_t SB = 1024;
constexpr uint32_t BARS = SB + OFF_BAR;
constexpr uint32_t BAR_FULLA = BARS, BAR_EMPTYA = BARS + 40, BAR_FULLB = BARS + 80, BAR_EMPTYB = BARS + 120, BAR_XDONE = BARS + 160,
                   BAR_QPART = BARS + 168, BAR_QMAIN1 = BARS + 176, BAR_PFULL = BARS + 184, BAR_PFREE = BARS + 200, BAR_LFULL = BARS + 216,
                   BAR_OFULL = BARS + 224, BAR_GFULL = BARS + 248, BAR_GEMPTY = BARS + 280, BAR_GOUT = BARS + 312;
constexpr int O_ITEM_BYTES = SQ * DH * 2;

struct alignas(64) Params {
  CUtensorMap x[2], wq[2], k[2], v[2], wo[2], out;
  const __nv_bfloat16* kp[2];
  const __nv_bfloat16* vp[2];
};

__device__ uint4 g_o[(size_t)ORING * O_ITEM_BYTES / 16];
__device__ int g_ready[NITEMS];
__device__ int g_done[2 * NH];
__device__ int g_epoch[NCTA];
__device__ int g_bad[NITEMS * 4];

#define TL(id)
__device__ __forceinline__ uint32_t smem_u32(const void* p) { return (uint32_t)__cvta_generic_to_shared(p); }
__device__ __forceinline__ void wg_fence() { asm volatile("wgmma.fence.sync.aligned;" ::: "memory"); }
__device__ __forceinline__ void wg_commit() { asm volatile("wgmma.commit_group.sync.aligned;" ::: "memory"); }
template <int N> __device__ __forceinline__ void wg_wait() { asm volatile("wgmma.wait_group.sync.aligned %0;" ::"n"(N) : "memory"); }
template <int N> __device__ __forceinline__ void reg_fence(float (&d)[N]) {
#pragma unroll
  for (int i = 0; i < N; i++) asm volatile("" : "+f"(d[i])::"memory");
}
template <int N> __device__ __forceinline__ void zero_regs(float (&d)[N]) {
#pragma unroll
  for (int i = 0; i < N; i++) d[i] = 0.f;
}
__device__ __forceinline__ void proxy_fence() { asm volatile("fence.proxy.async.shared::cta;" ::: "memory"); }
__device__ __forceinline__ void mbar_init(uint32_t bar, int cnt) { asm volatile("mbarrier.init.shared::cta.b64 [%0], %1;" ::"r"(bar), "r"(cnt) : "memory"); }
__device__ __forceinline__ void mbar_arrive_if0(uint32_t bar, uint32_t sel) {
  asm volatile("{\n.reg .pred p;\nsetp.eq.u32 p, %1, 0;\n@p mbarrier.arrive.shared::cta.b64 _, [%0];\n}\n" ::"r"(bar), "r"(sel) : "memory");
}
__device__ __forceinline__ void mbar_arrive2_if0(uint32_t bar, uint32_t sel) {
  asm volatile("{\n.reg .pred p;\nsetp.eq.u32 p, %1, 0;\n@p mbarrier.arrive.shared::cta.b64 _, [%0], 2;\n}\n" ::"r"(bar), "r"(sel) : "memory");
}
__device__ __forceinline__ void mbar_expect(uint32_t bar, uint32_t bytes) {
  asm volatile("mbarrier.arrive.expect_tx.shared::cta.b64 _, [%0], %1;" ::"r"(bar), "r"(bytes) : "memory");
}
__device__ __forceinline__ void mbar_wait(int& bud, uint32_t bar, uint32_t parity) {
  asm volatile(
      "{\n.reg .pred p, q;\n"
      "LW:\n"
      "mbarrier.try_wait.parity.shared::cta.b64 p, [%1], %2;\n"
      "@!p add.s32 %0, %0, -1;\n"
      "setp.gt.and.s32 q, %0, 0, !p;\n"
      "@q bra LW;\n}\n" : "+r"(bud) : "r"(bar), "r"(parity) : "memory");
}
constexpr int WAIT_BUDGET = 1 << 20;
__device__ __forceinline__ bool elect_one() {
  uint32_t p;
  asm volatile("{\n.reg .pred p;\nelect.sync _|p, 0xffffffff;\nselp.u32 %0, 1, 0, p;\n}\n" : "=r"(p));
  return p;
}
__device__ __forceinline__ void tma2d(uint32_t dst, const CUtensorMap* m, uint32_t bar, int c0, int c1) {
  asm volatile("cp.async.bulk.tensor.2d.shared::cluster.global.mbarrier::complete_tx::bytes [%0], [%1, {%3, %4}], [%2];"
               ::"r"(dst), "l"(m), "r"(bar), "r"(c0), "r"(c1) : "memory");
}
__device__ __forceinline__ void tma3d(uint32_t dst, const CUtensorMap* m, uint32_t bar, int c0, int c1, int c2) {
  asm volatile("cp.async.bulk.tensor.3d.shared::cluster.global.mbarrier::complete_tx::bytes [%0], [%1, {%3, %4, %5}], [%2];"
               ::"r"(dst), "l"(m), "r"(bar), "r"(c0), "r"(c1), "r"(c2) : "memory");
}
__device__ __forceinline__ void tma3d_hint(uint32_t dst, const CUtensorMap* m, uint32_t bar, int c0, int c1, int c2, uint64_t pol) {
  asm volatile("cp.async.bulk.tensor.3d.shared::cluster.global.mbarrier::complete_tx::bytes.L2::cache_hint [%0], [%1, {%3, %4, %5}], [%2], %6;"
               ::"r"(dst), "l"(m), "r"(bar), "r"(c0), "r"(c1), "r"(c2), "l"(pol) : "memory");
}
__device__ __forceinline__ void bulk_load(uint32_t dst, const void* src, uint32_t bytes, uint32_t bar) {
  asm volatile("cp.async.bulk.shared::cluster.global.mbarrier::complete_tx::bytes [%0], [%1], %2, [%3];"
               ::"r"(dst), "l"(src), "r"(bytes), "r"(bar) : "memory");
}
__device__ __forceinline__ void l2_prefetch(const void* src, uint32_t bytes) {
  asm volatile("cp.async.bulk.prefetch.L2.global [%0], %1;" ::"l"(src), "r"(bytes) : "memory");
}
__device__ __forceinline__ void tma_store2d(const CUtensorMap* m, uint32_t src, int c0, int c1) {
  asm volatile("cp.async.bulk.tensor.2d.global.shared::cta.bulk_group [%0, {%2, %3}], [%1];" ::"l"(m), "r"(src), "r"(c0), "r"(c1) : "memory");
}
__device__ __forceinline__ void bar_sync(int id, int n) { asm volatile("bar.sync %0, %1;" ::"r"(id), "r"(n) : "memory"); }
__device__ __forceinline__ void bar_arrive(int id, int n) { asm volatile("bar.arrive %0, %1;" ::"r"(id), "r"(n) : "memory"); }
__device__ __forceinline__ float ex2(float x) { float y; asm("ex2.approx.ftz.f32 %0, %1;" : "=f"(y) : "f"(x)); return y; }
__device__ __forceinline__ uint32_t pack2(float lo, float hi) { uint32_t r; asm("cvt.rn.bf16x2.f32 %0, %1, %2;" : "=r"(r) : "f"(hi), "f"(lo)); return r; }
__device__ __forceinline__ void stsm_t(uint32_t a, uint32_t r0, uint32_t r1, uint32_t r2, uint32_t r3) {
  asm volatile("stmatrix.sync.aligned.m8n8.x4.trans.shared.b16 [%0], {%1,%2,%3,%4};" ::"r"(a), "r"(r0), "r"(r1), "r"(r2), "r"(r3) : "memory");
}
__device__ __forceinline__ void bulk_store(void* dst, uint32_t src, uint32_t bytes) {
  asm volatile("cp.async.bulk.global.shared::cta.bulk_group [%0], [%1], %2;" ::"l"(dst), "r"(src), "r"(bytes) : "memory");
}
__device__ __forceinline__ void flag_wait(int& bud, const int* p, int target) {
  while (true) {
    int v;
    asm volatile("ld.acquire.gpu.global.s32 %0, [%1];" : "=r"(v) : "l"(p) : "memory");
    if (v - target >= 0 || --bud <= 0) break;
    __nanosleep(64);
  }
}
__device__ __forceinline__ uint32_t lo_sw(uint32_t addr) { return (addr >> 4) | (1u << 16); }
__device__ __forceinline__ uint32_t opaque(uint32_t x) { uint32_t y; asm volatile("mov.u32 %0, %1;" : "=r"(y) : "r"(x)); return y; }

template <int TA, uint32_t OA, uint32_t OB>
__device__ __forceinline__ void mma160(float (&d)[80], uint32_t la, uint32_t lb, int sc) {
  asm volatile(
      "{\n.reg .pred p;\n.reg .b32 a, b;\n.reg .b64 da, db;\nsetp.ne.b32 p, %82, 0;\n"
      "add.u32 a, %80, %84;\nadd.u32 b, %81, %85;\nmov.b64 da, {a, 0x40000040};\nmov.b64 db, {b, 0x40000040};\n"
      "wgmma.mma_async.sync.aligned.m64n160k16.f32.bf16.bf16 {"
      "%0,%1,%2,%3,%4,%5,%6,%7,%8,%9,%10,%11,%12,%13,%14,%15,%16,%17,%18,%19,%20,%21,%22,%23,%24,%25,%26,%27,%28,%29,%30,%31,%32,%33,%34,%35,%36,"
      "%37,%38,%39,%40,%41,%42,%43,%44,%45,%46,%47,%48,%49,%50,%51,%52,%53,%54,%55,%56,%57,%58,%59,%60,%61,%62,%63,%64,%65,%66,%67,%68,%69,%70,%71,"
      "%72,%73,%74,%75,%76,%77,%78,%79"
      "}, da, db, p, 1, 1, %83, 0;\n}\n"
      :
      "+f"(d[0]),"+f"(d[1]),"+f"(d[2]),"+f"(d[3]),"+f"(d[4]),"+f"(d[5]),"+f"(d[6]),"+f"(d[7]),"+f"(d[8]),"+f"(d[9]),"+f"(d[10]),"+f"(d[11]),
      "+f"(d[12]),"+f"(d[13]),"+f"(d[14]),"+f"(d[15]),"+f"(d[16]),"+f"(d[17]),"+f"(d[18]),"+f"(d[19]),"+f"(d[20]),"+f"(d[21]),"+f"(d[22]),
      "+f"(d[23]),"+f"(d[24]),"+f"(d[25]),"+f"(d[26]),"+f"(d[27]),"+f"(d[28]),"+f"(d[29]),"+f"(d[30]),"+f"(d[31]),"+f"(d[32]),"+f"(d[33]),
      "+f"(d[34]),"+f"(d[35]),"+f"(d[36]),"+f"(d[37]),"+f"(d[38]),"+f"(d[39]),"+f"(d[40]),"+f"(d[41]),"+f"(d[42]),"+f"(d[43]),"+f"(d[44]),
      "+f"(d[45]),"+f"(d[46]),"+f"(d[47]),"+f"(d[48]),"+f"(d[49]),"+f"(d[50]),"+f"(d[51]),"+f"(d[52]),"+f"(d[53]),"+f"(d[54]),"+f"(d[55]),
      "+f"(d[56]),"+f"(d[57]),"+f"(d[58]),"+f"(d[59]),"+f"(d[60]),"+f"(d[61]),"+f"(d[62]),"+f"(d[63]),"+f"(d[64]),"+f"(d[65]),"+f"(d[66]),
      "+f"(d[67]),"+f"(d[68]),"+f"(d[69]),"+f"(d[70]),"+f"(d[71]),"+f"(d[72]),"+f"(d[73]),"+f"(d[74]),"+f"(d[75]),"+f"(d[76]),"+f"(d[77]),
      "+f"(d[78]),"+f"(d[79])
      : "r"(la), "r"(lb), "r"(sc), "n"(TA), "n"(OA >> 4), "n"(OB >> 4));
}

template <int TA, uint32_t OA, uint32_t OB>
__device__ __forceinline__ void mma80(float (&d)[40], uint32_t la, uint32_t lb, int sc) {
  asm volatile(
      "{\n.reg .pred p;\n.reg .b32 a, b;\n.reg .b64 da, db;\nsetp.ne.b32 p, %42, 0;\n"
      "add.u32 a, %40, %44;\nadd.u32 b, %41, %45;\nmov.b64 da, {a, 0x40000040};\nmov.b64 db, {b, 0x40000040};\n"
      "wgmma.mma_async.sync.aligned.m64n80k16.f32.bf16.bf16 {"
      "%0,%1,%2,%3,%4,%5,%6,%7,%8,%9,%10,%11,%12,%13,%14,%15,%16,%17,%18,%19,%20,%21,%22,%23,%24,%25,%26,%27,%28,%29,%30,%31,%32,%33,%34,%35,%36,"
      "%37,%38,%39"
      "}, da, db, p, 1, 1, %43, 0;\n}\n"
      :
      "+f"(d[0]),"+f"(d[1]),"+f"(d[2]),"+f"(d[3]),"+f"(d[4]),"+f"(d[5]),"+f"(d[6]),"+f"(d[7]),"+f"(d[8]),"+f"(d[9]),"+f"(d[10]),"+f"(d[11]),
      "+f"(d[12]),"+f"(d[13]),"+f"(d[14]),"+f"(d[15]),"+f"(d[16]),"+f"(d[17]),"+f"(d[18]),"+f"(d[19]),"+f"(d[20]),"+f"(d[21]),"+f"(d[22]),
      "+f"(d[23]),"+f"(d[24]),"+f"(d[25]),"+f"(d[26]),"+f"(d[27]),"+f"(d[28]),"+f"(d[29]),"+f"(d[30]),"+f"(d[31]),"+f"(d[32]),"+f"(d[33]),
      "+f"(d[34]),"+f"(d[35]),"+f"(d[36]),"+f"(d[37]),"+f"(d[38]),"+f"(d[39])
      : "r"(la), "r"(lb), "r"(sc), "n"(TA), "n"(OA >> 4), "n"(OB >> 4));
}

template <int TA, uint32_t OA, uint32_t OB>
__device__ __forceinline__ void mma128(float (&d)[64], uint32_t la, uint32_t lb, int sc) {
  asm volatile(
      "{\n.reg .pred p;\n.reg .b32 a, b;\n.reg .b64 da, db;\nsetp.ne.b32 p, %66, 0;\n"
      "add.u32 a, %64, %68;\nadd.u32 b, %65, %69;\nmov.b64 da, {a, 0x40000040};\nmov.b64 db, {b, 0x40000040};\n"
      "wgmma.mma_async.sync.aligned.m64n128k16.f32.bf16.bf16 {"
      "%0,%1,%2,%3,%4,%5,%6,%7,%8,%9,%10,%11,%12,%13,%14,%15,%16,%17,%18,%19,%20,%21,%22,%23,%24,%25,%26,%27,%28,%29,%30,%31,%32,%33,%34,%35,%36,"
      "%37,%38,%39,%40,%41,%42,%43,%44,%45,%46,%47,%48,%49,%50,%51,%52,%53,%54,%55,%56,%57,%58,%59,%60,%61,%62,%63"
      "}, da, db, p, 1, 1, %67, 0;\n}\n"
      :
      "+f"(d[0]),"+f"(d[1]),"+f"(d[2]),"+f"(d[3]),"+f"(d[4]),"+f"(d[5]),"+f"(d[6]),"+f"(d[7]),"+f"(d[8]),"+f"(d[9]),"+f"(d[10]),"+f"(d[11]),
      "+f"(d[12]),"+f"(d[13]),"+f"(d[14]),"+f"(d[15]),"+f"(d[16]),"+f"(d[17]),"+f"(d[18]),"+f"(d[19]),"+f"(d[20]),"+f"(d[21]),"+f"(d[22]),
      "+f"(d[23]),"+f"(d[24]),"+f"(d[25]),"+f"(d[26]),"+f"(d[27]),"+f"(d[28]),"+f"(d[29]),"+f"(d[30]),"+f"(d[31]),"+f"(d[32]),"+f"(d[33]),
      "+f"(d[34]),"+f"(d[35]),"+f"(d[36]),"+f"(d[37]),"+f"(d[38]),"+f"(d[39]),"+f"(d[40]),"+f"(d[41]),"+f"(d[42]),"+f"(d[43]),"+f"(d[44]),
      "+f"(d[45]),"+f"(d[46]),"+f"(d[47]),"+f"(d[48]),"+f"(d[49]),"+f"(d[50]),"+f"(d[51]),"+f"(d[52]),"+f"(d[53]),"+f"(d[54]),"+f"(d[55]),
      "+f"(d[56]),"+f"(d[57]),"+f"(d[58]),"+f"(d[59]),"+f"(d[60]),"+f"(d[61]),"+f"(d[62]),"+f"(d[63])
      : "r"(la), "r"(lb), "r"(sc), "n"(TA), "n"(OA >> 4), "n"(OB >> 4));
}

template <int TA, uint32_t OA, uint32_t OB>
__device__ __forceinline__ void mma64(float (&d)[32], uint32_t la, uint32_t lb, int sc) {
  asm volatile(
      "{\n.reg .pred p;\n.reg .b32 a, b;\n.reg .b64 da, db;\nsetp.ne.b32 p, %34, 0;\n"
      "add.u32 a, %32, %36;\nadd.u32 b, %33, %37;\nmov.b64 da, {a, 0x40000040};\nmov.b64 db, {b, 0x40000040};\n"
      "wgmma.mma_async.sync.aligned.m64n64k16.f32.bf16.bf16 {"
      "%0,%1,%2,%3,%4,%5,%6,%7,%8,%9,%10,%11,%12,%13,%14,%15,%16,%17,%18,%19,%20,%21,%22,%23,%24,%25,%26,%27,%28,%29,%30,%31"
      "}, da, db, p, 1, 1, %35, 0;\n}\n"
      :
      "+f"(d[0]),"+f"(d[1]),"+f"(d[2]),"+f"(d[3]),"+f"(d[4]),"+f"(d[5]),"+f"(d[6]),"+f"(d[7]),"+f"(d[8]),"+f"(d[9]),"+f"(d[10]),"+f"(d[11]),
      "+f"(d[12]),"+f"(d[13]),"+f"(d[14]),"+f"(d[15]),"+f"(d[16]),"+f"(d[17]),"+f"(d[18]),"+f"(d[19]),"+f"(d[20]),"+f"(d[21]),"+f"(d[22]),
      "+f"(d[23]),"+f"(d[24]),"+f"(d[25]),"+f"(d[26]),"+f"(d[27]),"+f"(d[28]),"+f"(d[29]),"+f"(d[30]),"+f"(d[31])
      : "r"(la), "r"(lb), "r"(sc), "n"(TA), "n"(OA >> 4), "n"(OB >> 4));
}

struct Ring { uint32_t s0, ph0; };
__device__ __forceinline__ void ring_pos(const Ring& r, int i, uint32_t& slot, uint32_t& ph) {
  uint32_t s = opaque(r.s0) + (i % NSLOT);
  uint32_t wrap = s >= NSLOT;
  slot = s - (wrap ? NSLOT : 0);
  ph = r.ph0 ^ ((i / NSLOT) & 1) ^ wrap;
}
__device__ __forceinline__ void ring_advance(Ring& r, int n) {
  uint32_t s, p;
  ring_pos(r, n, s, p);
  r.s0 = s; r.ph0 = p;
}
__host__ __device__ constexpr int idxK(int j) { return j == 0 ? 10 : 9 + 2 * j; }
__host__ __device__ constexpr int idxV(int j) { return j == 7 ? 25 : 12 + 2 * j; }
__host__ __device__ constexpr int xs(int c) { return (int)((0x3402310210ull >> (4 * c)) & 15); }
__host__ __device__ constexpr int xu(int c) { return (int)((0x1021011000ull >> (4 * c)) & 15); }
__host__ __device__ constexpr int xodd(int c) { return xs(c) == 0 || xs(c) == 4; }
__host__ __device__ constexpr bool xrel(int c) { return c <= 3 || c == 5; }

struct Sched { int first, second, n, delay; };
__device__ __forceinline__ Sched get_sched(int cta) {
  if (cta < N_OCTA) return Sched{cta, 0, 1, 0};
  if (cta < N_OCTA + N_G1) return Sched{cta, NCTA + (cta - N_OCTA), 11, 0};
  return Sched{cta, cta + N_ATT, 10, 1};
}
__device__ __forceinline__ int sched_item(const Sched& s, int k) { return k == 0 ? s.first : s.second + (k - 1) * N_ATT; }

template <int W>
__device__ __forceinline__ void mma_main(float (&d)[80], uint32_t aaddr, uint32_t baddr, int acc) {
  const uint32_t la = lo_sw(aaddr), lb = lo_sw(baddr);
  mma160<1, W * 16384 + 0 * 2048, 0 * 32>(d, la, lb, acc);
  mma160<1, W * 16384 + 1 * 2048, 1 * 32>(d, la, lb, 1);
  mma160<1, W * 16384 + 2 * 2048, 2 * 32>(d, la, lb, 1);
  mma160<1, W * 16384 + 3 * 2048, 3 * 32>(d, la, lb, 1);
}
template <int W>
__device__ __forceinline__ void mma_mid(float (&d)[40], uint32_t aaddr, uint32_t baddr, int acc) {
  const uint32_t la = lo_sw(aaddr), lb = lo_sw(baddr);
  mma80<1, 8192 + 0 * 2048, W * 10240 + 0 * 32>(d, la, lb, acc);
  mma80<1, 8192 + 1 * 2048, W * 10240 + 1 * 32>(d, la, lb, 1);
  mma80<1, 8192 + 2 * 2048, W * 10240 + 2 * 32>(d, la, lb, 1);
  mma80<1, 8192 + 3 * 2048, W * 10240 + 3 * 32>(d, la, lb, 1);
}
template <int W>
__device__ __forceinline__ void mma_both(float (&dm)[80], float (&dh)[40], uint32_t aaddr, uint32_t baddr, int acc) {
  mma_mid<W>(dh, aaddr, baddr, acc);
  mma_main<W>(dm, aaddr, baddr, acc);
}
template <int KB>
__device__ __forceinline__ void s_mma(float (&sacc)[80], uint32_t kaddr) {
  const uint32_t la = lo_sw(kaddr), lb = lo_sw(SB + OFF_B);
  mma160<0, KB * 8192 + 0, KB * B_SLOT + 0>(sacc, la, lb, KB != 0);
  mma160<0, KB * 8192 + 32, KB * B_SLOT + 32>(sacc, la, lb, 1);
  mma160<0, KB * 8192 + 64, KB * B_SLOT + 64>(sacc, la, lb, 1);
  mma160<0, KB * 8192 + 96, KB * B_SLOT + 96>(sacc, la, lb, 1);
}
template <int N>
__device__ __forceinline__ void store_scaled(uint32_t addr, const float (&d)[N], float sc) {
#pragma unroll
  for (int J = 0; J < N / 8; J++)
    stsm_t(addr + J * 2048, pack2(d[8 * J] * sc, d[8 * J + 1] * sc), pack2(d[8 * J + 2] * sc, d[8 * J + 3] * sc),
           pack2(d[8 * J + 4] * sc, d[8 * J + 5] * sc), pack2(d[8 * J + 6] * sc, d[8 * J + 7] * sc));
}
template <int N>
__device__ __forceinline__ void store_normed(uint32_t addr, const float (&d)[N], uint32_t laddr) {
#pragma unroll
  for (int J = 0; J < N / 8; J++) {
    float i0, i1, i2, i3;
    asm volatile("ld.shared.v4.f32 {%0,%1,%2,%3}, [%4];" : "=f"(i0), "=f"(i1), "=f"(i2), "=f"(i3) : "r"(laddr + J * 16) : "memory");
    stsm_t(addr + J * 2048, pack2(d[8 * J] * i0, d[8 * J + 1] * i1), pack2(d[8 * J + 2] * i0, d[8 * J + 3] * i1),
           pack2(d[8 * J + 4] * i2, d[8 * J + 5] * i3), pack2(d[8 * J + 6] * i2, d[8 * J + 7] * i3));
  }
}
__device__ __forceinline__ void publish(uint32_t bar, int lane) {
  proxy_fence();
  __syncwarp();
  mbar_arrive_if0(bar, lane);
}

#define A_ADDR(s) (SB + OFF_A + (s) * A_SLOT)
#define B_ADDR(s) (SB + OFF_B + (s) * B_SLOT)
#define WAIT_CHUNK(c, ro, par, sA)                                              \
  uint32_t sA;                                                                  \
  {                                                                             \
    uint32_t pA_;                                                               \
    ring_pos(ring, (ro) + (c), sA, pA_);                                        \
    mbar_wait(bud, BAR_FULLA + sA * 8, pA_);                                    \
    mbar_wait(bud, BAR_FULLB + xs(c) * 8, (xu(c) & 1) ^ (xodd(c) ? (par) : 0)); \
  }
#define RELEASE_CHUNK(c, sA)                                  \
  mbar_arrive_if0(BAR_EMPTYA + (sA) * 8, tid);                \
  if (xrel(c)) mbar_arrive_if0(BAR_EMPTYB + xs(c) * 8, tid);

template <int W>
__device__ __forceinline__ void attn_consumer(int nitems) {
  int bud = WAIT_BUDGET;
  const int tid = threadIdx.x & 127, lane = tid & 31, warp = tid >> 5;
  const uint32_t st_off = ((lane & 7) + 8 * (lane >> 4)) * 128 + (((2 * warp + ((lane >> 3) & 1)) ^ (lane & 7)) << 4);
  const uint32_t laddr = SB + OFF_L + (lane & 3) * 160;
  float om[80], oh[40], sacc[80];
  zero_regs(om); zero_regs(oh); zero_regs(sacc);
  Ring ring{0u, 0u};
  uint32_t par = 0;
  const float qscale = 0.07216878364870322f * 1.4426950408889634f;
  constexpr uint32_t pown = B_ADDR(3 + W), poth = B_ADDR(4 - W);
  TL(0);
  {
    WAIT_CHUNK(0, 0, 0, s0)
    wg_fence();
    mma_both<W>(sacc, oh, A_ADDR(s0), B_ADDR(xs(0)), 0);
    wg_commit();
    WAIT_CHUNK(1, 0, 0, s1)
    wg_fence();
    mma_both<W>(sacc, oh, A_ADDR(s1), B_ADDR(xs(1)), 1);
    wg_commit();
    wg_wait<1>();
    RELEASE_CHUNK(0, s0)
  }
#pragma unroll 1
  for (int it = 0;; it++) {
#pragma unroll
    for (int c = 2; c < (W == 0 ? 10 : 8); c++) {
      WAIT_CHUNK(c, 0, par, sA)
      TL(40 + c);
      wg_fence();
      mma_both<W>(sacc, oh, A_ADDR(sA), B_ADDR(xs(c)), 1);
      wg_commit();
      if (W == 0 && c == 9) bar_arrive(5, 256);
      wg_wait<1>();
      uint32_t sP, pP;
      ring_pos(ring, c - 1, sP, pP);
      RELEASE_CHUNK(c - 1, sP)
    }
    uint32_t sK0, pK0;
    ring_pos(ring, idxK(W), sK0, pK0);
    if (W == 0) {
      wg_wait<0>();
      reg_fence(sacc); reg_fence(oh);
      TL(1);
      uint32_t sP, pP;
      ring_pos(ring, 9, sP, pP);
      RELEASE_CHUNK(9, sP)
      store_scaled(B_ADDR(1) + st_off, oh, qscale);
      mbar_wait(bud, BAR_XDONE, par);
      store_scaled(B_ADDR(0) + st_off, sacc, qscale);
      publish(BAR_QPART, lane);
      TL(2);
      mbar_wait(bud, BAR_FULLA + sK0 * 8, pK0);
      mbar_wait(bud, BAR_QPART, par);
      TL(3);
      wg_fence();
      s_mma<0>(sacc, A_ADDR(sK0));
      s_mma<1>(sacc, A_ADDR(sK0));
      wg_commit();
      mbar_wait(bud, BAR_QMAIN1, par);
      TL(5);
      wg_fence();
      s_mma<2>(sacc, A_ADDR(sK0));
      wg_commit();
    } else {
      wg_wait<0>();
      uint32_t s7, p7;
      ring_pos(ring, 7, s7, p7);
      RELEASE_CHUNK(7, s7)
      mbar_arrive_if0(BAR_XDONE, tid);
      WAIT_CHUNK(8, 0, par, s8)
      WAIT_CHUNK(9, 0, par, s9)
      TL(48);
      bar_sync(5, 256);
      wg_fence();
      mma_mid<1>(oh, A_ADDR(s8), B_ADDR(xs(8)), 1);
      mma_mid<1>(oh, A_ADDR(s9), B_ADDR(xs(9)), 1);
      wg_commit();
      mma_main<1>(sacc, A_ADDR(s8), B_ADDR(xs(8)), 1);
      mma_main<1>(sacc, A_ADDR(s9), B_ADDR(xs(9)), 1);
      wg_commit();
      TL(49);
      wg_wait<1>();
      reg_fence(oh);
      store_scaled(B_ADDR(1) + 10240 + st_off, oh, qscale);
      publish(BAR_QPART, lane);
      wg_wait<0>();
      reg_fence(sacc);
      TL(1);
      RELEASE_CHUNK(8, s8)
      RELEASE_CHUNK(9, s9)
      store_scaled(B_ADDR(2) + st_off, sacc, qscale);
      publish(BAR_QMAIN1, lane);
      TL(2);
      mbar_wait(bud, BAR_QPART, par);
      TL(3);
    }

#pragma unroll
    for (int jj = 0; jj < 4; jj++) {
      const int j = 2 * jj + W;
      uint32_t sK = sK0, pK = pK0, sV2 = 0, pV2 = 0, sV1 = 0, pV1 = 0;
      if (j >= 1) {
        if (jj >= 1) ring_pos(ring, idxK(j), sK, pK);
        if (j >= 2) ring_pos(ring, idxV(j >= 2 ? j - 2 : 0), sV2, pV2);
        ring_pos(ring, idxV(j >= 1 ? j - 1 : 0), sV1, pV1);
        if (j >= 2) mbar_wait(bud, BAR_FULLA + sV2 * 8, pV2);
        mbar_wait(bud, BAR_FULLA + sK * 8, pK);
        TL(4 + jj * 7);
        bar_sync(1 + W, 256);
        wg_fence();
        if (j >= 2) mma_both<W>(om, oh, A_ADDR(sV2), pown, j != 2);
        s_mma<0>(sacc, A_ADDR(sK));
        s_mma<1>(sacc, A_ADDR(sK));
        s_mma<2>(sacc, A_ADDR(sK));
        wg_commit();
        TL(6 + jj * 7);
        mbar_wait(bud, BAR_PFULL + (1 - W) * 8, ((j - 1) >> 1) & 1);
        mbar_wait(bud, BAR_FULLA + sV1 * 8, pV1);
        TL(7 + jj * 7);
        wg_fence();
        mma_both<W>(om, oh, A_ADDR(sV1), poth, j != 1);
        wg_commit();
      }
      bar_arrive(2 - W, 256);
      if (j >= 1) wg_wait<1>(); else wg_wait<0>();
      reg_fence(sacc);
      TL(8 + jj * 7);
      mbar_arrive2_if0(BAR_EMPTYA + sK * 8, tid);
      if (j >= 2) mbar_arrive_if0(BAR_EMPTYA + sV2 * 8, tid);
      if (jj == 3) mbar_arrive_if0(BAR_EMPTYB + tid * 8, tid >= 3);
      if (jj >= 1) mbar_wait(bud, BAR_PFREE + W * 8, (jj - 1) & 1);
      TL(9 + jj * 7);
#pragma unroll
      for (int J = 0; J < 10; J++)
        stsm_t(pown + st_off + J * 2048, pack2(ex2(sacc[8 * J]), ex2(sacc[8 * J + 1])), pack2(ex2(sacc[8 * J + 2]), ex2(sacc[8 * J + 3])),
               pack2(ex2(sacc[8 * J + 4]), ex2(sacc[8 * J + 5])), pack2(ex2(sacc[8 * J + 6]), ex2(sacc[8 * J + 7])));
      if (j >= 1) {
        wg_wait<0>();
        mbar_arrive_if0(BAR_EMPTYA + sV1 * 8, tid);
      }
      publish(BAR_PFULL + W * 8, lane);
      TL(10 + jj * 7);
    }
    uint32_t sV7, pV7;
    ring_pos(ring, idxV(7), sV7, pV7);
    if (W == 0) {
      uint32_t sV6, pV6;
      ring_pos(ring, idxV(6), sV6, pV6);
      mbar_wait(bud, BAR_FULLA + sV6 * 8, pV6);
      bar_sync(1, 256);
      wg_fence();
      mma_both<0>(om, oh, A_ADDR(sV6), pown, 1);
      wg_commit();
      mbar_wait(bud, BAR_FULLA + sV7 * 8, pV7);
      wg_wait<0>();
      mbar_arrive_if0(BAR_EMPTYA + sV6 * 8, tid);
      mbar_wait(bud, BAR_PFULL + 8, 1);
      wg_fence();
      mma_both<0>(om, oh, A_ADDR(sV7), poth, 1);
      wg_commit();
      bar_arrive(6, 256);
    } else {
      mbar_wait(bud, BAR_FULLA + sV7 * 8, pV7);
      bar_sync(6, 256);
      wg_fence();
      mma_both<1>(om, oh, A_ADDR(sV7), pown, 1);
      wg_commit();
    }
    TL(32);
    wg_wait<0>();
    reg_fence(om); reg_fence(oh);
    mbar_arrive_if0(BAR_LFULL, tid);
    TL(33);
    if (it + 1 == nitems) {
      mbar_wait(bud, BAR_LFULL, par);
      TL(34);
      store_normed(A_ADDR(sV7) + W * 10240 + st_off, oh, laddr + W * 80);
      publish(BAR_OFULL + 8, lane);
      store_normed(pown + st_off, om, laddr);
      publish(BAR_OFULL + W * 16, lane);
      TL(35);
      break;
    }
    {
      WAIT_CHUNK(0, 26, par ^ 1, s0)
      wg_fence();
      mma_main<W>(sacc, A_ADDR(s0), B_ADDR(xs(0)), 0);
      wg_commit();
      mbar_wait(bud, BAR_LFULL, par);
      TL(34);
      store_normed(A_ADDR(sV7) + W * 10240 + st_off, oh, laddr + W * 80);
      publish(BAR_OFULL + 8, lane);
      TL(36);
      wg_fence();
      mma_mid<W>(oh, A_ADDR(s0), B_ADDR(xs(0)), 0);
      wg_commit();
      WAIT_CHUNK(1, 26, par ^ 1, s1)
      wg_fence();
      mma_both<W>(sacc, oh, A_ADDR(s1), B_ADDR(xs(1)), 1);
      wg_commit();
      wg_wait<1>();
      RELEASE_CHUNK(0, s0)
      TL(37);
      store_normed(pown + st_off, om, laddr);
      publish(BAR_OFULL + W * 16, lane);
      TL(35);
    }
    TL(0);
    ring_advance(ring, 26);
    par ^= 1;
  }
}

__device__ __forceinline__ uint4 lds128(uint32_t a) {
  uint4 v;
  asm volatile("ld.shared.v4.b32 {%0,%1,%2,%3}, [%4];" : "=r"(v.x), "=r"(v.y), "=r"(v.z), "=r"(v.w) : "r"(a) : "memory");
  return v;
}
__device__ __forceinline__ void acc8(float& s, float& t, const uint4& v) {
  s += __uint_as_float(v.x << 16); t += __uint_as_float(v.x & 0xffff0000u);
  s += __uint_as_float(v.y << 16); t += __uint_as_float(v.y & 0xffff0000u);
  s += __uint_as_float(v.z << 16); t += __uint_as_float(v.z & 0xffff0000u);
  s += __uint_as_float(v.w << 16); t += __uint_as_float(v.w & 0xffff0000u);
}
__device__ __forceinline__ void attn_helper(int hw, const Sched& sc, int epoch) {
  int bud = WAIT_BUDGET;
  const int lane = threadIdx.x & 31, r = lane >> 1;
  const uint32_t base = B_ADDR(3) + (16 * hw + r) * 128 + (lane & 1) * 16;
  const uint32_t a0 = base + ((r & 3) << 5);
  Ring ring{0u, 0u};
  uint32_t par = 0;
#pragma unroll 1
  for (int it = 0; it < sc.n; it++) {
    const int item = sched_item(sc, it);
    float acc[4] = {0.f, 0.f, 0.f, 0.f};
#pragma unroll 1
    for (int j = 0; j < 8; j++) {
      mbar_wait(bud, BAR_PFULL + (j & 1) * 8, (j >> 1) & 1);
      const uint32_t pb = a0 + (j & 1) * B_SLOT;
#pragma unroll
      for (int u = 0; u < 4; u++) {
        if (u < 3 || hw == 0) {
          const uint4 v0 = lds128(pb + u * 6144), v1 = lds128((pb ^ 32) + u * 6144), v2 = lds128((pb ^ 64) + u * 6144), v3 = lds128((pb ^ 96) + u * 6144);
          float s0 = acc[u], t0 = 0.f, s1 = 0.f, t1 = 0.f;
          acc8(s0, t0, v0); acc8(s1, t1, v1); acc8(s0, t0, v2); acc8(s1, t1, v3);
          acc[u] = (s0 + t0) + (s1 + t1);
        }
      }
      __syncwarp();
      mbar_arrive_if0(BAR_PFREE + (j & 1) * 8, lane);
    }
    bool bad = false;
    const uint32_t la = SB + OFF_L + (((r & 7) >> 1) * 40 + 2 * (r >> 3) + (r & 1) + 4 * hw) * 4;
#pragma unroll
    for (int u = 0; u < 4; u++) {
      if (u < 3 || hw == 0) {
        const float l = acc[u] + __shfl_xor_sync(0xffffffffu, acc[u], 1);
        bad |= !(l >= 8.8817841970012523e-16f && l <= 1.125899906842624e15f);
        float inv;
        asm("rcp.approx.ftz.f32 %0, %1;" : "=f"(inv) : "f"(l));
        asm volatile("st.shared.f32 [%0], %1;" ::"r"(la + u * 48), "f"(inv) : "memory");
      }
    }
    __syncwarp();
    mbar_arrive_if0(BAR_LFULL, lane);
    const bool anybad = __any_sync(0xffffffffu, bad);
    uint32_t sV7, pV7;
    ring_pos(ring, idxV(7), sV7, pV7);
    if (lane == 0) {
      g_bad[item * 4 + hw] = anybad;
      if (item >= ORING) flag_wait(bud, &g_done[(item - ORING) >> 4], (epoch + 1) * N_OCTA);
      mbar_wait(bud, BAR_OFULL + hw * 8, par);
      const uint32_t src = hw == 1 ? A_ADDR(sV7) : B_ADDR(3 + (hw >> 1));
      asm volatile("fence.proxy.async.global;" ::: "memory");
      bulk_store((char*)g_o + (size_t)(item % ORING) * O_ITEM_BYTES + hw * B_SLOT, src, B_SLOT);
      asm volatile("cp.async.bulk.commit_group;" ::: "memory");
      asm volatile("cp.async.bulk.wait_group.read 0;" ::: "memory");
      mbar_arrive2_if0(hw == 1 ? BAR_EMPTYA + sV7 * 8 : BAR_EMPTYB + (3 + (hw >> 1)) * 8, 0);
      asm volatile("cp.async.bulk.wait_group 0;" ::: "memory");
      asm volatile("fence.proxy.async.global;" ::: "memory");
      asm volatile("red.release.gpu.global.add.s32 [%0], 1;" ::"l"(&g_ready[item]) : "memory");
    }
    __syncwarp();
    bud = __shfl_sync(0xffffffffu, bud, 0);
    ring_advance(ring, 26);
    par ^= 1;
  }
}

__device__ __forceinline__ void attn_producer(const Params& p, const Sched& sc) {
  int bud = WAIT_BUDGET;
  uint32_t sa = 0, pa = 1, par = 0;
  uint64_t pol;
  asm volatile("createpolicy.fractional.L2::evict_first.b64 %0, 1.0;" : "=l"(pol));
  if (sc.delay) {
    const long long t0 = clock64();
    while (clock64() - t0 < G2_DELAY) __nanosleep(200);
  }
#pragma unroll 1
  for (int it = 0; it < sc.n; it++) {
    const int item = sched_item(sc, it);
    const int blk = item >> 9, h = (item >> 4) & 31, b = item & 15;
    const int row0 = (b * NH + h) * SK;
#pragma unroll
    for (int c = 0; c < 10; c++) {
      mbar_wait(bud, BAR_EMPTYA + sa * 8, pa);
      mbar_expect(BAR_FULLA + sa * 8, A_SLOT);
      tma3d(A_ADDR(sa), &p.wq[blk], BAR_FULLA + sa * 8, 0, c * 64, h * 3);
      if (++sa == NSLOT) { sa = 0; pa ^= 1; }
      mbar_wait(bud, BAR_EMPTYB + xs(c) * 8, 1 ^ (xu(c) & 1) ^ (xodd(c) ? par : 0));
      mbar_expect(BAR_FULLB + xs(c) * 8, B_SLOT);
      tma2d(B_ADDR(xs(c)), &p.x[blk], BAR_FULLB + xs(c) * 8, c * 64, b * SQ);
    }
#pragma unroll 1
    for (int i = 0; i < 16; i++) {
      const bool isK = (i == 0) || ((i & 1) && i < 15);
      const int j = i == 0 ? 0 : (i == 15 ? 7 : (isK ? (i + 1) >> 1 : (i - 2) >> 1));
      mbar_wait(bud, BAR_EMPTYA + sa * 8, pa);
      mbar_expect(BAR_FULLA + sa * 8, A_SLOT);
      tma3d_hint(A_ADDR(sa), isK ? &p.k[blk] : &p.v[blk], BAR_FULLA + sa * 8, 0, row0 + j * 64, 0, pol);
      if (++sa == NSLOT) { sa = 0; pa ^= 1; }
    }
    par ^= 1;
  }
}

template <int W>
__device__ __forceinline__ void oproj_consumer() {
  int bud = WAIT_BUDGET;
  const int tid = threadIdx.x & 127, lane = tid & 31, warp = tid >> 5;
  const uint32_t st_off = ((lane & 7) + 8 * (lane >> 4)) * 128 + (((2 * warp + ((lane >> 3) & 1)) ^ (lane & 7)) << 4);
  float a0[64], a1[64], ah[32];
  zero_regs(a0); zero_regs(a1); zero_regs(ah);
#pragma unroll 1
  for (int blk = 0; blk < 2; blk++) {
    int c3 = 0, step = blk * NH;
#pragma unroll 1
    for (int c = 0; c < 96; c++) {
      const uint32_t st = c & 3;
      mbar_wait(bud, BAR_GFULL + st * 8, (c >> 2) & 1);
      wg_fence();
      const uint32_t la = lo_sw(SB + st * O_STAGE), lb = lo_sw(SB + st * O_STAGE + O_AB);
#define O_STEP(ks, sc)                                                   \
  mma64<1, 2 * 8192 + ks * 2048, W * 8192 + ks * 32>(ah, la, lb, sc);    \
  mma128<1, (W * 3) * 8192 + ks * 2048, ks * 32>(a0, la, lb, sc);        \
  mma128<1, (W * 3 + 1) * 8192 + ks * 2048, ks * 32>(a1, la, lb, sc);
      O_STEP(0, c != 0) O_STEP(1, 1) O_STEP(2, 1) O_STEP(3, 1)
#undef O_STEP
      wg_commit();
      if (++c3 == 3) {
        c3 = 0;
        if (W == 0)
          asm volatile("{\n.reg .pred p;\nsetp.eq.u32 p, %1, 0;\n@p red.relaxed.gpu.global.add.s32 [%0], 1;\n}\n" ::"l"(&g_done[step]), "r"(tid) : "memory");
        TL(step);
        step++;
      }
      wg_wait<1>();
      mbar_arrive_if0(BAR_GEMPTY + ((c - 1) & 3) * 8, tid | (c == 0) | (c == 95));
    }
    wg_wait<0>();
    reg_fence(a0); reg_fence(a1); reg_fence(ah);
    bar_sync(3, 256);
    const uint32_t sg = SB + 2 * O_STAGE + st_off;
    store_scaled(sg + 2 * 16384 + W * 8192, ah, 1.0f);
    store_scaled(sg + (W * 3) * 16384, a0, 1.0f);
    store_scaled(sg + (W * 3 + 1) * 16384, a1, 1.0f);
    publish(BAR_GOUT, lane);
  }
}

__device__ __forceinline__ void oproj_producer(const Params& p, int cta, int epoch) {
  int bud = WAIT_BUDGET;
  const int half = cta & 1, r0 = (cta >> 1) * 128;
  const int b0 = r0 / SQ, off0 = r0 - b0 * SQ, n0 = min(128, SQ - off0), n1 = 128 - n0;
  const int target = (epoch + 1) * 3;
#pragma unroll 1
  for (int step = 0; step < 2 * NH; step++) {
    const int blk = step >> 5, item0 = step * 16 + b0;
    const char* o0 = (const char*)g_o + (size_t)(item0 % ORING) * O_ITEM_BYTES + off0 * 128;
    const char* o1 = (const char*)g_o + (size_t)((item0 + 1) % ORING) * O_ITEM_BYTES;
#pragma unroll 1
    for (int kb = 0; kb < 3; kb++) {
      const int c = step * 3 + kb;
      const uint32_t st = c & 3, dst = SB + st * O_STAGE, bar = BAR_GFULL + st * 8;
      mbar_wait(bud, BAR_GEMPTY + st * 8, ((c >> 2) & 1) ^ 1);
      mbar_expect(bar, O_STAGE);
      tma3d(dst, &p.wo[blk], bar, 0, ((step & 31) * 3 + kb) * 64, half * 5);
      if (kb == 0) {
        flag_wait(bud, &g_ready[item0], target);
        if (n1) flag_wait(bud, &g_ready[item0 + 1], target);
        asm volatile("fence.proxy.async.global;" ::: "memory");
      }
      bulk_load(dst + O_AB, o0 + kb * B_SLOT, n0 * 128, bar);
      if (n1) bulk_load(dst + O_AB + n0 * 128, o1 + kb * B_SLOT, n1 * 128, bar);
    }
  }
}

__device__ __forceinline__ void oproj_storer(const Params& p, int cta) {
  int bud = WAIT_BUDGET;
  const int half = cta & 1, r0 = (cta >> 1) * 128;
#pragma unroll 1
  for (int blk = 0; blk < 2; blk++) {
    mbar_wait(bud, BAR_GOUT, blk);
    for (int k = 0; k < 5; k++) tma_store2d(&p.out, SB + 2 * O_STAGE + k * 16384, blk * DM + half * 320 + k * 64, r0);
    asm volatile("cp.async.bulk.commit_group;" ::: "memory");
    asm volatile("cp.async.bulk.wait_group.read 0;" ::: "memory");
    mbar_arrive2_if0(BAR_GEMPTY + 16, 0);
    mbar_arrive2_if0(BAR_GEMPTY + 24, 0);
  }
  asm volatile("cp.async.bulk.wait_group 0;" ::: "memory");
}

__global__ void __launch_bounds__(384, 1) fused_kernel(const __grid_constant__ Params p) {
  extern __shared__ __align__(1024) char smem_raw[];
  if ((smem_u32(smem_raw) & 0xFFFFFFu) != SB) return;
  const int cta = blockIdx.x;
  const int epoch = g_epoch[cta];
  if (threadIdx.x == 0) {
    for (int i = 0; i < NSLOT; i++) {
      mbar_init(BAR_FULLA + i * 8, 1); mbar_init(BAR_EMPTYA + i * 8, 2);
      mbar_init(BAR_FULLB + i * 8, 1); mbar_init(BAR_EMPTYB + i * 8, 2);
    }
    mbar_init(BAR_XDONE, 1); mbar_init(BAR_QPART, 8); mbar_init(BAR_QMAIN1, 4);
    mbar_init(BAR_PFULL, 4); mbar_init(BAR_PFULL + 8, 4);
    mbar_init(BAR_PFREE, 3); mbar_init(BAR_PFREE + 8, 3);
    mbar_init(BAR_LFULL, 5);
    mbar_init(BAR_OFULL, 4); mbar_init(BAR_OFULL + 8, 8); mbar_init(BAR_OFULL + 16, 4);
    for (int i = 0; i < O_NST; i++) { mbar_init(BAR_GFULL + i * 8, 1); mbar_init(BAR_GEMPTY + i * 8, 2); }
    mbar_init(BAR_GOUT, 8);
    asm volatile("fence.mbarrier_init.release.cluster;" ::: "memory");
    proxy_fence();
  }
  __syncthreads();
  if (threadIdx.x == 0) g_epoch[cta] = epoch + 1;
  const int warp = __shfl_sync(0xffffffffu, threadIdx.x >> 5, 0);
  const Sched sc = get_sched(cta);
  if (warp >= 8) {
    asm volatile("setmaxnreg.dec.sync.aligned.u32 40;");
    if (warp == 8) {
      if (elect_one()) attn_producer(p, sc);
      __syncwarp();
    } else {
      attn_helper(warp - 9, sc, epoch);
    }
    if (cta < N_OCTA) {
      bar_sync(4, 128);
      if (warp == 8) {
        if (elect_one()) oproj_producer(p, cta, epoch);
      } else if (warp == 9) {
        if (elect_one()) oproj_storer(p, cta);
      }
    }
  } else {
    asm volatile("setmaxnreg.inc.sync.aligned.u32 232;");
    if (warp < 4) {
      attn_consumer<0>(sc.n);
      if (cta < N_OCTA) oproj_consumer<0>();
    } else {
      attn_consumer<1>(sc.n);
      if (cta < N_OCTA) oproj_consumer<1>();
    }
  }
}

typedef CUresult (*EncodeFn)(CUtensorMap*, CUtensorMapDataType, cuuint32_t, void*, const cuuint64_t*, const cuuint64_t*, const cuuint32_t*,
                             const cuuint32_t*, CUtensorMapInterleave, CUtensorMapSwizzle, CUtensorMapL2promotion, CUtensorMapFloatOOBfill);

void make3d(EncodeFn enc, CUtensorMap* m, const void* ptr, uint64_t rows, uint64_t cols, uint32_t box_rows, uint32_t box_blocks) {
  cuuint64_t gd[3] = {64, rows, cols / 64};
  cuuint64_t gs[2] = {cols * 2, 128};
  cuuint32_t bd[3] = {64, box_rows, box_blocks}, es[3] = {1, 1, 1};
  enc(m, CU_TENSOR_MAP_DATA_TYPE_BFLOAT16, 3, (void*)ptr, gd, gs, bd, es, CU_TENSOR_MAP_INTERLEAVE_NONE, CU_TENSOR_MAP_SWIZZLE_128B,
      CU_TENSOR_MAP_L2_PROMOTION_L2_128B, CU_TENSOR_MAP_FLOAT_OOB_FILL_NONE);
}
void make2d(EncodeFn enc, CUtensorMap* m, const void* ptr, uint64_t rows, uint64_t cols, uint32_t box_rows) {
  cuuint64_t gd[2] = {cols, rows};
  cuuint64_t gs[1] = {cols * 2};
  cuuint32_t bd[2] = {64, box_rows}, es[2] = {1, 1};
  enc(m, CU_TENSOR_MAP_DATA_TYPE_BFLOAT16, 2, (void*)ptr, gd, gs, bd, es, CU_TENSOR_MAP_INTERLEAVE_NONE, CU_TENSOR_MAP_SWIZZLE_128B,
      CU_TENSOR_MAP_L2_PROMOTION_L2_128B, CU_TENSOR_MAP_FLOAT_OOB_FILL_NONE);
}

}

extern "C" void kernel_launch(void* const* d_in, const int* in_sizes, int n_in, void* d_out, int out_size) {
  static EncodeFn enc = nullptr;
  if (!enc) {
    cudaDriverEntryPointQueryResult qr;
    cudaGetDriverEntryPoint("cuTensorMapEncodeTiled", (void**)&enc, cudaEnableDefault, &qr);
    cudaFuncSetAttribute(fused_kernel, cudaFuncAttributeMaxDynamicSharedMemorySize, SMEM_BYTES);
  }
  Params p;
  for (int s = 0; s < 2; s++) {
    make2d(enc, &p.x[s], d_in[5 * s + 0], NB * SQ, DM, SQ);
    make3d(enc, &p.k[s], d_in[5 * s + 1], (uint64_t)NB * NH * SK, DH, 64, 3);
    make3d(enc, &p.v[s], d_in[5 * s + 2], (uint64_t)NB * NH * SK, DH, 64, 3);
    make3d(enc, &p.wq[s], d_in[5 * s + 3], DM, NH * DH, 64, 3);
    make3d(enc, &p.wo[s], d_in[5 * s + 4], NH * DH, DM, 64, 5);
    p.kp[s] = (const __nv_bfloat16*)d_in[5 * s + 1];
    p.vp[s] = (const __nv_bfloat16*)d_in[5 * s + 2];
  }
  make2d(enc, &p.out, d_out, NB * SQ, 2 * DM, 128);
  fused_kernel<<<NCTA, 384, SMEM_BYTES>>>(p);
}
```

```cpp
#include <cuda_runtime.h>
#include <cuda_bf16.h>
#include <cuda.h>
#include <stdint.h>

#define DEBUG_TIMEOUT 1

namespace {

constexpr int SQ = 160, DM = 640, NH = 32, SK = 512, DH = 192, NB = 16;
constexpr int NITEMS = 2 * NB * NH;
constexpr int NCTA = 132, N_OCTA = 40, N_G2 = 28, N_G1 = 64, N_ATT = N_G1 + N_G2;
#define ORING 192
#define G2_DELAY 13000
constexpr int A_SLOT = 24576, B_SLOT = 20480, NSLOT = 5;
constexpr int OFF_A = 0;
constexpr int OFF_B = NSLOT * A_SLOT;
constexpr int O_STAGE = 57344, O_AB = 40960, O_NST = 4;
constexpr int OFF_L = O_NST * O_STAGE;
constexpr int OFF_BAR = OFF_L + 160 * 4;
constexpr int SMEM_BYTES = OFF_BAR + 384 + 512;
static_assert(OFF_B + NSLOT * B_SLOT <= OFF_L, "smem layout");
constexpr uint32_t SB = 1024;
constexpr uint32_t BARS = SB + OFF_BAR;
constexpr uint32_t BAR_FULLA = BARS, BAR_EMPTYA = BARS + 40, BAR_PMID = BARS + 80, BAR_EMPTYB = BARS + 120, BAR_XDONE = BARS + 160,
                   BAR_QH = BARS + 168, BAR_QM = BARS + 96, BAR_PFULL = BARS + 184, BAR_PFREE = BARS + 200, BAR_LFULL = BARS + 216,
                   BAR_OFULL = BARS + 224, BAR_GFULL = BARS + 248, BAR_GEMPTY = BARS + 280, BAR_GOUT = BARS + 312;
constexpr int O_ITEM_BYTES = SQ * DH * 2;

struct alignas(64) Params {
  CUtensorMap x[2], wq[2], k[2], v[2], wo[2], out;
  const __nv_bfloat16* kp[2];
  const __nv_bfloat16* vp[2];
};

__device__ uint4 g_o[(size_t)ORING * O_ITEM_BYTES / 16];
__device__ int g_ready[NITEMS];
__device__ int g_done[2 * NH];
__device__ int g_epoch[NCTA];
__device__ int g_bad[NITEMS * 4];

#define TLP(id)
#define TL(id)
#define TL_FLUSH()
__device__ __forceinline__ uint32_t smem_u32(const void* p) { return (uint32_t)__cvta_generic_to_shared(p); }
__device__ __forceinline__ void wg_fence() { asm volatile("wgmma.fence.sync.aligned;" ::: "memory"); }
__device__ __forceinline__ void wg_commit() { asm volatile("wgmma.commit_group.sync.aligned;" ::: "memory"); }
template <int N> __device__ __forceinline__ void wg_wait() { asm volatile("wgmma.wait_group.sync.aligned %0;" ::"n"(N) : "memory"); }
template <int N> __device__ __forceinline__ void reg_fence(float (&d)[N]) {
#pragma unroll
  for (int i = 0; i < N; i++) asm volatile("" : "+f"(d[i])::"memory");
}
template <int N> __device__ __forceinline__ void zero_regs(float (&d)[N]) {
#pragma unroll
  for (int i = 0; i < N; i++) d[i] = 0.f;
}
__device__ __forceinline__ void proxy_fence() { asm volatile("fence.proxy.async.shared::cta;" ::: "memory"); }
__device__ __forceinline__ void mbar_init(uint32_t bar, int cnt) { asm volatile("mbarrier.init.shared::cta.b64 [%0], %1;" ::"r"(bar), "r"(cnt) : "memory"); }
__device__ __forceinline__ void mbar_arrive_if0(uint32_t bar, uint32_t sel) {
  asm volatile("{\n.reg .pred p;\nsetp.eq.u32 p, %1, 0;\n@p mbarrier.arrive.shared::cta.b64 _, [%0];\n}\n" ::"r"(bar), "r"(sel) : "memory");
}
__device__ __forceinline__ void mbar_arrive2_if0(uint32_t bar, uint32_t sel) {
  asm volatile("{\n.reg .pred p;\nsetp.eq.u32 p, %1, 0;\n@p mbarrier.arrive.shared::cta.b64 _, [%0], 2;\n}\n" ::"r"(bar), "r"(sel) : "memory");
}
__device__ __forceinline__ void mbar_expect(uint32_t bar, uint32_t bytes) {
  asm volatile("mbarrier.arrive.expect_tx.shared::cta.b64 _, [%0], %1;" ::"r"(bar), "r"(bytes) : "memory");
}
__device__ __forceinline__ void mbar_wait(int& bud, uint32_t bar, uint32_t parity) {
  asm volatile(
      "{\n.reg .pred p, q;\n"
      "LW:\n"
      "mbarrier.try_wait.parity.shared::cta.b64 p, [%1], %2;\n"
      "@!p add.s32 %0, %0, -1;\n"
      "setp.gt.and.s32 q, %0, 0, !p;\n"
      "@q bra LW;\n}\n" : "+r"(bud) : "r"(bar), "r"(parity) : "memory");
}
constexpr int WAIT_BUDGET = 1 << 20;
__device__ __forceinline__ bool elect_one() {
  uint32_t p;
  asm volatile("{\n.reg .pred p;\nelect.sync _|p, 0xffffffff;\nselp.u32 %0, 1, 0, p;\n}\n" : "=r"(p));
  return p;
}
__device__ __forceinline__ void tma2d(uint32_t dst, const CUtensorMap* m, uint32_t bar, int c0, int c1) {
  asm volatile("cp.async.bulk.tensor.2d.shared::cluster.global.mbarrier::complete_tx::bytes [%0], [%1, {%3, %4}], [%2];"
               ::"r"(dst), "l"(m), "r"(bar), "r"(c0), "r"(c1) : "memory");
}
__device__ __forceinline__ void tma3d(uint32_t dst, const CUtensorMap* m, uint32_t bar, int c0, int c1, int c2) {
  asm volatile("cp.async.bulk.tensor.3d.shared::cluster.global.mbarrier::complete_tx::bytes [%0], [%1, {%3, %4, %5}], [%2];"
               ::"r"(dst), "l"(m), "r"(bar), "r"(c0), "r"(c1), "r"(c2) : "memory");
}
__device__ __forceinline__ void tma3d_hint(uint32_t dst, const CUtensorMap* m, uint32_t bar, int c0, int c1, int c2, uint64_t pol) {
  asm volatile("cp.async.bulk.tensor.3d.shared::cluster.global.mbarrier::complete_tx::bytes.L2::cache_hint [%0], [%1, {%3, %4, %5}], [%2], %6;"
               ::"r"(dst), "l"(m), "r"(bar), "r"(c0), "r"(c1), "r"(c2), "l"(pol) : "memory");
}
__device__ __forceinline__ void bulk_load(uint32_t dst, const void* src, uint32_t bytes, uint32_t bar) {
  asm volatile("cp.async.bulk.shared::cluster.global.mbarrier::complete_tx::bytes [%0], [%1], %2, [%3];"
               ::"r"(dst), "l"(src), "r"(bytes), "r"(bar) : "memory");
}
__device__ __forceinline__ void l2_prefetch(const void* src, uint32_t bytes) {
  asm volatile("cp.async.bulk.prefetch.L2.global [%0], %1;" ::"l"(src), "r"(bytes) : "memory");
}
__device__ __forceinline__ void tma_store2d(const CUtensorMap* m, uint32_t src, int c0, int c1) {
  asm volatile("cp.async.bulk.tensor.2d.global.shared::cta.bulk_group [%0, {%2, %3}], [%1];" ::"l"(m), "r"(src), "r"(c0), "r"(c1) : "memory");
}
__device__ __forceinline__ void bar_sync(int id, int n) { asm volatile("bar.sync %0, %1;" ::"r"(id), "r"(n) : "memory"); }
__device__ __forceinline__ void bar_arrive(int id, int n) { asm volatile("bar.arrive %0, %1;" ::"r"(id), "r"(n) : "memory"); }
__device__ __forceinline__ float ex2(float x) { float y; asm("ex2.approx.ftz.f32 %0, %1;" : "=f"(y) : "f"(x)); return y; }
__device__ __forceinline__ uint32_t pack2(float lo, float hi) { uint32_t r; asm("cvt.rn.bf16x2.f32 %0, %1, %2;" : "=r"(r) : "f"(hi), "f"(lo)); return r; }
__device__ __forceinline__ void stsm_t(uint32_t a, uint32_t r0, uint32_t r1, uint32_t r2, uint32_t r3) {
  asm volatile("stmatrix.sync.aligned.m8n8.x4.trans.shared.b16 [%0], {%1,%2,%3,%4};" ::"r"(a), "r"(r0), "r"(r1), "r"(r2), "r"(r3) : "memory");
}
__device__ __forceinline__ void flag_wait(int& bud, const int* p, int target) {
  while (true) {
    int v;
    asm volatile("ld.acquire.gpu.global.s32 %0, [%1];" : "=r"(v) : "l"(p) : "memory");
    if (v - target >= 0 || --bud <= 0) break;
    __nanosleep(64);
  }
}
__device__ __forceinline__ uint32_t lo_sw(uint32_t addr) { return (addr >> 4) | (1u << 16); }
__device__ __forceinline__ uint32_t lo_o(uint32_t addr) { return (addr >> 4) | (8u << 16); }
__device__ __forceinline__ uint32_t opaque(uint32_t x) { uint32_t y; asm volatile("mov.u32 %0, %1;" : "=r"(y) : "r"(x)); return y; }

template <int TA, int TB, uint32_t OA, uint32_t OB>
__device__ __forceinline__ void mma160(float (&d)[80], uint32_t la, uint32_t lb) {
  asm volatile(
      "{\n.reg .pred p;\n.reg .b32 a, b;\n.reg .b64 da, db;\nsetp.eq.b32 p, 0, 0;\n"
      "add.u32 a, %80, %84;\nadd.u32 b, %81, %85;\nmov.b64 da, {a, 0x40000040};\nmov.b64 db, {b, %86};\n"
      "wgmma.mma_async.sync.aligned.m64n160k16.f32.bf16.bf16 {"
      "%0,%1,%2,%3,%4,%5,%6,%7,%8,%9,%10,%11,%12,%13,%14,%15,%16,%17,%18,%19,%20,%21,%22,%23,%24,%25,%26,%27,%28,%29,%30,%31,%32,%33,%34,%35,%36,"
      "%37,%38,%39,%40,%41,%42,%43,%44,%45,%46,%47,%48,%49,%50,%51,%52,%53,%54,%55,%56,%57,%58,%59,%60,%61,%62,%63,%64,%65,%66,%67,%68,%69,%70,%71,"
      "%72,%73,%74,%75,%76,%77,%78,%79"
      "}, da, db, p, 1, 1, %82, %83;\n}\n"
      :
      "+f"(d[0]),"+f"(d[1]),"+f"(d[2]),"+f"(d[3]),"+f"(d[4]),"+f"(d[5]),"+f"(d[6]),"+f"(d[7]),"+f"(d[8]),"+f"(d[9]),"+f"(d[10]),"+f"(d[11]),
      "+f"(d[12]),"+f"(d[13]),"+f"(d[14]),"+f"(d[15]),"+f"(d[16]),"+f"(d[17]),"+f"(d[18]),"+f"(d[19]),"+f"(d[20]),"+f"(d[21]),"+f"(d[22]),
      "+f"(d[23]),"+f"(d[24]),"+f"(d[25]),"+f"(d[26]),"+f"(d[27]),"+f"(d[28]),"+f"(d[29]),"+f"(d[30]),"+f"(d[31]),"+f"(d[32]),"+f"(d[33]),
      "+f"(d[34]),"+f"(d[35]),"+f"(d[36]),"+f"(d[37]),"+f"(d[38]),"+f"(d[39]),"+f"(d[40]),"+f"(d[41]),"+f"(d[42]),"+f"(d[43]),"+f"(d[44]),
      "+f"(d[45]),"+f"(d[46]),"+f"(d[47]),"+f"(d[48]),"+f"(d[49]),"+f"(d[50]),"+f"(d[51]),"+f"(d[52]),"+f"(d[53]),"+f"(d[54]),"+f"(d[55]),
      "+f"(d[56]),"+f"(d[57]),"+f"(d[58]),"+f"(d[59]),"+f"(d[60]),"+f"(d[61]),"+f"(d[62]),"+f"(d[63]),"+f"(d[64]),"+f"(d[65]),"+f"(d[66]),
      "+f"(d[67]),"+f"(d[68]),"+f"(d[69]),"+f"(d[70]),"+f"(d[71]),"+f"(d[72]),"+f"(d[73]),"+f"(d[74]),"+f"(d[75]),"+f"(d[76]),"+f"(d[77]),
      "+f"(d[78]),"+f"(d[79])
      : "r"(la), "r"(lb), "n"(TA), "n"(TB), "n"(OA >> 4), "n"(OB >> 4), "n"(TB ? 0x40 : 0x40000040));
}

template <int TA, int TB, uint32_t OA, uint32_t OB>
__device__ __forceinline__ void mma160z(float (&d)[80], uint32_t la, uint32_t lb) {
  asm volatile(
      "{\n.reg .pred p;\n.reg .b32 a, b;\n.reg .b64 da, db;\nsetp.ne.b32 p, 0, 0;\n"
      "add.u32 a, %80, %84;\nadd.u32 b, %81, %85;\nmov.b64 da, {a, 0x40000040};\nmov.b64 db, {b, %86};\n"
      "wgmma.mma_async.sync.aligned.m64n160k16.f32.bf16.bf16 {"
      "%0,%1,%2,%3,%4,%5,%6,%7,%8,%9,%10,%11,%12,%13,%14,%15,%16,%17,%18,%19,%20,%21,%22,%23,%24,%25,%26,%27,%28,%29,%30,%31,%32,%33,%34,%35,%36,"
      "%37,%38,%39,%40,%41,%42,%43,%44,%45,%46,%47,%48,%49,%50,%51,%52,%53,%54,%55,%56,%57,%58,%59,%60,%61,%62,%63,%64,%65,%66,%67,%68,%69,%70,%71,"
      "%72,%73,%74,%75,%76,%77,%78,%79"
      "}, da, db, p, 1, 1, %82, %83;\n}\n"
      :
      "=f"(d[0]),"=f"(d[1]),"=f"(d[2]),"=f"(d[3]),"=f"(d[4]),"=f"(d[5]),"=f"(d[6]),"=f"(d[7]),"=f"(d[8]),"=f"(d[9]),"=f"(d[10]),"=f"(d[11]),
      "=f"(d[12]),"=f"(d[13]),"=f"(d[14]),"=f"(d[15]),"=f"(d[16]),"=f"(d[17]),"=f"(d[18]),"=f"(d[19]),"=f"(d[20]),"=f"(d[21]),"=f"(d[22]),
      "=f"(d[23]),"=f"(d[24]),"=f"(d[25]),"=f"(d[26]),"=f"(d[27]),"=f"(d[28]),"=f"(d[29]),"=f"(d[30]),"=f"(d[31]),"=f"(d[32]),"=f"(d[33]),
      "=f"(d[34]),"=f"(d[35]),"=f"(d[36]),"=f"(d[37]),"=f"(d[38]),"=f"(d[39]),"=f"(d[40]),"=f"(d[41]),"=f"(d[42]),"=f"(d[43]),"=f"(d[44]),
      "=f"(d[45]),"=f"(d[46]),"=f"(d[47]),"=f"(d[48]),"=f"(d[49]),"=f"(d[50]),"=f"(d[51]),"=f"(d[52]),"=f"(d[53]),"=f"(d[54]),"=f"(d[55]),
      "=f"(d[56]),"=f"(d[57]),"=f"(d[58]),"=f"(d[59]),"=f"(d[60]),"=f"(d[61]),"=f"(d[62]),"=f"(d[63]),"=f"(d[64]),"=f"(d[65]),"=f"(d[66]),
      "=f"(d[67]),"=f"(d[68]),"=f"(d[69]),"=f"(d[70]),"=f"(d[71]),"=f"(d[72]),"=f"(d[73]),"=f"(d[74]),"=f"(d[75]),"=f"(d[76]),"=f"(d[77]),
      "=f"(d[78]),"=f"(d[79])
      : "r"(la), "r"(lb), "n"(TA), "n"(TB), "n"(OA >> 4), "n"(OB >> 4), "n"(TB ? 0x40 : 0x40000040));
}

template <int TA, int TB, uint32_t OA, uint32_t OB>
__device__ __forceinline__ void mma80(float (&d)[40], uint32_t la, uint32_t lb) {
  asm volatile(
      "{\n.reg .pred p;\n.reg .b32 a, b;\n.reg .b64 da, db;\nsetp.eq.b32 p, 0, 0;\n"
      "add.u32 a, %40, %44;\nadd.u32 b, %41, %45;\nmov.b64 da, {a, 0x40000040};\nmov.b64 db, {b, %46};\n"
      "wgmma.mma_async.sync.aligned.m64n80k16.f32.bf16.bf16 {"
      "%0,%1,%2,%3,%4,%5,%6,%7,%8,%9,%10,%11,%12,%13,%14,%15,%16,%17,%18,%19,%20,%21,%22,%23,%24,%25,%26,%27,%28,%29,%30,%31,%32,%33,%34,%35,%36,"
      "%37,%38,%39"
      "}, da, db, p, 1, 1, %42, %43;\n}\n"
      :
      "+f"(d[0]),"+f"(d[1]),"+f"(d[2]),"+f"(d[3]),"+f"(d[4]),"+f"(d[5]),"+f"(d[6]),"+f"(d[7]),"+f"(d[8]),"+f"(d[9]),"+f"(d[10]),"+f"(d[11]),
      "+f"(d[12]),"+f"(d[13]),"+f"(d[14]),"+f"(d[15]),"+f"(d[16]),"+f"(d[17]),"+f"(d[18]),"+f"(d[19]),"+f"(d[20]),"+f"(d[21]),"+f"(d[22]),
      "+f"(d[23]),"+f"(d[24]),"+f"(d[25]),"+f"(d[26]),"+f"(d[27]),"+f"(d[28]),"+f"(d[29]),"+f"(d[30]),"+f"(d[31]),"+f"(d[32]),"+f"(d[33]),
      "+f"(d[34]),"+f"(d[35]),"+f"(d[36]),"+f"(d[37]),"+f"(d[38]),"+f"(d[39])
      : "r"(la), "r"(lb), "n"(TA), "n"(TB), "n"(OA >> 4), "n"(OB >> 4), "n"(TB ? 0x40 : 0x40000040));
}

template <int TA, int TB, uint32_t OA, uint32_t OB>
__device__ __forceinline__ void mma80z(float (&d)[40], uint32_t la, uint32_t lb) {
  asm volatile(
      "{\n.reg .pred p;\n.reg .b32 a, b;\n.reg .b64 da, db;\nsetp.ne.b32 p, 0, 0;\n"
      "add.u32 a, %40, %44;\nadd.u32 b, %41, %45;\nmov.b64 da, {a, 0x40000040};\nmov.b64 db, {b, %46};\n"
      "wgmma.mma_async.sync.aligned.m64n80k16.f32.bf16.bf16 {"
      "%0,%1,%2,%3,%4,%5,%6,%7,%8,%9,%10,%11,%12,%13,%14,%15,%16,%17,%18,%19,%20,%21,%22,%23,%24,%25,%26,%27,%28,%29,%30,%31,%32,%33,%34,%35,%36,"
      "%37,%38,%39"
      "}, da, db, p, 1, 1, %42, %43;\n}\n"
      :
      "=f"(d[0]),"=f"(d[1]),"=f"(d[2]),"=f"(d[3]),"=f"(d[4]),"=f"(d[5]),"=f"(d[6]),"=f"(d[7]),"=f"(d[8]),"=f"(d[9]),"=f"(d[10]),"=f"(d[11]),
      "=f"(d[12]),"=f"(d[13]),"=f"(d[14]),"=f"(d[15]),"=f"(d[16]),"=f"(d[17]),"=f"(d[18]),"=f"(d[19]),"=f"(d[20]),"=f"(d[21]),"=f"(d[22]),
      "=f"(d[23]),"=f"(d[24]),"=f"(d[25]),"=f"(d[26]),"=f"(d[27]),"=f"(d[28]),"=f"(d[29]),"=f"(d[30]),"=f"(d[31]),"=f"(d[32]),"=f"(d[33]),
      "=f"(d[34]),"=f"(d[35]),"=f"(d[36]),"=f"(d[37]),"=f"(d[38]),"=f"(d[39])
      : "r"(la), "r"(lb), "n"(TA), "n"(TB), "n"(OA >> 4), "n"(OB >> 4), "n"(TB ? 0x40 : 0x40000040));
}

template <int TA, int TB, uint32_t OA, uint32_t OB>
__device__ __forceinline__ void mma128r(float (&d)[64], uint32_t la, uint32_t lb, int sc) {
  asm volatile(
      "{\n.reg .pred p;\n.reg .b32 a, b;\n.reg .b64 da, db;\nsetp.ne.b32 p, %71, 0;\n"
      "add.u32 a, %64, %68;\nadd.u32 b, %65, %69;\nmov.b64 da, {a, 0x40000040};\nmov.b64 db, {b, %70};\n"
      "wgmma.mma_async.sync.aligned.m64n128k16.f32.bf16.bf16 {"
      "%0,%1,%2,%3,%4,%5,%6,%7,%8,%9,%10,%11,%12,%13,%14,%15,%16,%17,%18,%19,%20,%21,%22,%23,%24,%25,%26,%27,%28,%29,%30,%31,%32,%33,%34,%35,%36,"
      "%37,%38,%39,%40,%41,%42,%43,%44,%45,%46,%47,%48,%49,%50,%51,%52,%53,%54,%55,%56,%57,%58,%59,%60,%61,%62,%63"
      "}, da, db, p, 1, 1, %66, %67;\n}\n"
      :
      "+f"(d[0]),"+f"(d[1]),"+f"(d[2]),"+f"(d[3]),"+f"(d[4]),"+f"(d[5]),"+f"(d[6]),"+f"(d[7]),"+f"(d[8]),"+f"(d[9]),"+f"(d[10]),"+f"(d[11]),
      "+f"(d[12]),"+f"(d[13]),"+f"(d[14]),"+f"(d[15]),"+f"(d[16]),"+f"(d[17]),"+f"(d[18]),"+f"(d[19]),"+f"(d[20]),"+f"(d[21]),"+f"(d[22]),
      "+f"(d[23]),"+f"(d[24]),"+f"(d[25]),"+f"(d[26]),"+f"(d[27]),"+f"(d[28]),"+f"(d[29]),"+f"(d[30]),"+f"(d[31]),"+f"(d[32]),"+f"(d[33]),
      "+f"(d[34]),"+f"(d[35]),"+f"(d[36]),"+f"(d[37]),"+f"(d[38]),"+f"(d[39]),"+f"(d[40]),"+f"(d[41]),"+f"(d[42]),"+f"(d[43]),"+f"(d[44]),
      "+f"(d[45]),"+f"(d[46]),"+f"(d[47]),"+f"(d[48]),"+f"(d[49]),"+f"(d[50]),"+f"(d[51]),"+f"(d[52]),"+f"(d[53]),"+f"(d[54]),"+f"(d[55]),
      "+f"(d[56]),"+f"(d[57]),"+f"(d[58]),"+f"(d[59]),"+f"(d[60]),"+f"(d[61]),"+f"(d[62]),"+f"(d[63])
      : "r"(la), "r"(lb), "n"(TA), "n"(TB), "n"(OA >> 4), "n"(OB >> 4), "n"(TB ? 0x40 : 0x40000040), "r"(sc));
}

template <int TA, int TB, uint32_t OA, uint32_t OB>
__device__ __forceinline__ void mma64r(float (&d)[32], uint32_t la, uint32_t lb, int sc) {
  asm volatile(
      "{\n.reg .pred p;\n.reg .b32 a, b;\n.reg .b64 da, db;\nsetp.ne.b32 p, %39, 0;\n"
      "add.u32 a, %32, %36;\nadd.u32 b, %33, %37;\nmov.b64 da, {a, 0x40000040};\nmov.b64 db, {b, %38};\n"
      "wgmma.mma_async.sync.aligned.m64n64k16.f32.bf16.bf16 {"
      "%0,%1,%2,%3,%4,%5,%6,%7,%8,%9,%10,%11,%12,%13,%14,%15,%16,%17,%18,%19,%20,%21,%22,%23,%24,%25,%26,%27,%28,%29,%30,%31"
      "}, da, db, p, 1, 1, %34, %35;\n}\n"
      :
      "+f"(d[0]),"+f"(d[1]),"+f"(d[2]),"+f"(d[3]),"+f"(d[4]),"+f"(d[5]),"+f"(d[6]),"+f"(d[7]),"+f"(d[8]),"+f"(d[9]),"+f"(d[10]),"+f"(d[11]),
      "+f"(d[12]),"+f"(d[13]),"+f"(d[14]),"+f"(d[15]),"+f"(d[16]),"+f"(d[17]),"+f"(d[18]),"+f"(d[19]),"+f"(d[20]),"+f"(d[21]),"+f"(d[22]),
      "+f"(d[23]),"+f"(d[24]),"+f"(d[25]),"+f"(d[26]),"+f"(d[27]),"+f"(d[28]),"+f"(d[29]),"+f"(d[30]),"+f"(d[31])
      : "r"(la), "r"(lb), "n"(TA), "n"(TB), "n"(OA >> 4), "n"(OB >> 4), "n"(TB ? 0x40 : 0x40000040), "r"(sc));
}

struct Ring { uint32_t s0, ph0; };
__device__ __forceinline__ void ring_pos(const Ring& r, int i, uint32_t& slot, uint32_t& ph) {
  uint32_t s = opaque(r.s0) + (i % NSLOT);
  uint32_t wrap = s >= NSLOT;
  slot = s - (wrap ? NSLOT : 0);
  ph = r.ph0 ^ ((i / NSLOT) & 1) ^ wrap;
}
__device__ __forceinline__ void ring_advance(Ring& r, int n) {
  uint32_t s, p;
  ring_pos(r, n, s, p);
  r.s0 = s; r.ph0 = p;
}
__host__ __device__ constexpr int idxK(int j) { return j == 0 ? 10 : 9 + 2 * j; }
__host__ __device__ constexpr int idxV(int j) { return j == 7 ? 25 : 12 + 2 * j; }
__host__ __device__ constexpr int xs(int c) { return c % NSLOT; }

struct Sched { int first, second, n, delay; };
__device__ __forceinline__ Sched get_sched(int cta) {
  if (cta < N_OCTA) return Sched{cta, 0, 1, 0};
  if (cta < N_OCTA + N_G1) return Sched{cta, NCTA + (cta - N_OCTA), 11, 0};
  return Sched{cta, cta + N_ATT, 10, 1};
}
__device__ __forceinline__ int sched_item(const Sched& s, int k) { return k == 0 ? s.first : s.second + (k - 1) * N_ATT; }

template <int W, bool ACC>
__device__ __forceinline__ void mma_main(float (&d)[80], uint32_t aaddr, uint32_t baddr) {
  const uint32_t la = lo_sw(aaddr), lb = lo_sw(baddr);
  if (ACC) mma160<1, 0, W * 16384, 0>(d, la, lb); else mma160z<1, 0, W * 16384, 0>(d, la, lb);
  mma160<1, 0, W * 16384 + 1 * 2048, 1 * 32>(d, la, lb);
  mma160<1, 0, W * 16384 + 2 * 2048, 2 * 32>(d, la, lb);
  mma160<1, 0, W * 16384 + 3 * 2048, 3 * 32>(d, la, lb);
}
template <int W, bool ACC>
__device__ __forceinline__ void mma_mid(float (&d)[40], uint32_t aaddr, uint32_t baddr) {
  const uint32_t la = lo_sw(aaddr), lb = lo_sw(baddr);
  if (ACC) mma80<1, 0, 8192, W * 10240>(d, la, lb); else mma80z<1, 0, 8192, W * 10240>(d, la, lb);
  mma80<1, 0, 8192 + 1 * 2048, W * 10240 + 1 * 32>(d, la, lb);
  mma80<1, 0, 8192 + 2 * 2048, W * 10240 + 2 * 32>(d, la, lb);
  mma80<1, 0, 8192 + 3 * 2048, W * 10240 + 3 * 32>(d, la, lb);
}
template <int W, bool ACC>
__device__ __forceinline__ void mma_both(float (&dm)[80], float (&dh)[40], uint32_t aaddr, uint32_t baddr) {
  mma_mid<W, ACC>(dh, aaddr, baddr);
  mma_main<W, ACC>(dm, aaddr, baddr);
}
template <int KB, bool ACC>
__device__ __forceinline__ void s_mma(float (&sacc)[80], uint32_t kaddr) {
  const uint32_t la = lo_sw(kaddr), lb = lo_sw(SB + OFF_B);
  if (ACC) mma160<0, 0, KB * 8192, KB * B_SLOT>(sacc, la, lb); else mma160z<0, 0, KB * 8192, KB * B_SLOT>(sacc, la, lb);
  mma160<0, 0, KB * 8192 + 32, KB * B_SLOT + 32>(sacc, la, lb);
  mma160<0, 0, KB * 8192 + 64, KB * B_SLOT + 64>(sacc, la, lb);
  mma160<0, 0, KB * 8192 + 96, KB * B_SLOT + 96>(sacc, la, lb);
}
template <int N>
__device__ __forceinline__ void store_scaled(uint32_t addr, const float (&d)[N], float sc) {
#pragma unroll
  for (int J = 0; J < N / 8; J++)
    stsm_t(addr + J * 2048, pack2(d[8 * J] * sc, d[8 * J + 1] * sc), pack2(d[8 * J + 2] * sc, d[8 * J + 3] * sc),
           pack2(d[8 * J + 4] * sc, d[8 * J + 5] * sc), pack2(d[8 * J + 6] * sc, d[8 * J + 7] * sc));
}
__device__ __forceinline__ float4 lds_f4(uint32_t a) {
  float4 v;
  asm volatile("ld.shared.v4.f32 {%0,%1,%2,%3}, [%4];" : "=f"(v.x), "=f"(v.y), "=f"(v.z), "=f"(v.w) : "r"(a) : "memory");
  return v;
}
__device__ __forceinline__ void norm_pack(uint32_t* p, const float* d, const float4& i) {
  p[0] = pack2(d[0] * i.x, d[1] * i.y); p[1] = pack2(d[4] * i.z, d[5] * i.w);
  p[2] = pack2(d[2] * i.x, d[3] * i.y); p[3] = pack2(d[6] * i.z, d[7] * i.w);
  asm volatile("" : "+r"(p[0]), "+r"(p[1]), "+r"(p[2]), "+r"(p[3])::"memory");
}
template <int W>
__device__ __forceinline__ void pack_first(uint32_t (&pk)[60], const float (&om)[80], const float (&oh)[40], uint32_t laddr) {
  float4 n0 = lds_f4(laddr + W * 80), n1 = lds_f4(laddr + W * 80 + 16);
#pragma unroll
  for (int J = 0; J < 5; J++) {
    const float4 i = n0;
    n0 = n1;
    if (J + 2 < 5) n1 = lds_f4(laddr + W * 80 + (J + 2) * 16);
    norm_pack(&pk[20 + 4 * J], &om[8 * (5 * W + J)], i);
    norm_pack(&pk[4 * J], &oh[8 * J], i);
  }
}
template <int W>
__device__ __forceinline__ void pack_second(uint32_t (&pk)[60], const float (&om)[80], uint32_t laddr) {
  float4 n0 = lds_f4(laddr + (1 - W) * 80), n1 = lds_f4(laddr + (1 - W) * 80 + 16);
#pragma unroll
  for (int J = 0; J < 5; J++) {
    const float4 i = n0;
    n0 = n1;
    if (J + 2 < 5) n1 = lds_f4(laddr + (1 - W) * 80 + (J + 2) * 16);
    norm_pack(&pk[40 + 4 * J], &om[8 * (5 * (1 - W) + J)], i);
  }
}
template <int W, int G0, int G1>
__device__ __forceinline__ void store_groups(char* op, const uint32_t (&pk)[60], uint32_t on) {
#pragma unroll
  for (int G = G0; G < G1; G++) {
    const int off = (G < 5 ? 1 : 2 * W) * B_SLOT + (5 * (G < 10 ? W : 1 - W) + G % 5) * 2048;
    asm volatile("{\n.reg .pred p;\nsetp.ne.u32 p, %5, 0;\n@p st.global.v2.b32 [%0], {%1, %2};\n@p st.global.v2.b32 [%0+128], {%3, %4};\n}\n"
                 ::"l"(op + off), "r"(pk[4 * G]), "r"(pk[4 * G + 1]), "r"(pk[4 * G + 2]), "r"(pk[4 * G + 3]), "r"(on) : "memory");
  }
}
__device__ __forceinline__ void publish_generic(uint32_t bar, int lane) {
  __syncwarp();
  mbar_arrive_if0(bar, lane);
}
__device__ __forceinline__ void publish(uint32_t bar, int lane) {
  proxy_fence();
  __syncwarp();
  mbar_arrive_if0(bar, lane);
}

#define A_ADDR(s) (SB + OFF_A + (s) * A_SLOT)
#define B_ADDR(s) (SB + OFF_B + (s) * B_SLOT)
#define WAIT_CHUNK(c, ro, sA)                \
  uint32_t sA;                               \
  {                                          \
    uint32_t pA_;                            \
    ring_pos(ring, (ro) + (c), sA, pA_);     \
    mbar_wait(bud, BAR_FULLA + sA * 8, pA_); \
  }
#define RELEASE_CHUNK(c, sA)                                  \
  mbar_arrive_if0(BAR_EMPTYA + (sA) * 8, tid);                \
  if ((c) < NSLOT) mbar_arrive_if0(BAR_EMPTYB + xs(c) * 8, tid);

template <int W>
__device__ __forceinline__ void attn_consumer(const Sched& sc) {
  int bud = WAIT_BUDGET;
  const int tid = threadIdx.x & 127, lane = tid & 31, warp = tid >> 5;
  const uint32_t st_off = ((lane & 7) + 8 * (lane >> 4)) * 128 + (((2 * warp + ((lane >> 3) & 1)) ^ (lane & 7)) << 4);
  const uint32_t laddr = SB + OFF_L + (lane & 3) * 160;
  const uint32_t o_off = ((lane & 3) >> 1) * 1024 + warp * 256 + (lane >> 2) * 16 + (lane & 1) * 8;
  float om[80], oh[40], sacc[80];
  uint32_t pk[60];
#pragma unroll
  for (int i = 0; i < 60; i++) pk[i] = 0;
  char* op = (char*)g_o;
  Ring ring{0u, 0u};
  uint32_t par = 0;
  const float qscale = 0.07216878364870322f * 1.4426950408889634f;
  constexpr uint32_t pown = B_ADDR(3 + W), poth = B_ADDR(4 - W);
  TL(0);
  {
    WAIT_CHUNK(0, 0, s0)
    wg_fence();
    mma_both<W, false>(sacc, oh, A_ADDR(s0), B_ADDR(xs(0)));
    wg_commit();
    WAIT_CHUNK(1, 0, s1)
    wg_fence();
    mma_both<W, true>(sacc, oh, A_ADDR(s1), B_ADDR(xs(1)));
    wg_commit();
    wg_wait<1>();
    RELEASE_CHUNK(0, s0)
  }
#pragma unroll 1
  for (int it = 0;; it++) {
#pragma unroll
    for (int c = 2; c < 8; c++) {
      WAIT_CHUNK(c, 0, sA)
      TL(40 + c);
      wg_fence();
      mma_both<W, true>(sacc, oh, A_ADDR(sA), B_ADDR(xs(c)));
      wg_commit();
      if (c == 2) store_groups<W, 0, 3>(op, pk, it);
      if (c == 3) store_groups<W, 3, 6>(op, pk, it);
      if (c == 4) store_groups<W, 6, 9>(op, pk, it);
      if (c == 5) store_groups<W, 9, 12>(op, pk, it);
      if (c == 6) {
        store_groups<W, 12, 15>(op, pk, it);
        __syncwarp();
        mbar_arrive_if0(BAR_OFULL, lane | (it == 0));
      }
      wg_wait<1>();
      uint32_t sP, pP;
      ring_pos(ring, c - 1, sP, pP);
      RELEASE_CHUNK(c - 1, sP)
    }
    uint32_t sK0, pK0, s7, p7;
    ring_pos(ring, idxK(W), sK0, pK0);
    ring_pos(ring, 7, s7, p7);
    if (W == 1) {
      wg_wait<0>();
      RELEASE_CHUNK(7, s7)
      mbar_arrive_if0(BAR_XDONE, tid);
    }
    WAIT_CHUNK(8, 0, s8)
    WAIT_CHUNK(9, 0, s9)
    TL(48);
    if (W == 1) bar_sync(5, 256);
    wg_fence();
    mma_mid<W, true>(oh, A_ADDR(s8), B_ADDR(xs(8)));
    mma_mid<W, true>(oh, A_ADDR(s9), B_ADDR(xs(9)));
    wg_commit();
    mma_main<W, true>(sacc, A_ADDR(s8), B_ADDR(xs(8)));
    mma_main<W, true>(sacc, A_ADDR(s9), B_ADDR(xs(9)));
    wg_commit();
    if (W == 0) bar_arrive(5, 256);
    TL(49);
    wg_wait<1>();
    reg_fence(oh);
    if (W == 0) {
      RELEASE_CHUNK(7, s7)
      mbar_arrive_if0(BAR_XDONE, tid);
    }
    mbar_wait(bud, BAR_XDONE, par);
    store_scaled(B_ADDR(1) + W * 10240 + st_off, oh, qscale);
    publish(BAR_QH, lane);
    if (W == 0) mbar_wait(bud, BAR_FULLA + sK0 * 8, pK0);
    wg_wait<0>();
    reg_fence(sacc);
    TL(1);
    RELEASE_CHUNK(8, s8)
    RELEASE_CHUNK(9, s9)
    store_scaled(B_ADDR(2 * W) + st_off, sacc, qscale);
    TL(2);
    if (W == 0) {
      mbar_wait(bud, BAR_QH, par);
      wg_fence();
      s_mma<1, false>(sacc, A_ADDR(sK0));
      wg_commit();
      TL(3);
      publish(BAR_QM, lane);
      mbar_wait(bud, BAR_QM, par);
      wg_fence();
      s_mma<0, true>(sacc, A_ADDR(sK0));
      wg_commit();
      mbar_wait(bud, BAR_QM + 8, par);
      TL(5);
      wg_fence();
      s_mma<2, true>(sacc, A_ADDR(sK0));
      wg_commit();
    } else {
      publish(BAR_QM + 8, lane);
      TL(3);
    }

#pragma unroll
    for (int jj = 0; jj < 4; jj++) {
      const int j = 2 * jj + W;
      uint32_t sK = sK0, pK = pK0, sV2 = 0, pV2 = 0, sV1 = 0, pV1 = 0;
      if (j >= 1) {
        if (jj >= 1) ring_pos(ring, idxK(j), sK, pK);
        if (j >= 2) ring_pos(ring, idxV(j >= 2 ? j - 2 : 0), sV2, pV2);
        ring_pos(ring, idxV(j >= 1 ? j - 1 : 0), sV1, pV1);
        if (j >= 2) mbar_wait(bud, BAR_FULLA + sV2 * 8, pV2); else mbar_wait(bud, BAR_FULLA + sK * 8, pK);
        bar_sync(1 + W, 256);
        wg_fence();
        if (j >= 2) {
          if (j == 2) mma_both<W, false>(om, oh, A_ADDR(sV2), pown); else mma_both<W, true>(om, oh, A_ADDR(sV2), pown);
          mbar_wait(bud, BAR_FULLA + sK * 8, pK);
          wg_fence();
        }
        TL(4 + jj * 7);
        s_mma<0, false>(sacc, A_ADDR(sK));
        s_mma<1, true>(sacc, A_ADDR(sK));
        s_mma<2, true>(sacc, A_ADDR(sK));
        wg_commit();
        TL(6 + jj * 7);
        mbar_wait(bud, BAR_FULLA + sV1 * 8, pV1);
        if (jj >= 1) mbar_wait(bud, BAR_PFREE + W * 8, (jj - 1) & 1);
        mbar_wait(bud, BAR_PFULL + (1 - W) * 8, ((j - 1) >> 1) & 1);
        TL(7 + jj * 7);
        wg_fence();
        if (j == 1) mma_both<W, false>(om, oh, A_ADDR(sV1), poth); else mma_both<W, true>(om, oh, A_ADDR(sV1), poth);
        wg_commit();
      }
      bar_arrive(2 - W, 256);
      if (j >= 1) wg_wait<1>(); else wg_wait<0>();
      reg_fence(sacc);
      TL(8 + jj * 7);
      mbar_arrive2_if0(BAR_EMPTYA + sK * 8, tid);
      if (j >= 2) mbar_arrive_if0(BAR_EMPTYA + sV2 * 8, tid);
      if (jj == 3) mbar_arrive_if0(BAR_EMPTYB + tid * 8, tid >= 3);
#pragma unroll
      for (int J = 0; J < 10; J++) {
        stsm_t(pown + st_off + J * 2048, pack2(ex2(sacc[8 * J]), ex2(sacc[8 * J + 1])), pack2(ex2(sacc[8 * J + 2]), ex2(sacc[8 * J + 3])),
               pack2(ex2(sacc[8 * J + 4]), ex2(sacc[8 * J + 5])), pack2(ex2(sacc[8 * J + 6]), ex2(sacc[8 * J + 7])));
        if (j == 7 && (J == 2 || J == 5)) publish_generic(BAR_PMID + (J / 3) * 8, lane);
      }
      if (j >= 1) {
        wg_wait<0>();
        mbar_arrive_if0(BAR_EMPTYA + sV1 * 8, tid);
      }
      publish(BAR_PFULL + W * 8, lane);
      TL(10 + jj * 7);
    }
    uint32_t sV7, pV7;
    ring_pos(ring, idxV(7), sV7, pV7);
    if (W == 0) {
      uint32_t sV6, pV6;
      ring_pos(ring, idxV(6), sV6, pV6);
      mbar_wait(bud, BAR_FULLA + sV6 * 8, pV6);
      bar_sync(1, 256);
      wg_fence();
      mma_both<0, true>(om, oh, A_ADDR(sV6), pown);
      wg_commit();
      mbar_wait(bud, BAR_FULLA + sV7 * 8, pV7);
      wg_wait<0>();
      mbar_arrive_if0(BAR_EMPTYA + sV6 * 8, tid);
      mbar_wait(bud, BAR_PFULL + 8, 1);
      wg_fence();
      mma_both<0, true>(om, oh, A_ADDR(sV7), poth);
      wg_commit();
      bar_arrive(6, 256);
    } else {
      mbar_wait(bud, BAR_FULLA + sV7 * 8, pV7);
      bar_sync(6, 256);
    }
    TL(32);
    op = (char*)g_o + (size_t)(sched_item(sc, it) % ORING) * O_ITEM_BYTES + o_off;
    if (it + 1 == sc.n) {
      if (W == 1) {
        wg_fence();
        mma_both<1, true>(om, oh, A_ADDR(sV7), pown);
        wg_commit();
      }
      wg_wait<0>();
      reg_fence(om); reg_fence(oh);
      TL(33);
      mbar_wait(bud, BAR_LFULL, par);
      TL(34);
      pack_first<W>(pk, om, oh, laddr);
      store_groups<W, 0, 10>(op, pk, 1);
      pack_second<W>(pk, om, laddr);
      store_groups<W, 10, 15>(op, pk, 1);
      publish_generic(BAR_OFULL, lane);
      TL(35);
      TL_FLUSH();
      break;
    }
    {
      if (W == 1) {
        wg_fence();
        mma_both<1, true>(om, oh, A_ADDR(sV7), pown);
        wg_commit();
      }
      WAIT_CHUNK(0, 26, s0)
      WAIT_CHUNK(1, 26, s1)
      if (W == 0) {
        wg_wait<0>();
        reg_fence(om); reg_fence(oh);
        TL(33);
        wg_fence();
        mma_main<W, false>(sacc, A_ADDR(s0), B_ADDR(xs(0)));
        wg_commit();
      } else {
        wg_fence();
        mma_main<W, false>(sacc, A_ADDR(s0), B_ADDR(xs(0)));
        mma_main<W, true>(sacc, A_ADDR(s1), B_ADDR(xs(1)));
        wg_commit();
        wg_wait<1>();
        reg_fence(om); reg_fence(oh);
        TL(33);
      }
      mbar_arrive_if0(BAR_EMPTYA + sV7 * 8, tid);
      mbar_wait(bud, BAR_LFULL, par);
      mbar_arrive_if0(BAR_EMPTYB + 24 + tid * 8, tid >= 2);
      TL(34);
      pack_first<W>(pk, om, oh, laddr);
      TL(36);
      wg_fence();
      mma_mid<W, false>(oh, A_ADDR(s0), B_ADDR(xs(0)));
      wg_commit();
      mma_mid<W, true>(oh, A_ADDR(s1), B_ADDR(xs(1)));
      if (W == 0) mma_main<W, true>(sacc, A_ADDR(s1), B_ADDR(xs(1)));
      wg_commit();
      TL(37);
      pack_second<W>(pk, om, laddr);
      TL(38);
      wg_wait<1>();
      RELEASE_CHUNK(0, s0)
      TL(35);
    }
    TL_FLUSH();
    TL(0);
    ring_advance(ring, 26);
    par ^= 1;
  }
}

__device__ __forceinline__ uint4 lds128(uint32_t a) {
  uint4 v;
  asm volatile("ld.shared.v4.b32 {%0,%1,%2,%3}, [%4];" : "=r"(v.x), "=r"(v.y), "=r"(v.z), "=r"(v.w) : "r"(a) : "memory");
  return v;
}
__device__ __forceinline__ void acc2(float& s, float& t, uint32_t w) {
  s += __uint_as_float(w << 16);
  t += __uint_as_float(w & 0xffff0000u);
}
__device__ __forceinline__ uint32_t badd2(uint32_t a, uint32_t b) { uint32_t r; asm("add.rn.bf16x2 %0, %1, %2;" : "=r"(r) : "r"(a), "r"(b)); return r; }
__device__ __forceinline__ void sum_unit(float& acc, uint32_t pb) {
  const uint4 v0 = lds128(pb), v1 = lds128(pb ^ 32), v2 = lds128(pb ^ 64), v3 = lds128(pb ^ 96);
  const uint32_t w0 = badd2(v0.x, v0.y), w1 = badd2(v0.z, v0.w);
  float s0 = acc + __uint_as_float(w0 << 16), t0 = __uint_as_float(w0 & 0xffff0000u);
  float s1 = __uint_as_float(w1 << 16), t1 = __uint_as_float(w1 & 0xffff0000u);
  acc2(s0, t0, badd2(v1.x, v1.y)); acc2(s1, t1, badd2(v1.z, v1.w));
  acc2(s0, t0, badd2(v2.x, v2.y)); acc2(s1, t1, badd2(v2.z, v2.w));
  acc2(s0, t0, badd2(v3.x, v3.y)); acc2(s1, t1, badd2(v3.z, v3.w));
  acc = (s0 + t0) + (s1 + t1);
}
__device__ __forceinline__ void attn_helper(int hw, const Sched& sc, int epoch) {
  int bud = WAIT_BUDGET;
  const int lane = threadIdx.x & 31, r = lane >> 1;
  const uint32_t a0 = B_ADDR(3) + (16 * hw + r) * 128 + (lane & 1) * 16 + ((r & 3) << 5);
  uint32_t par = 0;
#pragma unroll 1
  for (int it = 0; it < sc.n; it++) {
    const int item = sched_item(sc, it);
    float acc[4] = {0.f, 0.f, 0.f, 0.f};
#pragma unroll 1
    for (int j = 0; j < 8; j++) {
      const uint32_t pb = a0 + (j & 1) * B_SLOT, bfull = BAR_PFULL + (j & 1) * 8, pfull = (j >> 1) & 1;
      mbar_wait(bud, j == 7 ? BAR_PMID : bfull, j == 7 ? par : pfull);
      sum_unit(acc[0], pb);
      if (j == 7) mbar_wait(bud, BAR_PMID + 8, par);
      sum_unit(acc[1], pb + 6144);
      if (j == 7) mbar_wait(bud, bfull, pfull);
      sum_unit(acc[2], pb + 2 * 6144);
      if (hw == 0) sum_unit(acc[3], pb + 3 * 6144);
      __syncwarp();
      mbar_arrive_if0(BAR_PFREE + (j & 1) * 8, lane);
      if (j == 5 && hw == 2 && item >= ORING) flag_wait(bud, &g_done[(item - ORING) >> 4], (epoch + 1) * N_OCTA);
    }
    bool bad = false;
    const uint32_t la = SB + OFF_L + (((r & 7) >> 1) * 40 + 2 * (r >> 3) + (r & 1) + 4 * hw) * 4;
#pragma unroll
    for (int u = 0; u < 4; u++) {
      const float l = acc[u] + __shfl_xor_sync(0xffffffffu, acc[u], 1);
      if (u < 3 || hw == 0) {
        bad |= !(l >= 8.8817841970012523e-16f && l <= 1.125899906842624e15f);
        float inv;
        asm("rcp.approx.ftz.f32 %0, %1;" : "=f"(inv) : "f"(l));
        asm volatile("st.shared.f32 [%0], %1;" ::"r"(la + u * 48), "f"(inv) : "memory");
      }
    }
    publish_generic(BAR_LFULL, lane);
    if (lane == 0) TLP(40 + hw * 4);
    const bool anybad = __any_sync(0xffffffffu, bad);
    if (lane == 0) g_bad[item * 4 + hw] = anybad;
    if (hw == 1) {
      mbar_wait(bud, BAR_OFULL, par);
      if (lane == 0) {
        TLP(41 + hw * 4);
        __threadfence();
        asm volatile("fence.proxy.async.global;" ::: "memory");
        asm volatile("red.release.gpu.global.add.s32 [%0], 1;" ::"l"(&g_ready[item]) : "memory");
        TLP(42 + hw * 4);
      }
      __syncwarp();
    }
    par ^= 1;
  }
}

__device__ __forceinline__ void attn_producer(const Params& p, const Sched& sc) {
  int bud = WAIT_BUDGET;
  uint32_t sa = 0, pa = 1;
  uint64_t pol;
  asm volatile("createpolicy.fractional.L2::evict_first.b64 %0, 1.0;" : "=l"(pol));
  if (sc.delay) {
    const long long t0 = clock64();
    while (clock64() - t0 < G2_DELAY) __nanosleep(200);
  }
#pragma unroll 1
  for (int it = 0; it < sc.n; it++) {
    const int item = sched_item(sc, it);
    const int blk = item >> 9, h = (item >> 4) & 31, b = item & 15;
    const int row0 = (b * NH + h) * SK;
#pragma unroll
    for (int c = 0; c < 10; c++) {
      mbar_wait(bud, BAR_EMPTYA + sa * 8, pa);
      TLP(c);
      mbar_expect(BAR_FULLA + sa * 8, A_SLOT + B_SLOT);
      tma3d(A_ADDR(sa), &p.wq[blk], BAR_FULLA + sa * 8, 0, c * 64, h * 3);
      mbar_wait(bud, BAR_EMPTYB + xs(c) * 8, c < NSLOT);
      TLP(10 + c);
      tma2d(B_ADDR(xs(c)), &p.x[blk], BAR_FULLA + sa * 8, c * 64, b * SQ);
      if (++sa == NSLOT) { sa = 0; pa ^= 1; }
    }
#pragma unroll 1
    for (int i = 0; i < 16; i++) {
      const bool isK = (i == 0) || ((i & 1) && i < 15);
      const int j = i == 0 ? 0 : (i == 15 ? 7 : (isK ? (i + 1) >> 1 : (i - 2) >> 1));
      mbar_wait(bud, BAR_EMPTYA + sa * 8, pa);
      TLP(20 + i);
      mbar_expect(BAR_FULLA + sa * 8, A_SLOT);
      tma3d_hint(A_ADDR(sa), isK ? &p.k[blk] : &p.v[blk], BAR_FULLA + sa * 8, 0, row0 + j * 64, 0, pol);
      if (++sa == NSLOT) { sa = 0; pa ^= 1; }
    }
  }
}

template <int W>
__device__ __forceinline__ void oproj_consumer() {
  int bud = WAIT_BUDGET;
  const int tid = threadIdx.x & 127, lane = tid & 31, warp = tid >> 5;
  const int qrow = 8 * ((lane >> 1) & 1) + 4 * (lane >> 4) + 2 * ((lane >> 2) & 1) + (lane & 1);
  const uint32_t st_off = qrow * 128 + (((2 * warp + ((lane >> 3) & 1)) ^ (qrow & 7)) << 4);
  float a0[64], a1[64], ah[32];
  zero_regs(a0); zero_regs(a1); zero_regs(ah);
#pragma unroll 1
  for (int blk = 0; blk < 2; blk++) {
    int c3 = 0, step = blk * NH;
#pragma unroll 1
    for (int c = 0; c < 96; c++) {
      const uint32_t st = c & 3;
      mbar_wait(bud, BAR_GFULL + st * 8, (c >> 2) & 1);
      wg_fence();
      const uint32_t la = lo_sw(SB + st * O_STAGE), lb = lo_o(SB + st * O_STAGE + O_AB);
#define O_STEP(ks, sc)                                                   \
  mma64r<1, 1, 2 * 8192 + ks * 2048, W * 8192 + ks * 256>(ah, la, lb, sc);    \
  mma128r<1, 1, (W * 3) * 8192 + ks * 2048, ks * 256>(a0, la, lb, sc);        \
  mma128r<1, 1, (W * 3 + 1) * 8192 + ks * 2048, ks * 256>(a1, la, lb, sc);
      O_STEP(0, c != 0) O_STEP(1, 1) O_STEP(2, 1) O_STEP(3, 1)
#undef O_STEP
      wg_commit();
      if (++c3 == 3) {
        c3 = 0;
        if (W == 0)
          asm volatile("{\n.reg .pred p;\nsetp.eq.u32 p, %1, 0;\n@p red.relaxed.gpu.global.add.s32 [%0], 1;\n}\n" ::"l"(&g_done[step]), "r"(tid) : "memory");
        TL(step);
        step++;
      }
      wg_wait<1>();
      mbar_arrive_if0(BAR_GEMPTY + ((c - 1) & 3) * 8, tid | (c == 0) | (c == 95));
    }
    wg_wait<0>();
    reg_fence(a0); reg_fence(a1); reg_fence(ah);
    bar_sync(3, 256);
    const uint32_t sg = SB + 2 * O_STAGE + st_off;
    store_scaled(sg + 2 * 16384 + W * 8192, ah, 1.0f);
    store_scaled(sg + (W * 3) * 16384, a0, 1.0f);
    store_scaled(sg + (W * 3 + 1) * 16384, a1, 1.0f);
    publish(BAR_GOUT, lane);
  }
  TL_FLUSH();
}

__device__ __forceinline__ void oproj_producer(const Params& p, int cta, int epoch) {
  int bud = WAIT_BUDGET;
  const int half = cta & 1, r0 = (cta >> 1) * 128;
  const int b0 = r0 / SQ, off0 = r0 - b0 * SQ, n0 = min(128, SQ - off0), n1 = 128 - n0;
  const int target = epoch + 1;
#pragma unroll 1
  for (int step = 0; step < 2 * NH; step++) {
    const int blk = step >> 5, item0 = step * 16 + b0;
    const char* o0 = (const char*)g_o + (size_t)(item0 % ORING) * O_ITEM_BYTES + off0 * 128;
    const char* o1 = (const char*)g_o + (size_t)((item0 + 1) % ORING) * O_ITEM_BYTES;
#pragma unroll 1
    for (int kb = 0; kb < 3; kb++) {
      const int c = step * 3 + kb;
      const uint32_t st = c & 3, dst = SB + st * O_STAGE, bar = BAR_GFULL + st * 8;
      mbar_wait(bud, BAR_GEMPTY + st * 8, ((c >> 2) & 1) ^ 1);
      mbar_expect(bar, O_STAGE);
      tma3d(dst, &p.wo[blk], bar, 0, ((step & 31) * 3 + kb) * 64, half * 5);
      if (kb == 0) {
        flag_wait(bud, &g_ready[item0], target);
        if (n1) flag_wait(bud, &g_ready[item0 + 1], target);
        asm volatile("fence.proxy.async.global;" ::: "memory");
      }
      bulk_load(dst + O_AB, o0 + kb * B_SLOT, n0 * 128, bar);
      if (n1) bulk_load(dst + O_AB + n0 * 128, o1 + kb * B_SLOT, n1 * 128, bar);
    }
  }
}

__device__ __forceinline__ void oproj_storer(const Params& p, int cta) {
  int bud = WAIT_BUDGET;
  const int half = cta & 1, r0 = (cta >> 1) * 128;
#pragma unroll 1
  for (int blk = 0; blk < 2; blk++) {
    mbar_wait(bud, BAR_GOUT, blk);
    for (int k = 0; k < 5; k++) tma_store2d(&p.out, SB + 2 * O_STAGE + k * 16384, blk * DM + half * 320 + k * 64, r0);
    asm volatile("cp.async.bulk.commit_group;" ::: "memory");
    asm volatile("cp.async.bulk.wait_group.read 0;" ::: "memory");
    mbar_arrive2_if0(BAR_GEMPTY + 16, 0);
    mbar_arrive2_if0(BAR_GEMPTY + 24, 0);
  }
  asm volatile("cp.async.bulk.wait_group 0;" ::: "memory");
}

__global__ void __launch_bounds__(384, 1) fused_kernel(const __grid_constant__ Params p) {
  extern __shared__ __align__(1024) char smem_raw[];
  if ((smem_u32(smem_raw) & 0xFFFFFFu) != SB) return;
  const int cta = blockIdx.x;
  const int epoch = g_epoch[cta];
  if (threadIdx.x == 0) {
    for (int i = 0; i < NSLOT; i++) {
      mbar_init(BAR_FULLA + i * 8, 1); mbar_init(BAR_EMPTYA + i * 8, 2);
      mbar_init(BAR_EMPTYB + i * 8, 2);
    }
    mbar_init(BAR_XDONE, 2); mbar_init(BAR_QH, 8); mbar_init(BAR_QM, 4); mbar_init(BAR_QM + 8, 4);
    mbar_init(BAR_PFULL, 4); mbar_init(BAR_PFULL + 8, 4);
    mbar_init(BAR_PFREE, 3); mbar_init(BAR_PFREE + 8, 3);
    mbar_init(BAR_LFULL, 3); mbar_init(BAR_PMID, 4); mbar_init(BAR_PMID + 8, 4);
    mbar_init(BAR_OFULL, 8);
    for (int i = 0; i < O_NST; i++) { mbar_init(BAR_GFULL + i * 8, 1); mbar_init(BAR_GEMPTY + i * 8, 2); }
    mbar_init(BAR_GOUT, 8);
    asm volatile("fence.mbarrier_init.release.cluster;" ::: "memory");
    proxy_fence();
  }
  __syncthreads();
  if (threadIdx.x == 0) g_epoch[cta] = epoch + 1;
  const int warp = __shfl_sync(0xffffffffu, threadIdx.x >> 5, 0);
  const Sched sc = get_sched(cta);
  if (warp >= 8) {
    asm volatile("setmaxnreg.dec.sync.aligned.u32 40;");
    if (warp == 8) {
      if (elect_one()) attn_producer(p, sc);
      __syncwarp();
    } else {
      attn_helper(warp - 9, sc, epoch);
    }
    if (cta < N_OCTA) {
      bar_sync(4, 128);
      if (warp == 8) {
        if (elect_one()) oproj_producer(p, cta, epoch);
      } else if (warp == 9) {
        if (elect_one()) oproj_storer(p, cta);
      }
    }
  } else {
    asm volatile("setmaxnreg.inc.sync.aligned.u32 232;");
    if (warp < 4) {
      attn_consumer<0>(sc);
      if (cta < N_OCTA) oproj_consumer<0>();
    } else {
      attn_consumer<1>(sc);
      if (cta < N_OCTA) oproj_consumer<1>();
    }
  }
}

typedef CUresult (*EncodeFn)(CUtensorMap*, CUtensorMapDataType, cuuint32_t, void*, const cuuint64_t*, const cuuint64_t*, const cuuint32_t*,
                             const cuuint32_t*, CUtensorMapInterleave, CUtensorMapSwizzle, CUtensorMapL2promotion, CUtensorMapFloatOOBfill);

void make3d(EncodeFn enc, CUtensorMap* m, const void* ptr, uint64_t rows, uint64_t cols, uint32_t box_rows, uint32_t box_blocks) {
  cuuint64_t gd[3] = {64, rows, cols / 64};
  cuuint64_t gs[2] = {cols * 2, 128};
  cuuint32_t bd[3] = {64, box_rows, box_blocks}, es[3] = {1, 1, 1};
  enc(m, CU_TENSOR_MAP_DATA_TYPE_BFLOAT16, 3, (void*)ptr, gd, gs, bd, es, CU_TENSOR_MAP_INTERLEAVE_NONE, CU_TENSOR_MAP_SWIZZLE_128B,
      CU_TENSOR_MAP_L2_PROMOTION_L2_128B, CU_TENSOR_MAP_FLOAT_OOB_FILL_NONE);
}
void make2d(EncodeFn enc, CUtensorMap* m, const void* ptr, uint64_t rows, uint64_t cols, uint32_t box_rows) {
  cuuint64_t gd[2] = {cols, rows};
  cuuint64_t gs[1] = {cols * 2};
  cuuint32_t bd[2] = {64, box_rows}, es[2] = {1, 1};
  enc(m, CU_TENSOR_MAP_DATA_TYPE_BFLOAT16, 2, (void*)ptr, gd, gs, bd, es, CU_TENSOR_MAP_INTERLEAVE_NONE, CU_TENSOR_MAP_SWIZZLE_128B,
      CU_TENSOR_MAP_L2_PROMOTION_L2_128B, CU_TENSOR_MAP_FLOAT_OOB_FILL_NONE);
}

}

extern "C" void kernel_launch(void* const* d_in, const int* in_sizes, int n_in, void* d_out, int out_size) {
  static EncodeFn enc = nullptr;
  if (!enc) {
    cudaDriverEntryPointQueryResult qr;
    cudaGetDriverEntryPoint("cuTensorMapEncodeTiled", (void**)&enc, cudaEnableDefault, &qr);
    cudaFuncSetAttribute(fused_kernel, cudaFuncAttributeMaxDynamicSharedMemorySize, SMEM_BYTES);
  }
  Params p;
  for (int s = 0; s < 2; s++) {
    make2d(enc, &p.x[s], d_in[5 * s + 0], NB * SQ, DM, SQ);
    make3d(enc, &p.k[s], d_in[5 * s + 1], (uint64_t)NB * NH * SK, DH, 64, 3);
    make3d(enc, &p.v[s], d_in[5 * s + 2], (uint64_t)NB * NH * SK, DH, 64, 3);
    make3d(enc, &p.wq[s], d_in[5 * s + 3], DM, NH * DH, 64, 3);
    make3d(enc, &p.wo[s], d_in[5 * s + 4], NH * DH, DM, 64, 5);
    p.kp[s] = (const __nv_bfloat16*)d_in[5 * s + 1];
    p.vp[s] = (const __nv_bfloat16*)d_in[5 * s + 2];
  }
  make2d(enc, &p.out, d_out, NB * SQ, 2 * DM, 128);
  fused_kernel<<<NCTA, 384, SMEM_BYTES>>>(p);
}
```

```cpp
#include <cuda_runtime.h>
#include <cuda_bf16.h>
#include <cuda.h>
#include <stdint.h>

#define DEBUG_TIMEOUT 1

namespace {

constexpr int SQ = 160, DM = 640, NH = 32, SK = 512, DH = 192, NB = 16;
constexpr int NITEMS = 2 * NB * NH;
constexpr int NCTA = 132, N_OCTA = 40, N_G2 = 28, N_G1 = 64, N_ATT = N_G1 + N_G2;
#define ORING 112
#define KV_PROMO CU_TENSOR_MAP_L2_PROMOTION_L2_128B
#define G2_DELAY 13000
constexpr int A_SLOT = 24576, B_SLOT = 20480, NSLOT = 5;
constexpr int OFF_A = 0;
constexpr int OFF_B = NSLOT * A_SLOT;
constexpr int O_STAGE = 57344, O_AB = 40960, O_NST = 4;
constexpr int OFF_L = O_NST * O_STAGE;
constexpr int OFF_BAR = OFF_L + 160 * 4;
constexpr int SMEM_BYTES = OFF_BAR + 384 + 512;
static_assert(OFF_B + NSLOT * B_SLOT <= OFF_L, "smem layout");
constexpr uint32_t SB = 1024;
constexpr uint32_t BARS = SB + OFF_BAR;
constexpr uint32_t BAR_FULLA = BARS, BAR_EMPTYA = BARS + 40, BAR_PMID = BARS + 80, BAR_EMPTYB = BARS + 120, BAR_XDONE = BARS + 160,
                   BAR_QH = BARS + 168, BAR_QM = BARS + 96, BAR_PFULL = BARS + 184, BAR_PFREE = BARS + 200, BAR_LFULL = BARS + 216,
                   BAR_OFULL = BARS + 224, BAR_GFULL = BARS + 248, BAR_GEMPTY = BARS + 280, BAR_GOUT = BARS + 312;
constexpr int O_ITEM_BYTES = SQ * DH * 2;

struct alignas(64) Params {
  CUtensorMap x[2], wq[2], k[2], v[2], wo[2], out;
  const __nv_bfloat16* kp[2];
  const __nv_bfloat16* vp[2];
};

__device__ uint4 g_o[(size_t)ORING * O_ITEM_BYTES / 16];
__device__ int g_ready[NITEMS];
__device__ int g_done[2 * NH];
__device__ int g_epoch[NCTA];
__device__ int g_bad[NITEMS * 4];

#define TLP(id)
#define TLG(id)
#define TL(id)
#define TL_FLUSH()
__device__ __forceinline__ uint32_t smem_u32(const void* p) { return (uint32_t)__cvta_generic_to_shared(p); }
__device__ __forceinline__ void wg_fence() { asm volatile("wgmma.fence.sync.aligned;" ::: "memory"); }
__device__ __forceinline__ void wg_commit() { asm volatile("wgmma.commit_group.sync.aligned;" ::: "memory"); }
template <int N> __device__ __forceinline__ void wg_wait() { asm volatile("wgmma.wait_group.sync.aligned %0;" ::"n"(N) : "memory"); }
template <int N> __device__ __forceinline__ void reg_fence(float (&d)[N]) {
#pragma unroll
  for (int i = 0; i < N; i++) asm volatile("" : "+f"(d[i])::"memory");
}
template <int N> __device__ __forceinline__ void zero_regs(float (&d)[N]) {
#pragma unroll
  for (int i = 0; i < N; i++) d[i] = 0.f;
}
__device__ __forceinline__ void proxy_fence() { asm volatile("fence.proxy.async.shared::cta;" ::: "memory"); }
__device__ __forceinline__ void mbar_init(uint32_t bar, int cnt) { asm volatile("mbarrier.init.shared::cta.b64 [%0], %1;" ::"r"(bar), "r"(cnt) : "memory"); }
__device__ __forceinline__ void mbar_arrive_if0(uint32_t bar, uint32_t sel) {
  asm volatile("{\n.reg .pred p;\nsetp.eq.u32 p, %1, 0;\n@p mbarrier.arrive.shared::cta.b64 _, [%0];\n}\n" ::"r"(bar), "r"(sel) : "memory");
}
__device__ __forceinline__ void mbar_arrive2_if0(uint32_t bar, uint32_t sel) {
  asm volatile("{\n.reg .pred p;\nsetp.eq.u32 p, %1, 0;\n@p mbarrier.arrive.shared::cta.b64 _, [%0], 2;\n}\n" ::"r"(bar), "r"(sel) : "memory");
}
__device__ __forceinline__ void mbar_expect(uint32_t bar, uint32_t bytes) {
  asm volatile("mbarrier.arrive.expect_tx.shared::cta.b64 _, [%0], %1;" ::"r"(bar), "r"(bytes) : "memory");
}
__device__ __forceinline__ void mbar_wait(int& bud, uint32_t bar, uint32_t parity) {
  asm volatile(
      "{\n.reg .pred p, q;\n"
      "LW:\n"
      "mbarrier.try_wait.parity.shared::cta.b64 p, [%1], %2;\n"
      "@!p add.s32 %0, %0, -1;\n"
      "setp.gt.and.s32 q, %0, 0, !p;\n"
      "@q bra LW;\n}\n" : "+r"(bud) : "r"(bar), "r"(parity) : "memory");
}
constexpr int WAIT_BUDGET = 1 << 20;
__device__ __forceinline__ bool elect_one() {
  uint32_t p;
  asm volatile("{\n.reg .pred p;\nelect.sync _|p, 0xffffffff;\nselp.u32 %0, 1, 0, p;\n}\n" : "=r"(p));
  return p;
}
__device__ __forceinline__ void tma2d(uint32_t dst, const CUtensorMap* m, uint32_t bar, int c0, int c1) {
  asm volatile("cp.async.bulk.tensor.2d.shared::cluster.global.mbarrier::complete_tx::bytes [%0], [%1, {%3, %4}], [%2];"
               ::"r"(dst), "l"(m), "r"(bar), "r"(c0), "r"(c1) : "memory");
}
__device__ __forceinline__ void tma3d(uint32_t dst, const CUtensorMap* m, uint32_t bar, int c0, int c1, int c2) {
  asm volatile("cp.async.bulk.tensor.3d.shared::cluster.global.mbarrier::complete_tx::bytes [%0], [%1, {%3, %4, %5}], [%2];"
               ::"r"(dst), "l"(m), "r"(bar), "r"(c0), "r"(c1), "r"(c2) : "memory");
}
__device__ __forceinline__ void tma3d_hint(uint32_t dst, const CUtensorMap* m, uint32_t bar, int c0, int c1, int c2, uint64_t pol) {
  asm volatile("cp.async.bulk.tensor.3d.shared::cluster.global.mbarrier::complete_tx::bytes.L2::cache_hint [%0], [%1, {%3, %4, %5}], [%2], %6;"
               ::"r"(dst), "l"(m), "r"(bar), "r"(c0), "r"(c1), "r"(c2), "l"(pol) : "memory");
}
__device__ __forceinline__ void bulk_load(uint32_t dst, const void* src, uint32_t bytes, uint32_t bar) {
  asm volatile("cp.async.bulk.shared::cluster.global.mbarrier::complete_tx::bytes [%0], [%1], %2, [%3];"
               ::"r"(dst), "l"(src), "r"(bytes), "r"(bar) : "memory");
}
__device__ __forceinline__ void l2_prefetch(const void* src, uint32_t bytes) {
  asm volatile("cp.async.bulk.prefetch.L2.global [%0], %1;" ::"l"(src), "r"(bytes) : "memory");
}
__device__ __forceinline__ void l2_prefetch_hint(const void* src, uint32_t bytes, uint64_t pol) {
  asm volatile("cp.async.bulk.prefetch.L2.global.L2::cache_hint [%0], %1, %2;" ::"l"(src), "r"(bytes), "l"(pol) : "memory");
}
__device__ __forceinline__ void tma_store2d(const CUtensorMap* m, uint32_t src, int c0, int c1) {
  asm volatile("cp.async.bulk.tensor.2d.global.shared::cta.bulk_group [%0, {%2, %3}], [%1];" ::"l"(m), "r"(src), "r"(c0), "r"(c1) : "memory");
}
__device__ __forceinline__ void bar_sync(int id, int n) { asm volatile("bar.sync %0, %1;" ::"r"(id), "r"(n) : "memory"); }
__device__ __forceinline__ void bar_arrive(int id, int n) { asm volatile("bar.arrive %0, %1;" ::"r"(id), "r"(n) : "memory"); }
__device__ __forceinline__ float ex2(float x) { float y; asm("ex2.approx.ftz.f32 %0, %1;" : "=f"(y) : "f"(x)); return y; }
__device__ __forceinline__ uint32_t pack2(float lo, float hi) { uint32_t r; asm("cvt.rn.bf16x2.f32 %0, %1, %2;" : "=r"(r) : "f"(hi), "f"(lo)); return r; }
__device__ __forceinline__ void stsm_t(uint32_t a, uint32_t r0, uint32_t r1, uint32_t r2, uint32_t r3) {
  asm volatile("stmatrix.sync.aligned.m8n8.x4.trans.shared.b16 [%0], {%1,%2,%3,%4};" ::"r"(a), "r"(r0), "r"(r1), "r"(r2), "r"(r3) : "memory");
}
__device__ __forceinline__ void flag_wait(int& bud, const int* p, int target) {
  while (true) {
    int v;
    asm volatile("ld.acquire.gpu.global.s32 %0, [%1];" : "=r"(v) : "l"(p) : "memory");
    if (v - target >= 0 || --bud <= 0) break;
    __nanosleep(64);
  }
}
__device__ __forceinline__ uint32_t lo_sw(uint32_t addr) { return (addr >> 4) | (1u << 16); }
__device__ __forceinline__ uint32_t lo_o(uint32_t addr) { return (addr >> 4) | (8u << 16); }
__device__ __forceinline__ uint32_t opaque(uint32_t x) { uint32_t y; asm volatile("mov.u32 %0, %1;" : "=r"(y) : "r"(x)); return y; }

template <int TA, int TB, uint32_t OA, uint32_t OB>
__device__ __forceinline__ void mma160(float (&d)[80], uint32_t la, uint32_t lb) {
  asm volatile(
      "{\n.reg .pred p;\n.reg .b32 a, b;\n.reg .b64 da, db;\nsetp.eq.b32 p, 0, 0;\n"
      "add.u32 a, %80, %84;\nadd.u32 b, %81, %85;\nmov.b64 da, {a, 0x40000040};\nmov.b64 db, {b, %86};\n"
      "wgmma.mma_async.sync.aligned.m64n160k16.f32.bf16.bf16 {"
      "%0,%1,%2,%3,%4,%5,%6,%7,%8,%9,%10,%11,%12,%13,%14,%15,%16,%17,%18,%19,%20,%21,%22,%23,%24,%25,%26,%27,%28,%29,%30,%31,%32,%33,%34,%35,%36,"
      "%37,%38,%39,%40,%41,%42,%43,%44,%45,%46,%47,%48,%49,%50,%51,%52,%53,%54,%55,%56,%57,%58,%59,%60,%61,%62,%63,%64,%65,%66,%67,%68,%69,%70,%71,"
      "%72,%73,%74,%75,%76,%77,%78,%79"
      "}, da, db, p, 1, 1, %82, %83;\n}\n"
      :
      "+f"(d[0]),"+f"(d[1]),"+f"(d[2]),"+f"(d[3]),"+f"(d[4]),"+f"(d[5]),"+f"(d[6]),"+f"(d[7]),"+f"(d[8]),"+f"(d[9]),"+f"(d[10]),"+f"(d[11]),
      "+f"(d[12]),"+f"(d[13]),"+f"(d[14]),"+f"(d[15]),"+f"(d[16]),"+f"(d[17]),"+f"(d[18]),"+f"(d[19]),"+f"(d[20]),"+f"(d[21]),"+f"(d[22]),
      "+f"(d[23]),"+f"(d[24]),"+f"(d[25]),"+f"(d[26]),"+f"(d[27]),"+f"(d[28]),"+f"(d[29]),"+f"(d[30]),"+f"(d[31]),"+f"(d[32]),"+f"(d[33]),
      "+f"(d[34]),"+f"(d[35]),"+f"(d[36]),"+f"(d[37]),"+f"(d[38]),"+f"(d[39]),"+f"(d[40]),"+f"(d[41]),"+f"(d[42]),"+f"(d[43]),"+f"(d[44]),
      "+f"(d[45]),"+f"(d[46]),"+f"(d[47]),"+f"(d[48]),"+f"(d[49]),"+f"(d[50]),"+f"(d[51]),"+f"(d[52]),"+f"(d[53]),"+f"(d[54]),"+f"(d[55]),
      "+f"(d[56]),"+f"(d[57]),"+f"(d[58]),"+f"(d[59]),"+f"(d[60]),"+f"(d[61]),"+f"(d[62]),"+f"(d[63]),"+f"(d[64]),"+f"(d[65]),"+f"(d[66]),
      "+f"(d[67]),"+f"(d[68]),"+f"(d[69]),"+f"(d[70]),"+f"(d[71]),"+f"(d[72]),"+f"(d[73]),"+f"(d[74]),"+f"(d[75]),"+f"(d[76]),"+f"(d[77]),
      "+f"(d[78]),"+f"(d[79])
      : "r"(la), "r"(lb), "n"(TA), "n"(TB), "n"(OA >> 4), "n"(OB >> 4), "n"(TB ? 0x40 : 0x40000040));
}

template <int TA, int TB, uint32_t OA, uint32_t OB>
__device__ __forceinline__ void mma160z(float (&d)[80], uint32_t la, uint32_t lb) {
  asm volatile(
      "{\n.reg .pred p;\n.reg .b32 a, b;\n.reg .b64 da, db;\nsetp.ne.b32 p, 0, 0;\n"
      "add.u32 a, %80, %84;\nadd.u32 b, %81, %85;\nmov.b64 da, {a, 0x40000040};\nmov.b64 db, {b, %86};\n"
      "wgmma.mma_async.sync.aligned.m64n160k16.f32.bf16.bf16 {"
      "%0,%1,%2,%3,%4,%5,%6,%7,%8,%9,%10,%11,%12,%13,%14,%15,%16,%17,%18,%19,%20,%21,%22,%23,%24,%25,%26,%27,%28,%29,%30,%31,%32,%33,%34,%35,%36,"
      "%37,%38,%39,%40,%41,%42,%43,%44,%45,%46,%47,%48,%49,%50,%51,%52,%53,%54,%55,%56,%57,%58,%59,%60,%61,%62,%63,%64,%65,%66,%67,%68,%69,%70,%71,"
      "%72,%73,%74,%75,%76,%77,%78,%79"
      "}, da, db, p, 1, 1, %82, %83;\n}\n"
      :
      "=f"(d[0]),"=f"(d[1]),"=f"(d[2]),"=f"(d[3]),"=f"(d[4]),"=f"(d[5]),"=f"(d[6]),"=f"(d[7]),"=f"(d[8]),"=f"(d[9]),"=f"(d[10]),"=f"(d[11]),
      "=f"(d[12]),"=f"(d[13]),"=f"(d[14]),"=f"(d[15]),"=f"(d[16]),"=f"(d[17]),"=f"(d[18]),"=f"(d[19]),"=f"(d[20]),"=f"(d[21]),"=f"(d[22]),
      "=f"(d[23]),"=f"(d[24]),"=f"(d[25]),"=f"(d[26]),"=f"(d[27]),"=f"(d[28]),"=f"(d[29]),"=f"(d[30]),"=f"(d[31]),"=f"(d[32]),"=f"(d[33]),
      "=f"(d[34]),"=f"(d[35]),"=f"(d[36]),"=f"(d[37]),"=f"(d[38]),"=f"(d[39]),"=f"(d[40]),"=f"(d[41]),"=f"(d[42]),"=f"(d[43]),"=f"(d[44]),
      "=f"(d[45]),"=f"(d[46]),"=f"(d[47]),"=f"(d[48]),"=f"(d[49]),"=f"(d[50]),"=f"(d[51]),"=f"(d[52]),"=f"(d[53]),"=f"(d[54]),"=f"(d[55]),
      "=f"(d[56]),"=f"(d[57]),"=f"(d[58]),"=f"(d[59]),"=f"(d[60]),"=f"(d[61]),"=f"(d[62]),"=f"(d[63]),"=f"(d[64]),"=f"(d[65]),"=f"(d[66]),
      "=f"(d[67]),"=f"(d[68]),"=f"(d[69]),"=f"(d[70]),"=f"(d[71]),"=f"(d[72]),"=f"(d[73]),"=f"(d[74]),"=f"(d[75]),"=f"(d[76]),"=f"(d[77]),
      "=f"(d[78]),"=f"(d[79])
      : "r"(la), "r"(lb), "n"(TA), "n"(TB), "n"(OA >> 4), "n"(OB >> 4), "n"(TB ? 0x40 : 0x40000040));
}

template <int TA, int TB, uint32_t OA, uint32_t OB>
__device__ __forceinline__ void mma80(float (&d)[40], uint32_t la, uint32_t lb) {
  asm volatile(
      "{\n.reg .pred p;\n.reg .b32 a, b;\n.reg .b64 da, db;\nsetp.eq.b32 p, 0, 0;\n"
      "add.u32 a, %40, %44;\nadd.u32 b, %41, %45;\nmov.b64 da, {a, 0x40000040};\nmov.b64 db, {b, %46};\n"
      "wgmma.mma_async.sync.aligned.m64n80k16.f32.bf16.bf16 {"
      "%0,%1,%2,%3,%4,%5,%6,%7,%8,%9,%10,%11,%12,%13,%14,%15,%16,%17,%18,%19,%20,%21,%22,%23,%24,%25,%26,%27,%28,%29,%30,%31,%32,%33,%34,%35,%36,"
      "%37,%38,%39"
      "}, da, db, p, 1, 1, %42, %43;\n}\n"
      :
      "+f"(d[0]),"+f"(d[1]),"+f"(d[2]),"+f"(d[3]),"+f"(d[4]),"+f"(d[5]),"+f"(d[6]),"+f"(d[7]),"+f"(d[8]),"+f"(d[9]),"+f"(d[10]),"+f"(d[11]),
      "+f"(d[12]),"+f"(d[13]),"+f"(d[14]),"+f"(d[15]),"+f"(d[16]),"+f"(d[17]),"+f"(d[18]),"+f"(d[19]),"+f"(d[20]),"+f"(d[21]),"+f"(d[22]),
      "+f"(d[23]),"+f"(d[24]),"+f"(d[25]),"+f"(d[26]),"+f"(d[27]),"+f"(d[28]),"+f"(d[29]),"+f"(d[30]),"+f"(d[31]),"+f"(d[32]),"+f"(d[33]),
      "+f"(d[34]),"+f"(d[35]),"+f"(d[36]),"+f"(d[37]),"+f"(d[38]),"+f"(d[39])
      : "r"(la), "r"(lb), "n"(TA), "n"(TB), "n"(OA >> 4), "n"(OB >> 4), "n"(TB ? 0x40 : 0x40000040));
}

template <int TA, int TB, uint32_t OA, uint32_t OB>
__device__ __forceinline__ void mma80z(float (&d)[40], uint32_t la, uint32_t lb) {
  asm volatile(
      "{\n.reg .pred p;\n.reg .b32 a, b;\n.reg .b64 da, db;\nsetp.ne.b32 p, 0, 0;\n"
      "add.u32 a, %40, %44;\nadd.u32 b, %41, %45;\nmov.b64 da, {a, 0x40000040};\nmov.b64 db, {b, %46};\n"
      "wgmma.mma_async.sync.aligned.m64n80k16.f32.bf16.bf16 {"
      "%0,%1,%2,%3,%4,%5,%6,%7,%8,%9,%10,%11,%12,%13,%14,%15,%16,%17,%18,%19,%20,%21,%22,%23,%24,%25,%26,%27,%28,%29,%30,%31,%32,%33,%34,%35,%36,"
      "%37,%38,%39"
      "}, da, db, p, 1, 1, %42, %43;\n}\n"
      :
      "=f"(d[0]),"=f"(d[1]),"=f"(d[2]),"=f"(d[3]),"=f"(d[4]),"=f"(d[5]),"=f"(d[6]),"=f"(d[7]),"=f"(d[8]),"=f"(d[9]),"=f"(d[10]),"=f"(d[11]),
      "=f"(d[12]),"=f"(d[13]),"=f"(d[14]),"=f"(d[15]),"=f"(d[16]),"=f"(d[17]),"=f"(d[18]),"=f"(d[19]),"=f"(d[20]),"=f"(d[21]),"=f"(d[22]),
      "=f"(d[23]),"=f"(d[24]),"=f"(d[25]),"=f"(d[26]),"=f"(d[27]),"=f"(d[28]),"=f"(d[29]),"=f"(d[30]),"=f"(d[31]),"=f"(d[32]),"=f"(d[33]),
      "=f"(d[34]),"=f"(d[35]),"=f"(d[36]),"=f"(d[37]),"=f"(d[38]),"=f"(d[39])
      : "r"(la), "r"(lb), "n"(TA), "n"(TB), "n"(OA >> 4), "n"(OB >> 4), "n"(TB ? 0x40 : 0x40000040));
}

template <int TA, int TB, uint32_t OA, uint32_t OB>
__device__ __forceinline__ void mma128r(float (&d)[64], uint32_t la, uint32_t lb, int sc) {
  asm volatile(
      "{\n.reg .pred p;\n.reg .b32 a, b;\n.reg .b64 da, db;\nsetp.ne.b32 p, %71, 0;\n"
      "add.u32 a, %64, %68;\nadd.u32 b, %65, %69;\nmov.b64 da, {a, 0x40000040};\nmov.b64 db, {b, %70};\n"
      "wgmma.mma_async.sync.aligned.m64n128k16.f32.bf16.bf16 {"
      "%0,%1,%2,%3,%4,%5,%6,%7,%8,%9,%10,%11,%12,%13,%14,%15,%16,%17,%18,%19,%20,%21,%22,%23,%24,%25,%26,%27,%28,%29,%30,%31,%32,%33,%34,%35,%36,"
      "%37,%38,%39,%40,%41,%42,%43,%44,%45,%46,%47,%48,%49,%50,%51,%52,%53,%54,%55,%56,%57,%58,%59,%60,%61,%62,%63"
      "}, da, db, p, 1, 1, %66, %67;\n}\n"
      :
      "+f"(d[0]),"+f"(d[1]),"+f"(d[2]),"+f"(d[3]),"+f"(d[4]),"+f"(d[5]),"+f"(d[6]),"+f"(d[7]),"+f"(d[8]),"+f"(d[9]),"+f"(d[10]),"+f"(d[11]),
      "+f"(d[12]),"+f"(d[13]),"+f"(d[14]),"+f"(d[15]),"+f"(d[16]),"+f"(d[17]),"+f"(d[18]),"+f"(d[19]),"+f"(d[20]),"+f"(d[21]),"+f"(d[22]),
      "+f"(d[23]),"+f"(d[24]),"+f"(d[25]),"+f"(d[26]),"+f"(d[27]),"+f"(d[28]),"+f"(d[29]),"+f"(d[30]),"+f"(d[31]),"+f"(d[32]),"+f"(d[33]),
      "+f"(d[34]),"+f"(d[35]),"+f"(d[36]),"+f"(d[37]),"+f"(d[38]),"+f"(d[39]),"+f"(d[40]),"+f"(d[41]),"+f"(d[42]),"+f"(d[43]),"+f"(d[44]),
      "+f"(d[45]),"+f"(d[46]),"+f"(d[47]),"+f"(d[48]),"+f"(d[49]),"+f"(d[50]),"+f"(d[51]),"+f"(d[52]),"+f"(d[53]),"+f"(d[54]),"+f"(d[55]),
      "+f"(d[56]),"+f"(d[57]),"+f"(d[58]),"+f"(d[59]),"+f"(d[60]),"+f"(d[61]),"+f"(d[62]),"+f"(d[63])
      : "r"(la), "r"(lb), "n"(TA), "n"(TB), "n"(OA >> 4), "n"(OB >> 4), "n"(TB ? 0x40 : 0x40000040), "r"(sc));
}

template <int TA, int TB, uint32_t OA, uint32_t OB>
__device__ __forceinline__ void mma64r(float (&d)[32], uint32_t la, uint32_t lb, int sc) {
  asm volatile(
      "{\n.reg .pred p;\n.reg .b32 a, b;\n.reg .b64 da, db;\nsetp.ne.b32 p, %39, 0;\n"
      "add.u32 a, %32, %36;\nadd.u32 b, %33, %37;\nmov.b64 da, {a, 0x40000040};\nmov.b64 db, {b, %38};\n"
      "wgmma.mma_async.sync.aligned.m64n64k16.f32.bf16.bf16 {"
      "%0,%1,%2,%3,%4,%5,%6,%7,%8,%9,%10,%11,%12,%13,%14,%15,%16,%17,%18,%19,%20,%21,%22,%23,%24,%25,%26,%27,%28,%29,%30,%31"
      "}, da, db, p, 1, 1, %34, %35;\n}\n"
      :
      "+f"(d[0]),"+f"(d[1]),"+f"(d[2]),"+f"(d[3]),"+f"(d[4]),"+f"(d[5]),"+f"(d[6]),"+f"(d[7]),"+f"(d[8]),"+f"(d[9]),"+f"(d[10]),"+f"(d[11]),
      "+f"(d[12]),"+f"(d[13]),"+f"(d[14]),"+f"(d[15]),"+f"(d[16]),"+f"(d[17]),"+f"(d[18]),"+f"(d[19]),"+f"(d[20]),"+f"(d[21]),"+f"(d[22]),
      "+f"(d[23]),"+f"(d[24]),"+f"(d[25]),"+f"(d[26]),"+f"(d[27]),"+f"(d[28]),"+f"(d[29]),"+f"(d[30]),"+f"(d[31])
      : "r"(la), "r"(lb), "n"(TA), "n"(TB), "n"(OA >> 4), "n"(OB >> 4), "n"(TB ? 0x40 : 0x40000040), "r"(sc));
}

struct Ring { uint32_t s0, ph0; };
__device__ __forceinline__ void ring_pos(const Ring& r, int i, uint32_t& slot, uint32_t& ph) {
  uint32_t s = opaque(r.s0) + (i % NSLOT);
  uint32_t wrap = s >= NSLOT;
  slot = s - (wrap ? NSLOT : 0);
  ph = r.ph0 ^ ((i / NSLOT) & 1) ^ wrap;
}
__device__ __forceinline__ void ring_advance(Ring& r, int n) {
  uint32_t s, p;
  ring_pos(r, n, s, p);
  r.s0 = s; r.ph0 = p;
}
__host__ __device__ constexpr int idxK(int j) { return j == 0 ? 10 : 9 + 2 * j; }
__host__ __device__ constexpr int idxV(int j) { return j == 7 ? 25 : 12 + 2 * j; }
__host__ __device__ constexpr int xs(int c) { return c % NSLOT; }

struct Sched { int first, second, n, delay; };
__device__ __forceinline__ Sched get_sched(int cta) {
  if (cta < N_OCTA) return Sched{cta, 0, 1, 0};
  if (cta < N_OCTA + N_G1) return Sched{cta, NCTA + (cta - N_OCTA), 11, 0};
  return Sched{cta, cta + N_ATT, 10, 1};
}
__device__ __forceinline__ int sched_item(const Sched& s, int k) { return k == 0 ? s.first : s.second + (k - 1) * N_ATT; }

template <int W, bool ACC>
__device__ __forceinline__ void mma_main(float (&d)[80], uint32_t aaddr, uint32_t baddr) {
  const uint32_t la = lo_sw(aaddr), lb = lo_sw(baddr);
  if (ACC) mma160<1, 0, W * 16384, 0>(d, la, lb); else mma160z<1, 0, W * 16384, 0>(d, la, lb);
  mma160<1, 0, W * 16384 + 1 * 2048, 1 * 32>(d, la, lb);
  mma160<1, 0, W * 16384 + 2 * 2048, 2 * 32>(d, la, lb);
  mma160<1, 0, W * 16384 + 3 * 2048, 3 * 32>(d, la, lb);
}
template <int W, bool ACC>
__device__ __forceinline__ void mma_mid(float (&d)[40], uint32_t aaddr, uint32_t baddr) {
  const uint32_t la = lo_sw(aaddr), lb = lo_sw(baddr);
  if (ACC) mma80<1, 0, 8192, W * 10240>(d, la, lb); else mma80z<1, 0, 8192, W * 10240>(d, la, lb);
  mma80<1, 0, 8192 + 1 * 2048, W * 10240 + 1 * 32>(d, la, lb);
  mma80<1, 0, 8192 + 2 * 2048, W * 10240 + 2 * 32>(d, la, lb);
  mma80<1, 0, 8192 + 3 * 2048, W * 10240 + 3 * 32>(d, la, lb);
}
template <int W, bool ACC>
__device__ __forceinline__ void mma_both(float (&dm)[80], float (&dh)[40], uint32_t aaddr, uint32_t baddr) {
  mma_mid<W, ACC>(dh, aaddr, baddr);
  mma_main<W, ACC>(dm, aaddr, baddr);
}
template <int KB, bool ACC>
__device__ __forceinline__ void s_mma(float (&sacc)[80], uint32_t kaddr) {
  const uint32_t la = lo_sw(kaddr), lb = lo_sw(SB + OFF_B);
  if (ACC) mma160<0, 0, KB * 8192, KB * B_SLOT>(sacc, la, lb); else mma160z<0, 0, KB * 8192, KB * B_SLOT>(sacc, la, lb);
  mma160<0, 0, KB * 8192 + 32, KB * B_SLOT + 32>(sacc, la, lb);
  mma160<0, 0, KB * 8192 + 64, KB * B_SLOT + 64>(sacc, la, lb);
  mma160<0, 0, KB * 8192 + 96, KB * B_SLOT + 96>(sacc, la, lb);
}
template <int N>
__device__ __forceinline__ void store_scaled(uint32_t addr, const float (&d)[N], float sc) {
#pragma unroll
  for (int J = 0; J < N / 8; J++)
    stsm_t(addr + J * 2048, pack2(d[8 * J] * sc, d[8 * J + 1] * sc), pack2(d[8 * J + 2] * sc, d[8 * J + 3] * sc),
           pack2(d[8 * J + 4] * sc, d[8 * J + 5] * sc), pack2(d[8 * J + 6] * sc, d[8 * J + 7] * sc));
}
__device__ __forceinline__ float4 lds_f4(uint32_t a) {
  float4 v;
  asm volatile("ld.shared.v4.f32 {%0,%1,%2,%3}, [%4];" : "=f"(v.x), "=f"(v.y), "=f"(v.z), "=f"(v.w) : "r"(a) : "memory");
  return v;
}
__device__ __forceinline__ void norm_pack(uint32_t* p, const float* d, const float4& i) {
  p[0] = pack2(d[0] * i.x, d[1] * i.y); p[1] = pack2(d[4] * i.z, d[5] * i.w);
  p[2] = pack2(d[2] * i.x, d[3] * i.y); p[3] = pack2(d[6] * i.z, d[7] * i.w);
  asm volatile("" : "+r"(p[0]), "+r"(p[1]), "+r"(p[2]), "+r"(p[3])::"memory");
}
template <int W>
__device__ __forceinline__ void pack_first(uint32_t (&pk)[60], const float (&om)[80], const float (&oh)[40], uint32_t laddr) {
  float4 n0 = lds_f4(laddr + W * 80), n1 = lds_f4(laddr + W * 80 + 16);
#pragma unroll
  for (int J = 0; J < 5; J++) {
    const float4 i = n0;
    n0 = n1;
    if (J + 2 < 5) n1 = lds_f4(laddr + W * 80 + (J + 2) * 16);
    norm_pack(&pk[20 + 4 * J], &om[8 * (5 * W + J)], i);
    norm_pack(&pk[4 * J], &oh[8 * J], i);
  }
}
template <int W>
__device__ __forceinline__ void pack_second(uint32_t (&pk)[60], const float (&om)[80], uint32_t laddr) {
  float4 n0 = lds_f4(laddr + (1 - W) * 80), n1 = lds_f4(laddr + (1 - W) * 80 + 16);
#pragma unroll
  for (int J = 0; J < 5; J++) {
    const float4 i = n0;
    n0 = n1;
    if (J + 2 < 5) n1 = lds_f4(laddr + (1 - W) * 80 + (J + 2) * 16);
    norm_pack(&pk[40 + 4 * J], &om[8 * (5 * (1 - W) + J)], i);
  }
}
template <int W, int G0, int G1>
__device__ __forceinline__ void store_groups(char* op, const uint32_t (&pk)[60], uint32_t on) {
#pragma unroll
  for (int G = G0; G < G1; G++) {
    const int off = (G < 5 ? 1 : 2 * W) * B_SLOT + (5 * (G < 10 ? W : 1 - W) + G % 5) * 2048;
    asm volatile("{\n.reg .pred p;\nsetp.ne.u32 p, %5, 0;\n@p st.global.v2.b32 [%0], {%1, %2};\n@p st.global.v2.b32 [%0+128], {%3, %4};\n}\n"
                 ::"l"(op + off), "r"(pk[4 * G]), "r"(pk[4 * G + 1]), "r"(pk[4 * G + 2]), "r"(pk[4 * G + 3]), "r"(on) : "memory");
  }
}
__device__ __forceinline__ void publish_generic(uint32_t bar, int lane) {
  __syncwarp();
  mbar_arrive_if0(bar, lane);
}
__device__ __forceinline__ void publish(uint32_t bar, int lane) {
  proxy_fence();
  __syncwarp();
  mbar_arrive_if0(bar, lane);
}

#define A_ADDR(s) (SB + OFF_A + (s) * A_SLOT)
#define B_ADDR(s) (SB + OFF_B + (s) * B_SLOT)
#define WAIT_CHUNK(c, ro, sA)                \
  uint32_t sA;                               \
  {                                          \
    uint32_t pA_;                            \
    ring_pos(ring, (ro) + (c), sA, pA_);     \
    mbar_wait(bud, BAR_FULLA + sA * 8, pA_); \
  }
#define RELEASE_CHUNK(c, sA)                                  \
  mbar_arrive_if0(BAR_EMPTYA + (sA) * 8, tid);                \
  if ((c) < NSLOT) mbar_arrive_if0(BAR_EMPTYB + xs(c) * 8, tid);

template <int W>
__device__ __forceinline__ void attn_consumer(const Sched& sc) {
  int bud = WAIT_BUDGET;
  const int tid = threadIdx.x & 127, lane = tid & 31, warp = tid >> 5;
  const uint32_t st_off = ((lane & 7) + 8 * (lane >> 4)) * 128 + (((2 * warp + ((lane >> 3) & 1)) ^ (lane & 7)) << 4);
  const uint32_t laddr = SB + OFF_L + (lane & 3) * 160;
  const uint32_t o_off = ((lane & 3) >> 1) * 1024 + warp * 256 + (lane >> 2) * 16 + (lane & 1) * 8;
  float om[80], oh[40], sacc[80];
  uint32_t pk[60];
#pragma unroll
  for (int i = 0; i < 60; i++) pk[i] = 0;
  char* op = (char*)g_o;
  Ring ring{0u, 0u};
  uint32_t par = 0;
  const float qscale = 0.07216878364870322f * 1.4426950408889634f;
  constexpr uint32_t pown = B_ADDR(3 + W), poth = B_ADDR(4 - W);
  TL(0); TLG(62);
  {
    WAIT_CHUNK(0, 0, s0)
    wg_fence();
    mma_both<W, false>(sacc, oh, A_ADDR(s0), B_ADDR(xs(0)));
    wg_commit();
    WAIT_CHUNK(1, 0, s1)
    wg_fence();
    mma_both<W, true>(sacc, oh, A_ADDR(s1), B_ADDR(xs(1)));
    wg_commit();
    wg_wait<1>();
    RELEASE_CHUNK(0, s0)
  }
#pragma unroll 1
  for (int it = 0;; it++) {
#pragma unroll
    for (int c = 2; c < 8; c++) {
      WAIT_CHUNK(c, 0, sA)
      TL(40 + c);
      wg_fence();
      mma_both<W, true>(sacc, oh, A_ADDR(sA), B_ADDR(xs(c)));
      wg_commit();
      if (c == 2) store_groups<W, 0, 3>(op, pk, it);
      if (c == 3) store_groups<W, 3, 6>(op, pk, it);
      if (c == 4) store_groups<W, 6, 9>(op, pk, it);
      if (c == 5) store_groups<W, 9, 12>(op, pk, it);
      if (c == 6) {
        store_groups<W, 12, 15>(op, pk, it);
        __syncwarp();
        mbar_arrive_if0(BAR_OFULL, lane | (it == 0));
      }
      wg_wait<1>();
      uint32_t sP, pP;
      ring_pos(ring, c - 1, sP, pP);
      RELEASE_CHUNK(c - 1, sP)
    }
    uint32_t sK0, pK0, s7, p7;
    ring_pos(ring, idxK(W), sK0, pK0);
    ring_pos(ring, 7, s7, p7);
    if (W == 1) {
      wg_wait<0>();
      RELEASE_CHUNK(7, s7)
      mbar_arrive_if0(BAR_XDONE, tid);
    }
    WAIT_CHUNK(8, 0, s8)
    WAIT_CHUNK(9, 0, s9)
    TL(48);
    if (W == 1) bar_sync(5, 256);
    wg_fence();
    mma_mid<W, true>(oh, A_ADDR(s8), B_ADDR(xs(8)));
    mma_mid<W, true>(oh, A_ADDR(s9), B_ADDR(xs(9)));
    wg_commit();
    mma_main<W, true>(sacc, A_ADDR(s8), B_ADDR(xs(8)));
    mma_main<W, true>(sacc, A_ADDR(s9), B_ADDR(xs(9)));
    wg_commit();
    if (W == 0) bar_arrive(5, 256);
    TL(49);
    wg_wait<1>();
    reg_fence(oh);
    if (W == 0) {
      RELEASE_CHUNK(7, s7)
      mbar_arrive_if0(BAR_XDONE, tid);
    }
    mbar_wait(bud, BAR_XDONE, par);
    store_scaled(B_ADDR(1) + W * 10240 + st_off, oh, qscale);
    publish(BAR_QH, lane);
    if (W == 0) mbar_wait(bud, BAR_FULLA + sK0 * 8, pK0);
    wg_wait<0>();
    reg_fence(sacc);
    TL(1);
    RELEASE_CHUNK(8, s8)
    RELEASE_CHUNK(9, s9)
    store_scaled(B_ADDR(2 * W) + st_off, sacc, qscale);
    TL(2);
    if (W == 0) {
      mbar_wait(bud, BAR_QH, par);
      wg_fence();
      s_mma<1, false>(sacc, A_ADDR(sK0));
      wg_commit();
      TL(3);
      publish(BAR_QM, lane);
      mbar_wait(bud, BAR_QM, par);
      wg_fence();
      s_mma<0, true>(sacc, A_ADDR(sK0));
      wg_commit();
      mbar_wait(bud, BAR_QM + 8, par);
      TL(5);
      wg_fence();
      s_mma<2, true>(sacc, A_ADDR(sK0));
      wg_commit();
    } else {
      publish(BAR_QM + 8, lane);
      TL(3);
    }

#pragma unroll
    for (int jj = 0; jj < 4; jj++) {
      const int j = 2 * jj + W;
      uint32_t sK = sK0, pK = pK0, sV2 = 0, pV2 = 0, sV1 = 0, pV1 = 0;
      if (j >= 1) {
        if (jj >= 1) ring_pos(ring, idxK(j), sK, pK);
        if (j >= 2) ring_pos(ring, idxV(j >= 2 ? j - 2 : 0), sV2, pV2);
        ring_pos(ring, idxV(j >= 1 ? j - 1 : 0), sV1, pV1);
        if (j >= 2) mbar_wait(bud, BAR_FULLA + sV2 * 8, pV2); else mbar_wait(bud, BAR_FULLA + sK * 8, pK);
        bar_sync(1 + W, 256);
        wg_fence();
        if (j >= 2) {
          if (j == 2) mma_both<W, false>(om, oh, A_ADDR(sV2), pown); else mma_both<W, true>(om, oh, A_ADDR(sV2), pown);
          wg_commit();
          mbar_wait(bud, BAR_FULLA + sK * 8, pK);
          wg_fence();
        }
        TL(4 + jj * 7);
        s_mma<0, false>(sacc, A_ADDR(sK));
        s_mma<1, true>(sacc, A_ADDR(sK));
        if (j >= 2) {
          wg_commit();
          wg_wait<1>();
          mbar_arrive_if0(BAR_EMPTYA + sV2 * 8, tid);
          wg_fence();
        }
        s_mma<2, true>(sacc, A_ADDR(sK));
        wg_commit();
        TL(6 + jj * 7);
        mbar_wait(bud, BAR_FULLA + sV1 * 8, pV1);
        if (jj >= 1) mbar_wait(bud, BAR_PFREE + W * 8, (jj - 1) & 1);
        mbar_wait(bud, BAR_PFULL + (1 - W) * 8, ((j - 1) >> 1) & 1);
        TL(7 + jj * 7);
        wg_fence();
        if (j == 1) mma_both<W, false>(om, oh, A_ADDR(sV1), poth); else mma_both<W, true>(om, oh, A_ADDR(sV1), poth);
        wg_commit();
      }
      bar_arrive(2 - W, 256);
      if (j >= 1) wg_wait<1>(); else wg_wait<0>();
      reg_fence(sacc);
      TL(8 + jj * 7);
      mbar_arrive2_if0(BAR_EMPTYA + sK * 8, tid);
      if (jj == 3) mbar_arrive_if0(BAR_EMPTYB + tid * 8, tid >= 3);
#pragma unroll
      for (int J = 0; J < 10; J++) {
        stsm_t(pown + st_off + J * 2048, pack2(ex2(sacc[8 * J]), ex2(sacc[8 * J + 1])), pack2(ex2(sacc[8 * J + 2]), ex2(sacc[8 * J + 3])),
               pack2(ex2(sacc[8 * J + 4]), ex2(sacc[8 * J + 5])), pack2(ex2(sacc[8 * J + 6]), ex2(sacc[8 * J + 7])));
        if (j == 7 && (J == 2 || J == 5)) publish_generic(BAR_PMID + (J / 3) * 8, lane);
        if (j >= 1 && J == 5) {
          wg_wait<0>();
          mbar_arrive_if0(BAR_EMPTYA + sV1 * 8, tid);
        }
      }
      publish(BAR_PFULL + W * 8, lane);
      TL(10 + jj * 7);
    }
    uint32_t sV7, pV7;
    ring_pos(ring, idxV(7), sV7, pV7);
    if (W == 0) {
      uint32_t sV6, pV6;
      ring_pos(ring, idxV(6), sV6, pV6);
      mbar_wait(bud, BAR_FULLA + sV6 * 8, pV6);
      bar_sync(1, 256);
      wg_fence();
      mma_both<0, true>(om, oh, A_ADDR(sV6), pown);
      wg_commit();
      mbar_wait(bud, BAR_FULLA + sV7 * 8, pV7);
      wg_wait<0>();
      mbar_arrive_if0(BAR_EMPTYA + sV6 * 8, tid);
      mbar_wait(bud, BAR_PFULL + 8, 1);
      wg_fence();
      mma_both<0, true>(om, oh, A_ADDR(sV7), poth);
      wg_commit();
      bar_arrive(6, 256);
    } else {
      mbar_wait(bud, BAR_FULLA + sV7 * 8, pV7);
      bar_sync(6, 256);
    }
    TL(32);
    op = (char*)g_o + (size_t)(sched_item(sc, it) % ORING) * O_ITEM_BYTES + o_off;
    if (it + 1 == sc.n) {
      if (W == 1) {
        wg_fence();
        mma_both<1, true>(om, oh, A_ADDR(sV7), pown);
        wg_commit();
      }
      wg_wait<0>();
      reg_fence(om); reg_fence(oh);
      TL(33);
      mbar_wait(bud, BAR_LFULL, par);
      TL(34);
      pack_first<W>(pk, om, oh, laddr);
      store_groups<W, 0, 10>(op, pk, 1);
      pack_second<W>(pk, om, laddr);
      store_groups<W, 10, 15>(op, pk, 1);
      publish_generic(BAR_OFULL, lane);
      TL(35); TLG(63);
      TL_FLUSH();
      break;
    }
    {
      if (W == 1) {
        wg_fence();
        mma_both<1, true>(om, oh, A_ADDR(sV7), pown);
        wg_commit();
      }
      WAIT_CHUNK(0, 26, s0)
      WAIT_CHUNK(1, 26, s1)
      if (W == 0) {
        wg_wait<0>();
        reg_fence(om); reg_fence(oh);
        TL(33);
        wg_fence();
        mma_main<W, false>(sacc, A_ADDR(s0), B_ADDR(xs(0)));
        wg_commit();
      } else {
        wg_fence();
        mma_main<W, false>(sacc, A_ADDR(s0), B_ADDR(xs(0)));
        mma_main<W, true>(sacc, A_ADDR(s1), B_ADDR(xs(1)));
        wg_commit();
        wg_wait<1>();
        reg_fence(om); reg_fence(oh);
        TL(33);
      }
      mbar_arrive_if0(BAR_EMPTYA + sV7 * 8, tid);
      mbar_wait(bud, BAR_LFULL, par);
      mbar_arrive_if0(BAR_EMPTYB + 24 + tid * 8, tid >= 2);
      TL(34);
      pack_first<W>(pk, om, oh, laddr);
      TL(36);
      wg_fence();
      mma_mid<W, false>(oh, A_ADDR(s0), B_ADDR(xs(0)));
      wg_commit();
      mma_mid<W, true>(oh, A_ADDR(s1), B_ADDR(xs(1)));
      if (W == 0) mma_main<W, true>(sacc, A_ADDR(s1), B_ADDR(xs(1)));
      wg_commit();
      TL(37);
      pack_second<W>(pk, om, laddr);
      TL(38);
      wg_wait<1>();
      RELEASE_CHUNK(0, s0)
      TL(35); TLG(63);
    }
    TL_FLUSH();
    TL(0); TLG(62);
    ring_advance(ring, 26);
    par ^= 1;
  }
}

__device__ __forceinline__ uint4 lds128(uint32_t a) {
  uint4 v;
  asm volatile("ld.shared.v4.b32 {%0,%1,%2,%3}, [%4];" : "=r"(v.x), "=r"(v.y), "=r"(v.z), "=r"(v.w) : "r"(a) : "memory");
  return v;
}
__device__ __forceinline__ void acc2(float& s, float& t, uint32_t w) {
  s += __uint_as_float(w << 16);
  t += __uint_as_float(w & 0xffff0000u);
}
__device__ __forceinline__ uint32_t badd2(uint32_t a, uint32_t b) { uint32_t r; asm("add.rn.bf16x2 %0, %1, %2;" : "=r"(r) : "r"(a), "r"(b)); return r; }
__device__ __forceinline__ void sum_unit(float& acc, uint32_t pb) {
  const uint4 v0 = lds128(pb), v1 = lds128(pb ^ 32), v2 = lds128(pb ^ 64), v3 = lds128(pb ^ 96);
  const uint32_t w0 = badd2(v0.x, v0.y), w1 = badd2(v0.z, v0.w);
  float s0 = acc + __uint_as_float(w0 << 16), t0 = __uint_as_float(w0 & 0xffff0000u);
  float s1 = __uint_as_float(w1 << 16), t1 = __uint_as_float(w1 & 0xffff0000u);
  acc2(s0, t0, badd2(v1.x, v1.y)); acc2(s1, t1, badd2(v1.z, v1.w));
  acc2(s0, t0, badd2(v2.x, v2.y)); acc2(s1, t1, badd2(v2.z, v2.w));
  acc2(s0, t0, badd2(v3.x, v3.y)); acc2(s1, t1, badd2(v3.z, v3.w));
  acc = (s0 + t0) + (s1 + t1);
}
__device__ __forceinline__ void attn_helper(const Params& p, int hw, const Sched& sc, int epoch) {
  int bud = WAIT_BUDGET;
  const int lane = threadIdx.x & 31, r = lane >> 1;
  const uint32_t a0 = B_ADDR(3) + (16 * hw + r) * 128 + (lane & 1) * 16 + ((r & 3) << 5);
  uint32_t par = 0;
#pragma unroll 1
  for (int it = 0; it < sc.n; it++) {
    const int item = sched_item(sc, it);
    float acc[4] = {0.f, 0.f, 0.f, 0.f};
#pragma unroll 1
    for (int j = 0; j < 8; j++) {
      const uint32_t pb = a0 + (j & 1) * B_SLOT, bfull = BAR_PFULL + (j & 1) * 8, pfull = (j >> 1) & 1;
      mbar_wait(bud, j == 7 ? BAR_PMID : bfull, j == 7 ? par : pfull);
      sum_unit(acc[0], pb);
      if (j == 7) mbar_wait(bud, BAR_PMID + 8, par);
      sum_unit(acc[1], pb + 6144);
      if (j == 7) mbar_wait(bud, bfull, pfull);
      sum_unit(acc[2], pb + 2 * 6144);
      if (hw == 0) sum_unit(acc[3], pb + 3 * 6144);
      __syncwarp();
      mbar_arrive_if0(BAR_PFREE + (j & 1) * 8, lane);
      if (j == 5 && hw == 2 && item >= ORING) flag_wait(bud, &g_done[(item - ORING) >> 4], (epoch + 1) * N_OCTA);
    }
    bool bad = false;
    const uint32_t la = SB + OFF_L + (((r & 7) >> 1) * 40 + 2 * (r >> 3) + (r & 1) + 4 * hw) * 4;
#pragma unroll
    for (int u = 0; u < 4; u++) {
      const float l = acc[u] + __shfl_xor_sync(0xffffffffu, acc[u], 1);
      if (u < 3 || hw == 0) {
        bad |= !(l >= 8.8817841970012523e-16f && l <= 1.125899906842624e15f);
        float inv;
        asm("rcp.approx.ftz.f32 %0, %1;" : "=f"(inv) : "f"(l));
        asm volatile("st.shared.f32 [%0], %1;" ::"r"(la + u * 48), "f"(inv) : "memory");
      }
    }
    publish_generic(BAR_LFULL, lane);
    if (lane == 0) TLP(40 + hw * 4);
    const bool anybad = __any_sync(0xffffffffu, bad);
    if (lane == 0) g_bad[item * 4 + hw] = anybad;
    if (hw == 1) {
      mbar_wait(bud, BAR_OFULL, par);
      if (lane == 0) {
        TLP(41 + hw * 4);
        asm volatile("red.release.gpu.global.add.s32 [%0], 1;" ::"l"(&g_ready[item]) : "memory");
        TLP(42 + hw * 4);
      }
      __syncwarp();
    }
    par ^= 1;
  }
}

__device__ __forceinline__ void attn_producer(const Params& p, const Sched& sc) {
  int bud = WAIT_BUDGET;
  uint32_t sa = 0, pa = 1;
  uint64_t pol;
  asm volatile("createpolicy.fractional.L2::evict_first.b64 %0, 1.0;" : "=l"(pol));
  uint64_t poln;
  asm volatile("createpolicy.fractional.L2::evict_normal.b64 %0, 1.0;" : "=l"(poln));
  if (sc.delay) {
    const long long t0 = clock64();
    while (clock64() - t0 < G2_DELAY) __nanosleep(200);
  }
#pragma unroll 1
  for (int it = 0; it < sc.n; it++) {
    const int item = sched_item(sc, it);
    const int blk = item >> 9, h = (item >> 4) & 31, b = item & 15;
    const int row0 = (b * NH + h) * SK;
#pragma unroll
    for (int c = 0; c < 10; c++) {
      mbar_wait(bud, BAR_EMPTYA + sa * 8, pa);
      TLP(c);
      mbar_expect(BAR_FULLA + sa * 8, A_SLOT + B_SLOT);
      tma3d(A_ADDR(sa), &p.wq[blk], BAR_FULLA + sa * 8, 0, c * 64, h * 3);
      mbar_wait(bud, BAR_EMPTYB + xs(c) * 8, c < NSLOT);
      TLP(10 + c);
      tma2d(B_ADDR(xs(c)), &p.x[blk], BAR_FULLA + sa * 8, c * 64, b * SQ);
      if (++sa == NSLOT) { sa = 0; pa ^= 1; }
    }
#pragma unroll
    for (int i = 0; i < 16; i++) {
      const bool isK = (i == 0) || ((i & 1) && i < 15);
      const int j = i == 0 ? 0 : (i == 15 ? 7 : (isK ? (i + 1) >> 1 : (i - 2) >> 1));
      mbar_wait(bud, BAR_EMPTYA + sa * 8, pa);
      TLP(20 + i);
      mbar_expect(BAR_FULLA + sa * 8, A_SLOT);
      tma3d_hint(A_ADDR(sa), isK ? &p.k[blk] : &p.v[blk], BAR_FULLA + sa * 8, 0, row0 + j * 64, 0, pol);
      if (++sa == NSLOT) { sa = 0; pa ^= 1; }
    }
  }
}

template <int W>
__device__ __forceinline__ void oproj_consumer() {
  int bud = WAIT_BUDGET;
  const int tid = threadIdx.x & 127, lane = tid & 31, warp = tid >> 5;
  const int qrow = 8 * ((lane >> 1) & 1) + 4 * (lane >> 4) + 2 * ((lane >> 2) & 1) + (lane & 1);
  const uint32_t st_off = qrow * 128 + (((2 * warp + ((lane >> 3) & 1)) ^ (qrow & 7)) << 4);
  float a0[64], a1[64], ah[32];
  zero_regs(a0); zero_regs(a1); zero_regs(ah);
#pragma unroll 1
  for (int blk = 0; blk < 2; blk++) {
    int c3 = 0, step = blk * NH;
#pragma unroll 1
    for (int c = 0; c < 96; c++) {
      const uint32_t st = c & 3;
      mbar_wait(bud, BAR_GFULL + st * 8, (c >> 2) & 1);
      wg_fence();
      const uint32_t la = lo_sw(SB + st * O_STAGE), lb = lo_o(SB + st * O_STAGE + O_AB);
#define O_STEP(ks, sc)                                                   \
  mma64r<1, 1, 2 * 8192 + ks * 2048, W * 8192 + ks * 256>(ah, la, lb, sc);    \
  mma128r<1, 1, (W * 3) * 8192 + ks * 2048, ks * 256>(a0, la, lb, sc);        \
  mma128r<1, 1, (W * 3 + 1) * 8192 + ks * 2048, ks * 256>(a1, la, lb, sc);
      O_STEP(0, c != 0) O_STEP(1, 1) O_STEP(2, 1) O_STEP(3, 1)
#undef O_STEP
      wg_commit();
      if (++c3 == 3) {
        c3 = 0;
        if (W == 0)
          asm volatile("{\n.reg .pred p;\nsetp.eq.u32 p, %1, 0;\n@p red.relaxed.gpu.global.add.s32 [%0], 1;\n}\n" ::"l"(&g_done[step]), "r"(tid) : "memory");
        TL(step);
        step++;
      }
      wg_wait<1>();
      mbar_arrive_if0(BAR_GEMPTY + ((c - 1) & 3) * 8, tid | (c == 0) | (c == 95));
    }
    wg_wait<0>();
    reg_fence(a0); reg_fence(a1); reg_fence(ah);
    bar_sync(3, 256);
    const uint32_t sg = SB + 2 * O_STAGE + st_off;
    store_scaled(sg + 2 * 16384 + W * 8192, ah, 1.0f);
    store_scaled(sg + (W * 3) * 16384, a0, 1.0f);
    store_scaled(sg + (W * 3 + 1) * 16384, a1, 1.0f);
    publish(BAR_GOUT, lane);
  }
  TL_FLUSH();
}

__device__ __forceinline__ void oproj_producer(const Params& p, int cta, int epoch) {
  int bud = WAIT_BUDGET;
  const int half = cta & 1, r0 = (cta >> 1) * 128;
  const int b0 = r0 / SQ, off0 = r0 - b0 * SQ, n0 = min(128, SQ - off0), n1 = 128 - n0;
  const int target = epoch + 1;
#pragma unroll 1
  for (int step = 0; step < 2 * NH; step++) {
    const int blk = step >> 5, item0 = step * 16 + b0;
    const char* o0 = (const char*)g_o + (size_t)(item0 % ORING) * O_ITEM_BYTES + off0 * 128;
    const char* o1 = (const char*)g_o + (size_t)((item0 + 1) % ORING) * O_ITEM_BYTES;
#pragma unroll 1
    for (int kb = 0; kb < 3; kb++) {
      const int c = step * 3 + kb;
      const uint32_t st = c & 3, dst = SB + st * O_STAGE, bar = BAR_GFULL + st * 8;
      mbar_wait(bud, BAR_GEMPTY + st * 8, ((c >> 2) & 1) ^ 1);
      mbar_expect(bar, O_STAGE);
      tma3d(dst, &p.wo[blk], bar, 0, ((step & 31) * 3 + kb) * 64, half * 5);
      if (kb == 0) {
        flag_wait(bud, &g_ready[item0], target);
        if (n1) flag_wait(bud, &g_ready[item0 + 1], target);
        asm volatile("fence.proxy.async.global;" ::: "memory");
      }
      bulk_load(dst + O_AB, o0 + kb * B_SLOT, n0 * 128, bar);
      if (n1) bulk_load(dst + O_AB + n0 * 128, o1 + kb * B_SLOT, n1 * 128, bar);
    }
  }
}

__device__ __forceinline__ void oproj_storer(const Params& p, int cta) {
  int bud = WAIT_BUDGET;
  const int half = cta & 1, r0 = (cta >> 1) * 128;
#pragma unroll 1
  for (int blk = 0; blk < 2; blk++) {
    mbar_wait(bud, BAR_GOUT, blk);
    for (int k = 0; k < 5; k++) tma_store2d(&p.out, SB + 2 * O_STAGE + k * 16384, blk * DM + half * 320 + k * 64, r0);
    asm volatile("cp.async.bulk.commit_group;" ::: "memory");
    asm volatile("cp.async.bulk.wait_group.read 0;" ::: "memory");
    mbar_arrive2_if0(BAR_GEMPTY + 16, 0);
    mbar_arrive2_if0(BAR_GEMPTY + 24, 0);
  }
  asm volatile("cp.async.bulk.wait_group 0;" ::: "memory");
}

__global__ void __launch_bounds__(384, 1) fused_kernel(const __grid_constant__ Params p) {
  extern __shared__ __align__(1024) char smem_raw[];
  if ((smem_u32(smem_raw) & 0xFFFFFFu) != SB) return;
  const int cta = blockIdx.x;
  const int epoch = g_epoch[cta];
  if (threadIdx.x == 0) {
    for (int i = 0; i < NSLOT; i++) {
      mbar_init(BAR_FULLA + i * 8, 1); mbar_init(BAR_EMPTYA + i * 8, 2);
      mbar_init(BAR_EMPTYB + i * 8, 2);
    }
    mbar_init(BAR_XDONE, 2); mbar_init(BAR_QH, 8); mbar_init(BAR_QM, 4); mbar_init(BAR_QM + 8, 4);
    mbar_init(BAR_PFULL, 4); mbar_init(BAR_PFULL + 8, 4);
    mbar_init(BAR_PFREE, 3); mbar_init(BAR_PFREE + 8, 3);
    mbar_init(BAR_LFULL, 3); mbar_init(BAR_PMID, 4); mbar_init(BAR_PMID + 8, 4);
    mbar_init(BAR_OFULL, 8);
    for (int i = 0; i < O_NST; i++) { mbar_init(BAR_GFULL + i * 8, 1); mbar_init(BAR_GEMPTY + i * 8, 2); }
    mbar_init(BAR_GOUT, 8);
    asm volatile("fence.mbarrier_init.release.cluster;" ::: "memory");
    proxy_fence();
  }
  __syncthreads();
  if (threadIdx.x == 0) g_epoch[cta] = epoch + 1;
  const int warp = __shfl_sync(0xffffffffu, threadIdx.x >> 5, 0);
  const Sched sc = get_sched(cta);
  if (warp >= 8) {
    asm volatile("setmaxnreg.dec.sync.aligned.u32 40;");
    if (warp == 8) {
      if (elect_one()) attn_producer(p, sc);
      __syncwarp();
    } else {
      attn_helper(p, warp - 9, sc, epoch);
    }
    if (cta < N_OCTA) {
      bar_sync(4, 128);
      if (warp == 8) {
        if (elect_one()) oproj_producer(p, cta, epoch);
      } else if (warp == 9) {
        if (elect_one()) oproj_storer(p, cta);
      }
    }
  } else {
    asm volatile("setmaxnreg.inc.sync.aligned.u32 232;");
    if (warp < 4) {
      attn_consumer<0>(sc);
      if (cta < N_OCTA) oproj_consumer<0>();
    } else {
      attn_consumer<1>(sc);
      if (cta < N_OCTA) oproj_consumer<1>();
    }
  }
}

typedef CUresult (*EncodeFn)(CUtensorMap*, CUtensorMapDataType, cuuint32_t, void*, const cuuint64_t*, const cuuint64_t*, const cuuint32_t*,
                             const cuuint32_t*, CUtensorMapInterleave, CUtensorMapSwizzle, CUtensorMapL2promotion, CUtensorMapFloatOOBfill);

void make3d(EncodeFn enc, CUtensorMap* m, const void* ptr, uint64_t rows, uint64_t cols, uint32_t box_rows, uint32_t box_blocks,
            CUtensorMapL2promotion promo = CU_TENSOR_MAP_L2_PROMOTION_L2_128B) {
  cuuint64_t gd[3] = {64, rows, cols / 64};
  cuuint64_t gs[2] = {cols * 2, 128};
  cuuint32_t bd[3] = {64, box_rows, box_blocks}, es[3] = {1, 1, 1};
  enc(m, CU_TENSOR_MAP_DATA_TYPE_BFLOAT16, 3, (void*)ptr, gd, gs, bd, es, CU_TENSOR_MAP_INTERLEAVE_NONE, CU_TENSOR_MAP_SWIZZLE_128B,
      promo, CU_TENSOR_MAP_FLOAT_OOB_FILL_NONE);
}
void make2d(EncodeFn enc, CUtensorMap* m, const void* ptr, uint64_t rows, uint64_t cols, uint32_t box_rows) {
  cuuint64_t gd[2] = {cols, rows};
  cuuint64_t gs[1] = {cols * 2};
  cuuint32_t bd[2] = {64, box_rows}, es[2] = {1, 1};
  enc(m, CU_TENSOR_MAP_DATA_TYPE_BFLOAT16, 2, (void*)ptr, gd, gs, bd, es, CU_TENSOR_MAP_INTERLEAVE_NONE, CU_TENSOR_MAP_SWIZZLE_128B,
      CU_TENSOR_MAP_L2_PROMOTION_L2_128B, CU_TENSOR_MAP_FLOAT_OOB_FILL_NONE);
}

}

extern "C" void kernel_launch(void* const* d_in, const int* in_sizes, int n_in, void* d_out, int out_size) {
  static EncodeFn enc = nullptr;
  if (!enc) {
    cudaDriverEntryPointQueryResult qr;
    cudaGetDriverEntryPoint("cuTensorMapEncodeTiled", (void**)&enc, cudaEnableDefault, &qr);
    cudaFuncSetAttribute(fused_kernel, cudaFuncAttributeMaxDynamicSharedMemorySize, SMEM_BYTES);
  }
  Params p;
  for (int s = 0; s < 2; s++) {
    make2d(enc, &p.x[s], d_in[5 * s + 0], NB * SQ, DM, SQ);
    make3d(enc, &p.k[s], d_in[5 * s + 1], (uint64_t)NB * NH * SK, DH, 64, 3, KV_PROMO);
    make3d(enc, &p.v[s], d_in[5 * s + 2], (uint64_t)NB * NH * SK, DH, 64, 3, KV_PROMO);
    make3d(enc, &p.wq[s], d_in[5 * s + 3], DM, NH * DH, 64, 3);
    make3d(enc, &p.wo[s], d_in[5 * s + 4], NH * DH, DM, 64, 5);
    p.kp[s] = (const __nv_bfloat16*)d_in[5 * s + 1];
    p.vp[s] = (const __nv_bfloat16*)d_in[5 * s + 2];
  }
  make2d(enc, &p.out, d_out, NB * SQ, 2 * DM, 128);
  fused_kernel<<<NCTA, 384, SMEM_BYTES>>>(p);
}
```

```cpp
#include <cuda_runtime.h>
#include <cuda_bf16.h>
#include <cuda.h>
#include <stdint.h>

#define DEBUG_TIMEOUT 1

namespace {

constexpr int SQ = 160, DM = 640, NH = 32, SK = 512, DH = 192, NB = 16;
constexpr int NITEMS = 2 * NB * NH;
constexpr int NCTA = 132, N_OCTA = 40, N_G2 = 28, N_G1 = 64, N_ATT = N_G1 + N_G2;
#define ORING 112
#define KV_PROMO CU_TENSOR_MAP_L2_PROMOTION_L2_128B
#define G2_DELAY 13000
constexpr int A_SLOT = 24576, B_SLOT = 20480, NSLOT = 5;
constexpr int OFF_A = 0;
constexpr int OFF_B = NSLOT * A_SLOT;
constexpr int O_STAGE = 57344, O_AB = 40960, O_NST = 4;
constexpr int OFF_L = O_NST * O_STAGE;
constexpr int OFF_BAR = OFF_L + 160 * 4;
constexpr int SMEM_BYTES = OFF_BAR + 384 + 512;
static_assert(OFF_B + NSLOT * B_SLOT <= OFF_L, "smem layout");
constexpr uint32_t SB = 1024;
constexpr uint32_t BARS = SB + OFF_BAR;
constexpr uint32_t BAR_FULLA = BARS, BAR_EMPTYA = BARS + 40, BAR_PMID = BARS + 80, BAR_EMPTYB = BARS + 120, BAR_XDONE = BARS + 160,
                   BAR_QH = BARS + 168, BAR_QM = BARS + 96, BAR_PFULL = BARS + 184, BAR_PFREE = BARS + 200, BAR_LFULL = BARS + 216,
                   BAR_OFULL = BARS + 224, BAR_GFULL = BARS + 248, BAR_GEMPTY = BARS + 280, BAR_GOUT = BARS + 312;
constexpr int O_ITEM_BYTES = SQ * DH * 2;

struct alignas(64) Params {
  CUtensorMap x[2], wq[2], k[2], v[2], wo[2], out;
  const __nv_bfloat16* kp[2];
  const __nv_bfloat16* vp[2];
};

__device__ uint4 g_o[(size_t)ORING * O_ITEM_BYTES / 16];
__device__ int g_ready[NITEMS];
__device__ int g_done[2 * NH];
__device__ int g_epoch[NCTA];
__device__ int g_bad[NITEMS * 4];

#define TLP(id)
#define TLG(id)
#define TL(id)
#define TL_FLUSH()
__device__ __forceinline__ uint32_t smem_u32(const void* p) { return (uint32_t)__cvta_generic_to_shared(p); }
__device__ __forceinline__ void wg_fence() { asm volatile("wgmma.fence.sync.aligned;" ::: "memory"); }
__device__ __forceinline__ void wg_commit() { asm volatile("wgmma.commit_group.sync.aligned;" ::: "memory"); }
template <int N> __device__ __forceinline__ void wg_wait() { asm volatile("wgmma.wait_group.sync.aligned %0;" ::"n"(N) : "memory"); }
template <int N> __device__ __forceinline__ void reg_fence(float (&d)[N]) {
#pragma unroll
  for (int i = 0; i < N; i++) asm volatile("" : "+f"(d[i])::"memory");
}
template <int N> __device__ __forceinline__ void zero_regs(float (&d)[N]) {
#pragma unroll
  for (int i = 0; i < N; i++) d[i] = 0.f;
}
__device__ __forceinline__ void proxy_fence() { asm volatile("fence.proxy.async.shared::cta;" ::: "memory"); }
__device__ __forceinline__ void mbar_init(uint32_t bar, int cnt) { asm volatile("mbarrier.init.shared::cta.b64 [%0], %1;" ::"r"(bar), "r"(cnt) : "memory"); }
__device__ __forceinline__ void mbar_arrive_if0(uint32_t bar, uint32_t sel) {
  asm volatile("{\n.reg .pred p;\nsetp.eq.u32 p, %1, 0;\n@p mbarrier.arrive.shared::cta.b64 _, [%0];\n}\n" ::"r"(bar), "r"(sel) : "memory");
}
__device__ __forceinline__ void mbar_arrive2_if0(uint32_t bar, uint32_t sel) {
  asm volatile("{\n.reg .pred p;\nsetp.eq.u32 p, %1, 0;\n@p mbarrier.arrive.shared::cta.b64 _, [%0], 2;\n}\n" ::"r"(bar), "r"(sel) : "memory");
}
__device__ __forceinline__ void mbar_expect(uint32_t bar, uint32_t bytes) {
  asm volatile("mbarrier.arrive.expect_tx.shared::cta.b64 _, [%0], %1;" ::"r"(bar), "r"(bytes) : "memory");
}
__device__ __forceinline__ void mbar_wait(int& bud, uint32_t bar, uint32_t parity) {
  asm volatile(
      "{\n.reg .pred p, q;\n"
      "LW:\n"
      "mbarrier.try_wait.parity.shared::cta.b64 p, [%1], %2;\n"
      "@!p add.s32 %0, %0, -1;\n"
      "setp.gt.and.s32 q, %0, 0, !p;\n"
      "@q bra LW;\n}\n" : "+r"(bud) : "r"(bar), "r"(parity) : "memory");
}
constexpr int WAIT_BUDGET = 1 << 20;
__device__ __forceinline__ bool elect_one() {
  uint32_t p;
  asm volatile("{\n.reg .pred p;\nelect.sync _|p, 0xffffffff;\nselp.u32 %0, 1, 0, p;\n}\n" : "=r"(p));
  return p;
}
__device__ __forceinline__ void tma2d(uint32_t dst, const CUtensorMap* m, uint32_t bar, int c0, int c1) {
  asm volatile("cp.async.bulk.tensor.2d.shared::cluster.global.mbarrier::complete_tx::bytes [%0], [%1, {%3, %4}], [%2];"
               ::"r"(dst), "l"(m), "r"(bar), "r"(c0), "r"(c1) : "memory");
}
__device__ __forceinline__ void tma3d(uint32_t dst, const CUtensorMap* m, uint32_t bar, int c0, int c1, int c2) {
  asm volatile("cp.async.bulk.tensor.3d.shared::cluster.global.mbarrier::complete_tx::bytes [%0], [%1, {%3, %4, %5}], [%2];"
               ::"r"(dst), "l"(m), "r"(bar), "r"(c0), "r"(c1), "r"(c2) : "memory");
}
__device__ __forceinline__ void tma3d_hint(uint32_t dst, const CUtensorMap* m, uint32_t bar, int c0, int c1, int c2, uint64_t pol) {
  asm volatile("cp.async.bulk.tensor.3d.shared::cluster.global.mbarrier::complete_tx::bytes.L2::cache_hint [%0], [%1, {%3, %4, %5}], [%2], %6;"
               ::"r"(dst), "l"(m), "r"(bar), "r"(c0), "r"(c1), "r"(c2), "l"(pol) : "memory");
}
__device__ __forceinline__ void bulk_load(uint32_t dst, const void* src, uint32_t bytes, uint32_t bar) {
  asm volatile("cp.async.bulk.shared::cluster.global.mbarrier::complete_tx::bytes [%0], [%1], %2, [%3];"
               ::"r"(dst), "l"(src), "r"(bytes), "r"(bar) : "memory");
}
__device__ __forceinline__ void l2_prefetch(const void* src, uint32_t bytes) {
  asm volatile("cp.async.bulk.prefetch.L2.global [%0], %1;" ::"l"(src), "r"(bytes) : "memory");
}
__device__ __forceinline__ void l2_prefetch_hint(const void* src, uint32_t bytes, uint64_t pol) {
  asm volatile("cp.async.bulk.prefetch.L2.global.L2::cache_hint [%0], %1, %2;" ::"l"(src), "r"(bytes), "l"(pol) : "memory");
}
__device__ __forceinline__ void tma_store2d(const CUtensorMap* m, uint32_t src, int c0, int c1) {
  asm volatile("cp.async.bulk.tensor.2d.global.shared::cta.bulk_group [%0, {%2, %3}], [%1];" ::"l"(m), "r"(src), "r"(c0), "r"(c1) : "memory");
}
__device__ __forceinline__ void bar_sync(int id, int n) { asm volatile("bar.sync %0, %1;" ::"r"(id), "r"(n) : "memory"); }
__device__ __forceinline__ void bar_arrive(int id, int n) { asm volatile("bar.arrive %0, %1;" ::"r"(id), "r"(n) : "memory"); }
__device__ __forceinline__ float ex2(float x) { float y; asm("ex2.approx.ftz.f32 %0, %1;" : "=f"(y) : "f"(x)); return y; }
__device__ __forceinline__ uint32_t pack2(float lo, float hi) { uint32_t r; asm("cvt.rn.bf16x2.f32 %0, %1, %2;" : "=r"(r) : "f"(hi), "f"(lo)); return r; }
__device__ __forceinline__ void stsm_t(uint32_t a, uint32_t r0, uint32_t r1, uint32_t r2, uint32_t r3) {
  asm volatile("stmatrix.sync.aligned.m8n8.x4.trans.shared.b16 [%0], {%1,%2,%3,%4};" ::"r"(a), "r"(r0), "r"(r1), "r"(r2), "r"(r3) : "memory");
}
__device__ __forceinline__ void flag_wait(int& bud, const int* p, int target) {
  while (true) {
    int v;
    asm volatile("ld.acquire.gpu.global.s32 %0, [%1];" : "=r"(v) : "l"(p) : "memory");
    if (v - target >= 0 || --bud <= 0) break;
    __nanosleep(64);
  }
}
__device__ __forceinline__ uint32_t lo_sw(uint32_t addr) { return (addr >> 4) | (1u << 16); }
__device__ __forceinline__ uint32_t lo_o(uint32_t addr) { return (addr >> 4) | (8u << 16); }
__device__ __forceinline__ uint32_t opaque(uint32_t x) { uint32_t y; asm volatile("mov.u32 %0, %1;" : "=r"(y) : "r"(x)); return y; }

template <int TA, int TB, uint32_t OA, uint32_t OB>
__device__ __forceinline__ void mma160(float (&d)[80], uint32_t la, uint32_t lb) {
  asm volatile(
      "{\n.reg .pred p;\n.reg .b32 a, b;\n.reg .b64 da, db;\nsetp.eq.b32 p, 0, 0;\n"
      "add.u32 a, %80, %84;\nadd.u32 b, %81, %85;\nmov.b64 da, {a, 0x40000040};\nmov.b64 db, {b, %86};\n"
      "wgmma.mma_async.sync.aligned.m64n160k16.f32.bf16.bf16 {"
      "%0,%1,%2,%3,%4,%5,%6,%7,%8,%9,%10,%11,%12,%13,%14,%15,%16,%17,%18,%19,%20,%21,%22,%23,%24,%25,%26,%27,%28,%29,%30,%31,%32,%33,%34,%35,%36,"
      "%37,%38,%39,%40,%41,%42,%43,%44,%45,%46,%47,%48,%49,%50,%51,%52,%53,%54,%55,%56,%57,%58,%59,%60,%61,%62,%63,%64,%65,%66,%67,%68,%69,%70,%71,"
      "%72,%73,%74,%75,%76,%77,%78,%79"
      "}, da, db, p, 1, 1, %82, %83;\n}\n"
      :
      "+f"(d[0]),"+f"(d[1]),"+f"(d[2]),"+f"(d[3]),"+f"(d[4]),"+f"(d[5]),"+f"(d[6]),"+f"(d[7]),"+f"(d[8]),"+f"(d[9]),"+f"(d[10]),"+f"(d[11]),
      "+f"(d[12]),"+f"(d[13]),"+f"(d[14]),"+f"(d[15]),"+f"(d[16]),"+f"(d[17]),"+f"(d[18]),"+f"(d[19]),"+f"(d[20]),"+f"(d[21]),"+f"(d[22]),
      "+f"(d[23]),"+f"(d[24]),"+f"(d[25]),"+f"(d[26]),"+f"(d[27]),"+f"(d[28]),"+f"(d[29]),"+f"(d[30]),"+f"(d[31]),"+f"(d[32]),"+f"(d[33]),
      "+f"(d[34]),"+f"(d[35]),"+f"(d[36]),"+f"(d[37]),"+f"(d[38]),"+f"(d[39]),"+f"(d[40]),"+f"(d[41]),"+f"(d[42]),"+f"(d[43]),"+f"(d[44]),
      "+f"(d[45]),"+f"(d[46]),"+f"(d[47]),"+f"(d[48]),"+f"(d[49]),"+f"(d[50]),"+f"(d[51]),"+f"(d[52]),"+f"(d[53]),"+f"(d[54]),"+f"(d[55]),
      "+f"(d[56]),"+f"(d[57]),"+f"(d[58]),"+f"(d[59]),"+f"(d[60]),"+f"(d[61]),"+f"(d[62]),"+f"(d[63]),"+f"(d[64]),"+f"(d[65]),"+f"(d[66]),
      "+f"(d[67]),"+f"(d[68]),"+f"(d[69]),"+f"(d[70]),"+f"(d[71]),"+f"(d[72]),"+f"(d[73]),"+f"(d[74]),"+f"(d[75]),"+f"(d[76]),"+f"(d[77]),
      "+f"(d[78]),"+f"(d[79])
      : "r"(la), "r"(lb), "n"(TA), "n"(TB), "n"(OA >> 4), "n"(OB >> 4), "n"(TB ? 0x40 : 0x40000040));
}

template <int TA, int TB, uint32_t OA, uint32_t OB>
__device__ __forceinline__ void mma160z(float (&d)[80], uint32_t la, uint32_t lb) {
  asm volatile(
      "{\n.reg .pred p;\n.reg .b32 a, b;\n.reg .b64 da, db;\nsetp.ne.b32 p, 0, 0;\n"
      "add.u32 a, %80, %84;\nadd.u32 b, %81, %85;\nmov.b64 da, {a, 0x40000040};\nmov.b64 db, {b, %86};\n"
      "wgmma.mma_async.sync.aligned.m64n160k16.f32.bf16.bf16 {"
      "%0,%1,%2,%3,%4,%5,%6,%7,%8,%9,%10,%11,%12,%13,%14,%15,%16,%17,%18,%19,%20,%21,%22,%23,%24,%25,%26,%27,%28,%29,%30,%31,%32,%33,%34,%35,%36,"
      "%37,%38,%39,%40,%41,%42,%43,%44,%45,%46,%47,%48,%49,%50,%51,%52,%53,%54,%55,%56,%57,%58,%59,%60,%61,%62,%63,%64,%65,%66,%67,%68,%69,%70,%71,"
      "%72,%73,%74,%75,%76,%77,%78,%79"
      "}, da, db, p, 1, 1, %82, %83;\n}\n"
      :
      "=f"(d[0]),"=f"(d[1]),"=f"(d[2]),"=f"(d[3]),"=f"(d[4]),"=f"(d[5]),"=f"(d[6]),"=f"(d[7]),"=f"(d[8]),"=f"(d[9]),"=f"(d[10]),"=f"(d[11]),
      "=f"(d[12]),"=f"(d[13]),"=f"(d[14]),"=f"(d[15]),"=f"(d[16]),"=f"(d[17]),"=f"(d[18]),"=f"(d[19]),"=f"(d[20]),"=f"(d[21]),"=f"(d[22]),
      "=f"(d[23]),"=f"(d[24]),"=f"(d[25]),"=f"(d[26]),"=f"(d[27]),"=f"(d[28]),"=f"(d[29]),"=f"(d[30]),"=f"(d[31]),"=f"(d[32]),"=f"(d[33]),
      "=f"(d[34]),"=f"(d[35]),"=f"(d[36]),"=f"(d[37]),"=f"(d[38]),"=f"(d[39]),"=f"(d[40]),"=f"(d[41]),"=f"(d[42]),"=f"(d[43]),"=f"(d[44]),
      "=f"(d[45]),"=f"(d[46]),"=f"(d[47]),"=f"(d[48]),"=f"(d[49]),"=f"(d[50]),"=f"(d[51]),"=f"(d[52]),"=f"(d[53]),"=f"(d[54]),"=f"(d[55]),
      "=f"(d[56]),"=f"(d[57]),"=f"(d[58]),"=f"(d[59]),"=f"(d[60]),"=f"(d[61]),"=f"(d[62]),"=f"(d[63]),"=f"(d[64]),"=f"(d[65]),"=f"(d[66]),
      "=f"(d[67]),"=f"(d[68]),"=f"(d[69]),"=f"(d[70]),"=f"(d[71]),"=f"(d[72]),"=f"(d[73]),"=f"(d[74]),"=f"(d[75]),"=f"(d[76]),"=f"(d[77]),
      "=f"(d[78]),"=f"(d[79])
      : "r"(la), "r"(lb), "n"(TA), "n"(TB), "n"(OA >> 4), "n"(OB >> 4), "n"(TB ? 0x40 : 0x40000040));
}

template <int TA, int TB, uint32_t OA, uint32_t OB>
__device__ __forceinline__ void mma80(float (&d)[40], uint32_t la, uint32_t lb) {
  asm volatile(
      "{\n.reg .pred p;\n.reg .b32 a, b;\n.reg .b64 da, db;\nsetp.eq.b32 p, 0, 0;\n"
      "add.u32 a, %40, %44;\nadd.u32 b, %41, %45;\nmov.b64 da, {a, 0x40000040};\nmov.b64 db, {b, %46};\n"
      "wgmma.mma_async.sync.aligned.m64n80k16.f32.bf16.bf16 {"
      "%0,%1,%2,%3,%4,%5,%6,%7,%8,%9,%10,%11,%12,%13,%14,%15,%16,%17,%18,%19,%20,%21,%22,%23,%24,%25,%26,%27,%28,%29,%30,%31,%32,%33,%34,%35,%36,"
      "%37,%38,%39"
      "}, da, db, p, 1, 1, %42, %43;\n}\n"
      :
      "+f"(d[0]),"+f"(d[1]),"+f"(d[2]),"+f"(d[3]),"+f"(d[4]),"+f"(d[5]),"+f"(d[6]),"+f"(d[7]),"+f"(d[8]),"+f"(d[9]),"+f"(d[10]),"+f"(d[11]),
      "+f"(d[12]),"+f"(d[13]),"+f"(d[14]),"+f"(d[15]),"+f"(d[16]),"+f"(d[17]),"+f"(d[18]),"+f"(d[19]),"+f"(d[20]),"+f"(d[21]),"+f"(d[22]),
      "+f"(d[23]),"+f"(d[24]),"+f"(d[25]),"+f"(d[26]),"+f"(d[27]),"+f"(d[28]),"+f"(d[29]),"+f"(d[30]),"+f"(d[31]),"+f"(d[32]),"+f"(d[33]),
      "+f"(d[34]),"+f"(d[35]),"+f"(d[36]),"+f"(d[37]),"+f"(d[38]),"+f"(d[39])
      : "r"(la), "r"(lb), "n"(TA), "n"(TB), "n"(OA >> 4), "n"(OB >> 4), "n"(TB ? 0x40 : 0x40000040));
}

template <int TA, int TB, uint32_t OA, uint32_t OB>
__device__ __forceinline__ void mma80z(float (&d)[40], uint32_t la, uint32_t lb) {
  asm volatile(
      "{\n.reg .pred p;\n.reg .b32 a, b;\n.reg .b64 da, db;\nsetp.ne.b32 p, 0, 0;\n"
      "add.u32 a, %40, %44;\nadd.u32 b, %41, %45;\nmov.b64 da, {a, 0x40000040};\nmov.b64 db, {b, %46};\n"
      "wgmma.mma_async.sync.aligned.m64n80k16.f32.bf16.bf16 {"
      "%0,%1,%2,%3,%4,%5,%6,%7,%8,%9,%10,%11,%12,%13,%14,%15,%16,%17,%18,%19,%20,%21,%22,%23,%24,%25,%26,%27,%28,%29,%30,%31,%32,%33,%34,%35,%36,"
      "%37,%38,%39"
      "}, da, db, p, 1, 1, %42, %43;\n}\n"
      :
      "=f"(d[0]),"=f"(d[1]),"=f"(d[2]),"=f"(d[3]),"=f"(d[4]),"=f"(d[5]),"=f"(d[6]),"=f"(d[7]),"=f"(d[8]),"=f"(d[9]),"=f"(d[10]),"=f"(d[11]),
      "=f"(d[12]),"=f"(d[13]),"=f"(d[14]),"=f"(d[15]),"=f"(d[16]),"=f"(d[17]),"=f"(d[18]),"=f"(d[19]),"=f"(d[20]),"=f"(d[21]),"=f"(d[22]),
      "=f"(d[23]),"=f"(d[24]),"=f"(d[25]),"=f"(d[26]),"=f"(d[27]),"=f"(d[28]),"=f"(d[29]),"=f"(d[30]),"=f"(d[31]),"=f"(d[32]),"=f"(d[33]),
      "=f"(d[34]),"=f"(d[35]),"=f"(d[36]),"=f"(d[37]),"=f"(d[38]),"=f"(d[39])
      : "r"(la), "r"(lb), "n"(TA), "n"(TB), "n"(OA >> 4), "n"(OB >> 4), "n"(TB ? 0x40 : 0x40000040));
}

template <int TA, int TB, uint32_t OA, uint32_t OB>
__device__ __forceinline__ void mma128r(float (&d)[64], uint32_t la, uint32_t lb, int sc) {
  asm volatile(
      "{\n.reg .pred p;\n.reg .b32 a, b;\n.reg .b64 da, db;\nsetp.ne.b32 p, %71, 0;\n"
      "add.u32 a, %64, %68;\nadd.u32 b, %65, %69;\nmov.b64 da, {a, 0x40000040};\nmov.b64 db, {b, %70};\n"
      "wgmma.mma_async.sync.aligned.m64n128k16.f32.bf16.bf16 {"
      "%0,%1,%2,%3,%4,%5,%6,%7,%8,%9,%10,%11,%12,%13,%14,%15,%16,%17,%18,%19,%20,%21,%22,%23,%24,%25,%26,%27,%28,%29,%30,%31,%32,%33,%34,%35,%36,"
      "%37,%38,%39,%40,%41,%42,%43,%44,%45,%46,%47,%48,%49,%50,%51,%52,%53,%54,%55,%56,%57,%58,%59,%60,%61,%62,%63"
      "}, da, db, p, 1, 1, %66, %67;\n}\n"
      :
      "+f"(d[0]),"+f"(d[1]),"+f"(d[2]),"+f"(d[3]),"+f"(d[4]),"+f"(d[5]),"+f"(d[6]),"+f"(d[7]),"+f"(d[8]),"+f"(d[9]),"+f"(d[10]),"+f"(d[11]),
      "+f"(d[12]),"+f"(d[13]),"+f"(d[14]),"+f"(d[15]),"+f"(d[16]),"+f"(d[17]),"+f"(d[18]),"+f"(d[19]),"+f"(d[20]),"+f"(d[21]),"+f"(d[22]),
      "+f"(d[23]),"+f"(d[24]),"+f"(d[25]),"+f"(d[26]),"+f"(d[27]),"+f"(d[28]),"+f"(d[29]),"+f"(d[30]),"+f"(d[31]),"+f"(d[32]),"+f"(d[33]),
      "+f"(d[34]),"+f"(d[35]),"+f"(d[36]),"+f"(d[37]),"+f"(d[38]),"+f"(d[39]),"+f"(d[40]),"+f"(d[41]),"+f"(d[42]),"+f"(d[43]),"+f"(d[44]),
      "+f"(d[45]),"+f"(d[46]),"+f"(d[47]),"+f"(d[48]),"+f"(d[49]),"+f"(d[50]),"+f"(d[51]),"+f"(d[52]),"+f"(d[53]),"+f"(d[54]),"+f"(d[55]),
      "+f"(d[56]),"+f"(d[57]),"+f"(d[58]),"+f"(d[59]),"+f"(d[60]),"+f"(d[61]),"+f"(d[62]),"+f"(d[63])
      : "r"(la), "r"(lb), "n"(TA), "n"(TB), "n"(OA >> 4), "n"(OB >> 4), "n"(TB ? 0x40 : 0x40000040), "r"(sc));
}

template <int TA, int TB, uint32_t OA, uint32_t OB>
__device__ __forceinline__ void mma64r(float (&d)[32], uint32_t la, uint32_t lb, int sc) {
  asm volatile(
      "{\n.reg .pred p;\n.reg .b32 a, b;\n.reg .b64 da, db;\nsetp.ne.b32 p, %39, 0;\n"
      "add.u32 a, %32, %36;\nadd.u32 b, %33, %37;\nmov.b64 da, {a, 0x40000040};\nmov.b64 db, {b, %38};\n"
      "wgmma.mma_async.sync.aligned.m64n64k16.f32.bf16.bf16 {"
      "%0,%1,%2,%3,%4,%5,%6,%7,%8,%9,%10,%11,%12,%13,%14,%15,%16,%17,%18,%19,%20,%21,%22,%23,%24,%25,%26,%27,%28,%29,%30,%31"
      "}, da, db, p, 1, 1, %34, %35;\n}\n"
      :
      "+f"(d[0]),"+f"(d[1]),"+f"(d[2]),"+f"(d[3]),"+f"(d[4]),"+f"(d[5]),"+f"(d[6]),"+f"(d[7]),"+f"(d[8]),"+f"(d[9]),"+f"(d[10]),"+f"(d[11]),
      "+f"(d[12]),"+f"(d[13]),"+f"(d[14]),"+f"(d[15]),"+f"(d[16]),"+f"(d[17]),"+f"(d[18]),"+f"(d[19]),"+f"(d[20]),"+f"(d[21]),"+f"(d[22]),
      "+f"(d[23]),"+f"(d[24]),"+f"(d[25]),"+f"(d[26]),"+f"(d[27]),"+f"(d[28]),"+f"(d[29]),"+f"(d[30]),"+f"(d[31])
      : "r"(la), "r"(lb), "n"(TA), "n"(TB), "n"(OA >> 4), "n"(OB >> 4), "n"(TB ? 0x40 : 0x40000040), "r"(sc));
}

struct Ring { uint32_t s0, ph0; };
__device__ __forceinline__ void ring_pos(const Ring& r, int i, uint32_t& slot, uint32_t& ph) {
  uint32_t s = opaque(r.s0) + (i % NSLOT);
  uint32_t wrap = s >= NSLOT;
  slot = s - (wrap ? NSLOT : 0);
  ph = r.ph0 ^ ((i / NSLOT) & 1) ^ wrap;
}
__device__ __forceinline__ void ring_advance(Ring& r, int n) {
  uint32_t s, p;
  ring_pos(r, n, s, p);
  r.s0 = s; r.ph0 = p;
}
__host__ __device__ constexpr int idxK(int j) { return j == 0 ? 10 : 9 + 2 * j; }
__host__ __device__ constexpr int idxV(int j) { return j == 7 ? 25 : 12 + 2 * j; }
__host__ __device__ constexpr int xs(int c) { return c % NSLOT; }

struct Sched { int first, second, n, delay; };
__device__ __forceinline__ Sched get_sched(int cta) {
  if (cta < N_OCTA) return Sched{cta, 0, 1, 0};
  if (cta < N_OCTA + N_G1) return Sched{cta, NCTA + (cta - N_OCTA), 11, 0};
  return Sched{cta, cta + N_ATT, 10, 1};
}
__device__ __forceinline__ int sched_item(const Sched& s, int k) { return k == 0 ? s.first : s.second + (k - 1) * N_ATT; }

template <int W, bool ACC>
__device__ __forceinline__ void mma_main(float (&d)[80], uint32_t aaddr, uint32_t baddr) {
  const uint32_t la = lo_sw(aaddr), lb = lo_sw(baddr);
  if (ACC) mma160<1, 0, W * 16384, 0>(d, la, lb); else mma160z<1, 0, W * 16384, 0>(d, la, lb);
  mma160<1, 0, W * 16384 + 1 * 2048, 1 * 32>(d, la, lb);
  mma160<1, 0, W * 16384 + 2 * 2048, 2 * 32>(d, la, lb);
  mma160<1, 0, W * 16384 + 3 * 2048, 3 * 32>(d, la, lb);
}
template <int W, bool ACC>
__device__ __forceinline__ void mma_mid(float (&d)[40], uint32_t aaddr, uint32_t baddr) {
  const uint32_t la = lo_sw(aaddr), lb = lo_sw(baddr);
  if (ACC) mma80<1, 0, 8192, W * 10240>(d, la, lb); else mma80z<1, 0, 8192, W * 10240>(d, la, lb);
  mma80<1, 0, 8192 + 1 * 2048, W * 10240 + 1 * 32>(d, la, lb);
  mma80<1, 0, 8192 + 2 * 2048, W * 10240 + 2 * 32>(d, la, lb);
  mma80<1, 0, 8192 + 3 * 2048, W * 10240 + 3 * 32>(d, la, lb);
}
template <int W, bool ACC>
__device__ __forceinline__ void mma_both(float (&dm)[80], float (&dh)[40], uint32_t aaddr, uint32_t baddr) {
  mma_mid<W, ACC>(dh, aaddr, baddr);
  mma_main<W, ACC>(dm, aaddr, baddr);
}
template <int KB, bool ACC>
__device__ __forceinline__ void s_mma(float (&sacc)[80], uint32_t kaddr) {
  const uint32_t la = lo_sw(kaddr), lb = lo_sw(SB + OFF_B);
  if (ACC) mma160<0, 0, KB * 8192, KB * B_SLOT>(sacc, la, lb); else mma160z<0, 0, KB * 8192, KB * B_SLOT>(sacc, la, lb);
  mma160<0, 0, KB * 8192 + 32, KB * B_SLOT + 32>(sacc, la, lb);
  mma160<0, 0, KB * 8192 + 64, KB * B_SLOT + 64>(sacc, la, lb);
  mma160<0, 0, KB * 8192 + 96, KB * B_SLOT + 96>(sacc, la, lb);
}
template <int N>
__device__ __forceinline__ void store_scaled(uint32_t addr, const float (&d)[N], float sc) {
#pragma unroll
  for (int J = 0; J < N / 8; J++)
    stsm_t(addr + J * 2048, pack2(d[8 * J] * sc, d[8 * J + 1] * sc), pack2(d[8 * J + 2] * sc, d[8 * J + 3] * sc),
           pack2(d[8 * J + 4] * sc, d[8 * J + 5] * sc), pack2(d[8 * J + 6] * sc, d[8 * J + 7] * sc));
}
__device__ __forceinline__ float4 lds_f4(uint32_t a) {
  float4 v;
  asm volatile("ld.shared.v4.f32 {%0,%1,%2,%3}, [%4];" : "=f"(v.x), "=f"(v.y), "=f"(v.z), "=f"(v.w) : "r"(a) : "memory");
  return v;
}
__device__ __forceinline__ void norm_pack(uint32_t* p, const float* d, const float4& i) {
  p[0] = pack2(d[0] * i.x, d[1] * i.y); p[1] = pack2(d[4] * i.z, d[5] * i.w);
  p[2] = pack2(d[2] * i.x, d[3] * i.y); p[3] = pack2(d[6] * i.z, d[7] * i.w);
  asm volatile("" : "+r"(p[0]), "+r"(p[1]), "+r"(p[2]), "+r"(p[3])::"memory");
}
template <int W>
__device__ __forceinline__ void pack_first(uint32_t (&pk)[60], const float (&om)[80], const float (&oh)[40], uint32_t laddr) {
  float4 n0 = lds_f4(laddr + W * 80), n1 = lds_f4(laddr + W * 80 + 16);
#pragma unroll
  for (int J = 0; J < 5; J++) {
    const float4 i = n0;
    n0 = n1;
    if (J + 2 < 5) n1 = lds_f4(laddr + W * 80 + (J + 2) * 16);
    norm_pack(&pk[20 + 4 * J], &om[8 * (5 * W + J)], i);
    norm_pack(&pk[4 * J], &oh[8 * J], i);
  }
}
template <int W, int J0, int J1>
__device__ __forceinline__ void pack_second(uint32_t (&pk)[60], const float (&om)[80], uint32_t laddr) {
  float4 n[J1 - J0];
#pragma unroll
  for (int J = J0; J < J1; J++) n[J - J0] = lds_f4(laddr + (1 - W) * 80 + J * 16);
#pragma unroll
  for (int J = J0; J < J1; J++) norm_pack(&pk[40 + 4 * J], &om[8 * (5 * (1 - W) + J)], n[J - J0]);
}
template <int W, int G0, int G1>
__device__ __forceinline__ void store_groups(char* op, const uint32_t (&pk)[60], uint32_t on) {
#pragma unroll
  for (int G = G0; G < G1; G++) {
    const int off = (G < 5 ? 1 : 2 * W) * B_SLOT + (5 * (G < 10 ? W : 1 - W) + G % 5) * 2048;
    asm volatile("{\n.reg .pred p;\nsetp.ne.u32 p, %5, 0;\n@p st.global.v2.b32 [%0], {%1, %2};\n@p st.global.v2.b32 [%0+128], {%3, %4};\n}\n"
                 ::"l"(op + off), "r"(pk[4 * G]), "r"(pk[4 * G + 1]), "r"(pk[4 * G + 2]), "r"(pk[4 * G + 3]), "r"(on) : "memory");
  }
}
__device__ __forceinline__ void publish_generic(uint32_t bar, int lane) {
  __syncwarp();
  mbar_arrive_if0(bar, lane);
}
__device__ __forceinline__ void publish(uint32_t bar, int lane) {
  proxy_fence();
  __syncwarp();
  mbar_arrive_if0(bar, lane);
}

#define A_ADDR(s) (SB + OFF_A + (s) * A_SLOT)
#define B_ADDR(s) (SB + OFF_B + (s) * B_SLOT)
#define WAIT_CHUNK(c, ro, sA)                \
  uint32_t sA;                               \
  {                                          \
    uint32_t pA_;                            \
    ring_pos(ring, (ro) + (c), sA, pA_);     \
    mbar_wait(bud, BAR_FULLA + sA * 8, pA_); \
  }
#define RELEASE_CHUNK(c, sA)                                  \
  mbar_arrive_if0(BAR_EMPTYA + (sA) * 8, tid);                \
  if ((c) < NSLOT) mbar_arrive_if0(BAR_EMPTYB + xs(c) * 8, tid);

template <int W>
__device__ __forceinline__ void attn_consumer(const Sched& sc) {
  int bud = WAIT_BUDGET;
  const int tid = threadIdx.x & 127, lane = tid & 31, warp = tid >> 5;
  const uint32_t st_off = ((lane & 7) + 8 * (lane >> 4)) * 128 + (((2 * warp + ((lane >> 3) & 1)) ^ (lane & 7)) << 4);
  const uint32_t laddr = SB + OFF_L + (lane & 3) * 160;
  const uint32_t o_off = ((lane & 3) >> 1) * 1024 + warp * 256 + (lane >> 2) * 16 + (lane & 1) * 8;
  float om[80], oh[40], sacc[80];
  uint32_t pk[60];
#pragma unroll
  for (int i = 0; i < 40; i++) pk[i] = 0;
  zero_regs(om);
  char* op = (char*)g_o;
  Ring ring{0u, 0u};
  uint32_t par = 0;
  const float qscale = 0.07216878364870322f * 1.4426950408889634f;
  constexpr uint32_t pown = B_ADDR(3 + W), poth = B_ADDR(4 - W);
  TL(0); TLG(62);
  {
    WAIT_CHUNK(0, 0, s0)
    wg_fence();
    mma_both<W, false>(sacc, oh, A_ADDR(s0), B_ADDR(xs(0)));
    wg_commit();
    WAIT_CHUNK(1, 0, s1)
    wg_fence();
    mma_both<W, true>(sacc, oh, A_ADDR(s1), B_ADDR(xs(1)));
    wg_commit();
    wg_wait<1>();
    RELEASE_CHUNK(0, s0)
  }
#pragma unroll 1
  for (int it = 0;; it++) {
#pragma unroll
    for (int c = 2; c < 8; c++) {
      WAIT_CHUNK(c, 0, sA)
      TL(40 + c);
      wg_fence();
      mma_both<W, true>(sacc, oh, A_ADDR(sA), B_ADDR(xs(c)));
      wg_commit();
      wg_wait<1>();
      uint32_t sP, pP;
      ring_pos(ring, c - 1, sP, pP);
      RELEASE_CHUNK(c - 1, sP)
      if (c == 2) { store_groups<W, 0, 4>(op, pk, it); pack_second<W, 0, 2>(pk, om, laddr); }
      if (c == 3) { store_groups<W, 4, 8>(op, pk, it); pack_second<W, 2, 4>(pk, om, laddr); }
      if (c == 4) { store_groups<W, 8, 12>(op, pk, it); pack_second<W, 4, 5>(pk, om, laddr); }
      if (c == 5) {
        store_groups<W, 12, 15>(op, pk, it);
        __syncwarp();
        mbar_arrive_if0(BAR_OFULL, lane | (it == 0));
      }
    }
    uint32_t sK0, pK0, s7, p7;
    ring_pos(ring, idxK(W), sK0, pK0);
    ring_pos(ring, 7, s7, p7);
    if (W == 1) {
      wg_wait<0>();
      RELEASE_CHUNK(7, s7)
      mbar_arrive_if0(BAR_XDONE, tid);
    }
    WAIT_CHUNK(8, 0, s8)
    WAIT_CHUNK(9, 0, s9)
    TL(48);
    if (W == 1) bar_sync(5, 256);
    wg_fence();
    mma_mid<W, true>(oh, A_ADDR(s8), B_ADDR(xs(8)));
    mma_mid<W, true>(oh, A_ADDR(s9), B_ADDR(xs(9)));
    wg_commit();
    mma_main<W, true>(sacc, A_ADDR(s8), B_ADDR(xs(8)));
    mma_main<W, true>(sacc, A_ADDR(s9), B_ADDR(xs(9)));
    wg_commit();
    if (W == 0) bar_arrive(5, 256);
    TL(49);
    wg_wait<1>();
    reg_fence(oh);
    if (W == 0) {
      RELEASE_CHUNK(7, s7)
      mbar_arrive_if0(BAR_XDONE, tid);
    }
    mbar_wait(bud, BAR_XDONE, par);
    store_scaled(B_ADDR(1) + W * 10240 + st_off, oh, qscale);
    publish(BAR_QH, lane);
    if (W == 0) mbar_wait(bud, BAR_FULLA + sK0 * 8, pK0);
    wg_wait<0>();
    reg_fence(sacc);
    TL(1);
    RELEASE_CHUNK(8, s8)
    RELEASE_CHUNK(9, s9)
    store_scaled(B_ADDR(2 * W) + st_off, sacc, qscale);
    publish(BAR_QM + W * 8, lane);
    TL(2);
    uint32_t sK = sK0, sV1 = 0;
    if (W == 0) {
      zero_regs(om); zero_regs(oh);
      reg_fence(om); reg_fence(oh);
      mbar_wait(bud, BAR_QM, par);
      wg_fence();
      s_mma<0, false>(sacc, A_ADDR(sK));
      mbar_wait(bud, BAR_QH, par);
      TL(3);
      wg_fence();
      s_mma<1, true>(sacc, A_ADDR(sK));
      mbar_wait(bud, BAR_QM + 8, par);
      TL(5);
      wg_fence();
      s_mma<2, true>(sacc, A_ADDR(sK));
      wg_commit();
      wg_commit();
      bar_arrive(2, 256);
    } else {
      uint32_t pV1;
      ring_pos(ring, idxV(0), sV1, pV1);
      mbar_wait(bud, BAR_FULLA + sK * 8, pK0);
      bar_sync(2, 256);
      wg_fence();
      s_mma<0, false>(sacc, A_ADDR(sK));
      s_mma<1, true>(sacc, A_ADDR(sK));
      s_mma<2, true>(sacc, A_ADDR(sK));
      wg_commit();
      TL(6);
      mbar_wait(bud, BAR_FULLA + sV1 * 8, pV1);
      mbar_wait(bud, BAR_PFULL, 0);
      TL(7);
      wg_fence();
      mma_both<W, false>(om, oh, A_ADDR(sV1), poth);
      wg_commit();
      bar_arrive(1, 256);
    }
    Ring rv;
    ring_pos(ring, idxV(W), rv.s0, rv.ph0);
#pragma unroll 1
    for (int jj = 0;; jj++) {
      wg_wait<1>();
      reg_fence(sacc);
      TL(8 + jj * 7);
      mbar_arrive2_if0(BAR_EMPTYA + sK * 8, tid);
      mbar_arrive_if0(BAR_EMPTYB + tid * 8, (tid >= 3) | (jj != 3));
#pragma unroll
      for (int J = 0; J < 10; J++) {
        stsm_t(pown + st_off + J * 2048, pack2(ex2(sacc[8 * J]), ex2(sacc[8 * J + 1])), pack2(ex2(sacc[8 * J + 2]), ex2(sacc[8 * J + 3])),
               pack2(ex2(sacc[8 * J + 4]), ex2(sacc[8 * J + 5])), pack2(ex2(sacc[8 * J + 6]), ex2(sacc[8 * J + 7])));
        if (W == 1 && (J == 2 || J == 5)) publish_generic(BAR_PMID + (J / 3) * 8, lane | (jj != 3));
        if (J == 5) {
          wg_wait<0>();
          mbar_arrive_if0(BAR_EMPTYA + sV1 * 8, tid | (W == 0 && jj == 0));
        }
      }
      publish(BAR_PFULL + W * 8, lane);
      TL(10 + jj * 7);
      if (jj == 3) break;
      uint32_t pK, pV1;
      ring_pos(rv, 1, sK, pK);
      ring_pos(rv, 2, sV1, pV1);
      mbar_wait(bud, BAR_FULLA + rv.s0 * 8, rv.ph0);
      bar_sync(1 + W, 256);
      wg_fence();
      mma_both<W, true>(om, oh, A_ADDR(rv.s0), pown);
      wg_commit();
      mbar_wait(bud, BAR_FULLA + sK * 8, pK);
      TL(11 + jj * 7);
      wg_fence();
      s_mma<0, false>(sacc, A_ADDR(sK));
      s_mma<1, true>(sacc, A_ADDR(sK));
      wg_commit();
      wg_wait<1>();
      mbar_arrive_if0(BAR_EMPTYA + rv.s0 * 8, tid);
      wg_fence();
      s_mma<2, true>(sacc, A_ADDR(sK));
      wg_commit();
      TL(13 + jj * 7);
      mbar_wait(bud, BAR_FULLA + sV1 * 8, pV1);
      mbar_wait(bud, BAR_PFREE + W * 8, jj & 1);
      mbar_wait(bud, BAR_PFULL + (1 - W) * 8, (jj + W) & 1);
      TL(14 + jj * 7);
      wg_fence();
      mma_both<W, true>(om, oh, A_ADDR(sV1), poth);
      wg_commit();
      bar_arrive(2 - W, 256);
      ring_advance(rv, 4);
    }
    uint32_t sV7, pV7;
    ring_pos(ring, idxV(7), sV7, pV7);
    if (W == 0) {
      uint32_t sV6, pV6;
      ring_pos(ring, idxV(6), sV6, pV6);
      mbar_wait(bud, BAR_FULLA + sV6 * 8, pV6);
      bar_sync(1, 256);
      wg_fence();
      mma_both<0, true>(om, oh, A_ADDR(sV6), pown);
      wg_commit();
      mbar_wait(bud, BAR_FULLA + sV7 * 8, pV7);
      wg_wait<0>();
      mbar_arrive_if0(BAR_EMPTYA + sV6 * 8, tid);
      mbar_wait(bud, BAR_PFULL + 8, 1);
      wg_fence();
      mma_both<0, true>(om, oh, A_ADDR(sV7), poth);
      wg_commit();
      bar_arrive(6, 256);
    } else {
      mbar_wait(bud, BAR_FULLA + sV7 * 8, pV7);
      bar_sync(6, 256);
    }
    TL(32);
    op = (char*)g_o + (size_t)(sched_item(sc, it) % ORING) * O_ITEM_BYTES + o_off;
    if (it + 1 == sc.n) {
      if (W == 1) {
        wg_fence();
        mma_both<1, true>(om, oh, A_ADDR(sV7), pown);
        wg_commit();
      }
      wg_wait<0>();
      reg_fence(om); reg_fence(oh);
      TL(33);
      mbar_wait(bud, BAR_LFULL, par);
      TL(34);
      pack_first<W>(pk, om, oh, laddr);
      store_groups<W, 0, 10>(op, pk, 1);
      pack_second<W, 0, 5>(pk, om, laddr);
      store_groups<W, 10, 15>(op, pk, 1);
      publish_generic(BAR_OFULL, lane);
      TL(35); TLG(63);
      TL_FLUSH();
      break;
    }
    {
      if (W == 1) {
        wg_fence();
        mma_both<1, true>(om, oh, A_ADDR(sV7), pown);
        wg_commit();
      }
      WAIT_CHUNK(0, 26, s0)
      WAIT_CHUNK(1, 26, s1)
      if (W == 0) {
        wg_wait<0>();
        reg_fence(om); reg_fence(oh);
        TL(33);
        wg_fence();
        mma_main<W, false>(sacc, A_ADDR(s0), B_ADDR(xs(0)));
        wg_commit();
      } else {
        wg_fence();
        mma_main<W, false>(sacc, A_ADDR(s0), B_ADDR(xs(0)));
        mma_main<W, true>(sacc, A_ADDR(s1), B_ADDR(xs(1)));
        wg_commit();
        wg_wait<1>();
        reg_fence(om); reg_fence(oh);
        TL(33);
      }
      mbar_arrive_if0(BAR_EMPTYA + sV7 * 8, tid);
      mbar_wait(bud, BAR_LFULL, par);
      mbar_arrive_if0(BAR_EMPTYB + 24 + tid * 8, tid >= 2);
      TL(34);
      pack_first<W>(pk, om, oh, laddr);
      TL(36);
      wg_fence();
      mma_mid<W, false>(oh, A_ADDR(s0), B_ADDR(xs(0)));
      wg_commit();
      mma_mid<W, true>(oh, A_ADDR(s1), B_ADDR(xs(1)));
      if (W == 0) mma_main<W, true>(sacc, A_ADDR(s1), B_ADDR(xs(1)));
      wg_commit();
      TL(37);
      wg_wait<1>();
      RELEASE_CHUNK(0, s0)
      TL(35); TLG(63);
    }
    TL_FLUSH();
    TL(0); TLG(62);
    ring_advance(ring, 26);
    par ^= 1;
  }
}

__device__ __forceinline__ uint4 lds128(uint32_t a) {
  uint4 v;
  asm volatile("ld.shared.v4.b32 {%0,%1,%2,%3}, [%4];" : "=r"(v.x), "=r"(v.y), "=r"(v.z), "=r"(v.w) : "r"(a) : "memory");
  return v;
}
__device__ __forceinline__ void acc2(float& s, float& t, uint32_t w) {
  s += __uint_as_float(w << 16);
  t += __uint_as_float(w & 0xffff0000u);
}
__device__ __forceinline__ uint32_t badd2(uint32_t a, uint32_t b) { uint32_t r; asm("add.rn.bf16x2 %0, %1, %2;" : "=r"(r) : "r"(a), "r"(b)); return r; }
__device__ __forceinline__ void sum_unit(float& acc, uint32_t pb) {
  const uint4 v0 = lds128(pb), v1 = lds128(pb ^ 32), v2 = lds128(pb ^ 64), v3 = lds128(pb ^ 96);
  const uint32_t w0 = badd2(v0.x, v0.y), w1 = badd2(v0.z, v0.w);
  float s0 = acc + __uint_as_float(w0 << 16), t0 = __uint_as_float(w0 & 0xffff0000u);
  float s1 = __uint_as_float(w1 << 16), t1 = __uint_as_float(w1 & 0xffff0000u);
  acc2(s0, t0, badd2(v1.x, v1.y)); acc2(s1, t1, badd2(v1.z, v1.w));
  acc2(s0, t0, badd2(v2.x, v2.y)); acc2(s1, t1, badd2(v2.z, v2.w));
  acc2(s0, t0, badd2(v3.x, v3.y)); acc2(s1, t1, badd2(v3.z, v3.w));
  acc = (s0 + t0) + (s1 + t1);
}
__device__ __forceinline__ void attn_helper(const Params& p, int hw, const Sched& sc, int epoch) {
  int bud = WAIT_BUDGET;
  const int lane = threadIdx.x & 31, r = lane >> 1;
  const uint32_t a0 = B_ADDR(3) + (16 * hw + r) * 128 + (lane & 1) * 16 + ((r & 3) << 5);
  uint32_t par = 0;
#pragma unroll 1
  for (int it = 0; it < sc.n; it++) {
    const int item = sched_item(sc, it);
    float acc[4] = {0.f, 0.f, 0.f, 0.f};
#pragma unroll 1
    for (int j = 0; j < 8; j++) {
      const uint32_t pb = a0 + (j & 1) * B_SLOT, bfull = BAR_PFULL + (j & 1) * 8, pfull = (j >> 1) & 1;
      mbar_wait(bud, j == 7 ? BAR_PMID : bfull, j == 7 ? par : pfull);
      sum_unit(acc[0], pb);
      if (j == 7) mbar_wait(bud, BAR_PMID + 8, par);
      sum_unit(acc[1], pb + 6144);
      if (j == 7) mbar_wait(bud, bfull, pfull);
      sum_unit(acc[2], pb + 2 * 6144);
      if (hw == 0) sum_unit(acc[3], pb + 3 * 6144);
      __syncwarp();
      mbar_arrive_if0(BAR_PFREE + (j & 1) * 8, lane);
      if (j == 5 && hw == 2 && item >= ORING) flag_wait(bud, &g_done[(item - ORING) >> 4], (epoch + 1) * N_OCTA);
    }
    bool bad = false;
    const uint32_t la = SB + OFF_L + (((r & 7) >> 1) * 40 + 2 * (r >> 3) + (r & 1) + 4 * hw) * 4;
#pragma unroll
    for (int u = 0; u < 4; u++) {
      const float l = acc[u] + __shfl_xor_sync(0xffffffffu, acc[u], 1);
      if (u < 3 || hw == 0) {
        bad |= !(l >= 8.8817841970012523e-16f && l <= 1.125899906842624e15f);
        float inv;
        asm("rcp.approx.ftz.f32 %0, %1;" : "=f"(inv) : "f"(l));
        asm volatile("st.shared.f32 [%0], %1;" ::"r"(la + u * 48), "f"(inv) : "memory");
      }
    }
    publish_generic(BAR_LFULL, lane);
    if (lane == 0) TLP(40 + hw * 4);
    const bool anybad = __any_sync(0xffffffffu, bad);
    if (lane == 0) g_bad[item * 4 + hw] = anybad;
    if (hw == 1) {
      mbar_wait(bud, BAR_OFULL, par);
      if (lane == 0) {
        TLP(41 + hw * 4);
        asm volatile("red.release.gpu.global.add.s32 [%0], 1;" ::"l"(&g_ready[item]) : "memory");
        TLP(42 + hw * 4);
      }
      __syncwarp();
    }
    par ^= 1;
  }
}

__device__ __forceinline__ void attn_producer(const Params& p, const Sched& sc) {
  int bud = WAIT_BUDGET;
  uint32_t sa = 0, pa = 1;
  uint64_t pol;
  asm volatile("createpolicy.fractional.L2::evict_first.b64 %0, 1.0;" : "=l"(pol));
  uint64_t poln;
  asm volatile("createpolicy.fractional.L2::evict_normal.b64 %0, 1.0;" : "=l"(poln));
  if (sc.delay) {
    const long long t0 = clock64();
    while (clock64() - t0 < G2_DELAY) __nanosleep(200);
  }
#pragma unroll 1
  for (int it = 0; it < sc.n; it++) {
    const int item = sched_item(sc, it);
    const int blk = item >> 9, h = (item >> 4) & 31, b = item & 15;
    const int row0 = (b * NH + h) * SK;
#pragma unroll
    for (int c = 0; c < 10; c++) {
      mbar_wait(bud, BAR_EMPTYA + sa * 8, pa);
      TLP(c);
      mbar_expect(BAR_FULLA + sa * 8, A_SLOT + B_SLOT);
      tma3d(A_ADDR(sa), &p.wq[blk], BAR_FULLA + sa * 8, 0, c * 64, h * 3);
      mbar_wait(bud, BAR_EMPTYB + xs(c) * 8, c < NSLOT);
      TLP(10 + c);
      tma2d(B_ADDR(xs(c)), &p.x[blk], BAR_FULLA + sa * 8, c * 64, b * SQ);
      if (++sa == NSLOT) { sa = 0; pa ^= 1; }
    }
#pragma unroll
    for (int i = 0; i < 16; i++) {
      const bool isK = (i == 0) || ((i & 1) && i < 15);
      const int j = i == 0 ? 0 : (i == 15 ? 7 : (isK ? (i + 1) >> 1 : (i - 2) >> 1));
      mbar_wait(bud, BAR_EMPTYA + sa * 8, pa);
      TLP(20 + i);
      mbar_expect(BAR_FULLA + sa * 8, A_SLOT);
      tma3d_hint(A_ADDR(sa), isK ? &p.k[blk] : &p.v[blk], BAR_FULLA + sa * 8, 0, row0 + j * 64, 0, pol);
      if (++sa == NSLOT) { sa = 0; pa ^= 1; }
    }
  }
}

template <int W>
__device__ __forceinline__ void oproj_consumer() {
  int bud = WAIT_BUDGET;
  const int tid = threadIdx.x & 127, lane = tid & 31, warp = tid >> 5;
  const int qrow = 8 * ((lane >> 1) & 1) + 4 * (lane >> 4) + 2 * ((lane >> 2) & 1) + (lane & 1);
  const uint32_t st_off = qrow * 128 + (((2 * warp + ((lane >> 3) & 1)) ^ (qrow & 7)) << 4);
  float a0[64], a1[64], ah[32];
  zero_regs(a0); zero_regs(a1); zero_regs(ah);
#pragma unroll 1
  for (int blk = 0; blk < 2; blk++) {
    int c3 = 0, step = blk * NH;
#pragma unroll 1
    for (int c = 0; c < 96; c++) {
      const uint32_t st = c & 3;
      mbar_wait(bud, BAR_GFULL + st * 8, (c >> 2) & 1);
      wg_fence();
      const uint32_t la = lo_sw(SB + st * O_STAGE), lb = lo_o(SB + st * O_STAGE + O_AB);
#define O_STEP(ks, sc)                                                   \
  mma64r<1, 1, 2 * 8192 + ks * 2048, W * 8192 + ks * 256>(ah, la, lb, sc);    \
  mma128r<1, 1, (W * 3) * 8192 + ks * 2048, ks * 256>(a0, la, lb, sc);        \
  mma128r<1, 1, (W * 3 + 1) * 8192 + ks * 2048, ks * 256>(a1, la, lb, sc);
      O_STEP(0, c != 0) O_STEP(1, 1) O_STEP(2, 1) O_STEP(3, 1)
#undef O_STEP
      wg_commit();
      if (++c3 == 3) {
        c3 = 0;
        if (W == 0)
          asm volatile("{\n.reg .pred p;\nsetp.eq.u32 p, %1, 0;\n@p red.relaxed.gpu.global.add.s32 [%0], 1;\n}\n" ::"l"(&g_done[step]), "r"(tid) : "memory");
        TL(step);
        step++;
      }
      wg_wait<1>();
      mbar_arrive_if0(BAR_GEMPTY + ((c - 1) & 3) * 8, tid | (c == 0) | (c == 95));
    }
    wg_wait<0>();
    reg_fence(a0); reg_fence(a1); reg_fence(ah);
    bar_sync(3, 256);
    const uint32_t sg = SB + 2 * O_STAGE + st_off;
    store_scaled(sg + 2 * 16384 + W * 8192, ah, 1.0f);
    store_scaled(sg + (W * 3) * 16384, a0, 1.0f);
    store_scaled(sg + (W * 3 + 1) * 16384, a1, 1.0f);
    publish(BAR_GOUT, lane);
  }
  TL_FLUSH();
}

__device__ __forceinline__ void oproj_producer(const Params& p, int cta, int epoch) {
  int bud = WAIT_BUDGET;
  const int half = cta & 1, r0 = (cta >> 1) * 128;
  const int b0 = r0 / SQ, off0 = r0 - b0 * SQ, n0 = min(128, SQ - off0), n1 = 128 - n0;
  const int target = epoch + 1;
#pragma unroll 1
  for (int step = 0; step < 2 * NH; step++) {
    const int blk = step >> 5, item0 = step * 16 + b0;
    const char* o0 = (const char*)g_o + (size_t)(item0 % ORING) * O_ITEM_BYTES + off0 * 128;
    const char* o1 = (const char*)g_o + (size_t)((item0 + 1) % ORING) * O_ITEM_BYTES;
#pragma unroll 1
    for (int kb = 0; kb < 3; kb++) {
      const int c = step * 3 + kb;
      const uint32_t st = c & 3, dst = SB + st * O_STAGE, bar = BAR_GFULL + st * 8;
      mbar_wait(bud, BAR_GEMPTY + st * 8, ((c >> 2) & 1) ^ 1);
      mbar_expect(bar, O_STAGE);
      tma3d(dst, &p.wo[blk], bar, 0, ((step & 31) * 3 + kb) * 64, half * 5);
      if (kb == 0) {
        flag_wait(bud, &g_ready[item0], target);
        if (n1) flag_wait(bud, &g_ready[item0 + 1], target);
        asm volatile("fence.proxy.async.global;" ::: "memory");
      }
      bulk_load(dst + O_AB, o0 + kb * B_SLOT, n0 * 128, bar);
      if (n1) bulk_load(dst + O_AB + n0 * 128, o1 + kb * B_SLOT, n1 * 128, bar);
    }
  }
}

__device__ __forceinline__ void oproj_storer(const Params& p, int cta) {
  int bud = WAIT_BUDGET;
  const int half = cta & 1, r0 = (cta >> 1) * 128;
#pragma unroll 1
  for (int blk = 0; blk < 2; blk++) {
    mbar_wait(bud, BAR_GOUT, blk);
    for (int k = 0; k < 5; k++) tma_store2d(&p.out, SB + 2 * O_STAGE + k * 16384, blk * DM + half * 320 + k * 64, r0);
    asm volatile("cp.async.bulk.commit_group;" ::: "memory");
    asm volatile("cp.async.bulk.wait_group.read 0;" ::: "memory");
    mbar_arrive2_if0(BAR_GEMPTY + 16, 0);
    mbar_arrive2_if0(BAR_GEMPTY + 24, 0);
  }
  asm volatile("cp.async.bulk.wait_group 0;" ::: "memory");
}

__global__ void __launch_bounds__(384, 1) fused_kernel(const __grid_constant__ Params p) {
  extern __shared__ __align__(1024) char smem_raw[];
  if ((smem_u32(smem_raw) & 0xFFFFFFu) != SB) return;
  const int cta = blockIdx.x;
  const int epoch = g_epoch[cta];
  if (threadIdx.x == 0) {
    for (int i = 0; i < NSLOT; i++) {
      mbar_init(BAR_FULLA + i * 8, 1); mbar_init(BAR_EMPTYA + i * 8, 2);
      mbar_init(BAR_EMPTYB + i * 8, 2);
    }
    mbar_init(BAR_XDONE, 2); mbar_init(BAR_QH, 8); mbar_init(BAR_QM, 4); mbar_init(BAR_QM + 8, 4);
    mbar_init(BAR_PFULL, 4); mbar_init(BAR_PFULL + 8, 4);
    mbar_init(BAR_PFREE, 3); mbar_init(BAR_PFREE + 8, 3);
    mbar_init(BAR_LFULL, 3); mbar_init(BAR_PMID, 4); mbar_init(BAR_PMID + 8, 4);
    mbar_init(BAR_OFULL, 8);
    for (int i = 0; i < O_NST; i++) { mbar_init(BAR_GFULL + i * 8, 1); mbar_init(BAR_GEMPTY + i * 8, 2); }
    mbar_init(BAR_GOUT, 8);
    asm volatile("fence.mbarrier_init.release.cluster;" ::: "memory");
    proxy_fence();
  }
  __syncthreads();
  if (threadIdx.x == 0) g_epoch[cta] = epoch + 1;
  const int warp = __shfl_sync(0xffffffffu, threadIdx.x >> 5, 0);
  const Sched sc = get_sched(cta);
  if (warp >= 8) {
    asm volatile("setmaxnreg.dec.sync.aligned.u32 40;");
    if (warp == 8) {
      if (elect_one()) attn_producer(p, sc);
      __syncwarp();
    } else {
      attn_helper(p, warp - 9, sc, epoch);
    }
    if (cta < N_OCTA) {
      bar_sync(4, 128);
      if (warp == 8) {
        if (elect_one()) oproj_producer(p, cta, epoch);
      } else if (warp == 9) {
        if (elect_one()) oproj_storer(p, cta);
      }
    }
  } else {
    asm volatile("setmaxnreg.inc.sync.aligned.u32 232;");
    if (warp < 4) {
      attn_consumer<0>(sc);
      if (cta < N_OCTA) oproj_consumer<0>();
    } else {
      attn_consumer<1>(sc);
      if (cta < N_OCTA) oproj_consumer<1>();
    }
  }
}

typedef CUresult (*EncodeFn)(CUtensorMap*, CUtensorMapDataType, cuuint32_t, void*, const cuuint64_t*, const cuuint64_t*, const cuuint32_t*,
                             const cuuint32_t*, CUtensorMapInterleave, CUtensorMapSwizzle, CUtensorMapL2promotion, CUtensorMapFloatOOBfill);

void make3d(EncodeFn enc, CUtensorMap* m, const void* ptr, uint64_t rows, uint64_t cols, uint32_t box_rows, uint32_t box_blocks,
            CUtensorMapL2promotion promo = CU_TENSOR_MAP_L2_PROMOTION_L2_128B) {
  cuuint64_t gd[3] = {64, rows, cols / 64};
  cuuint64_t gs[2] = {cols * 2, 128};
  cuuint32_t bd[3] = {64, box_rows, box_blocks}, es[3] = {1, 1, 1};
  enc(m, CU_TENSOR_MAP_DATA_TYPE_BFLOAT16, 3, (void*)ptr, gd, gs, bd, es, CU_TENSOR_MAP_INTERLEAVE_NONE, CU_TENSOR_MAP_SWIZZLE_128B,
      promo, CU_TENSOR_MAP_FLOAT_OOB_FILL_NONE);
}
void make2d(EncodeFn enc, CUtensorMap* m, const void* ptr, uint64_t rows, uint64_t cols, uint32_t box_rows) {
  cuuint64_t gd[2] = {cols, rows};
  cuuint64_t gs[1] = {cols * 2};
  cuuint32_t bd[2] = {64, box_rows}, es[2] = {1, 1};
  enc(m, CU_TENSOR_MAP_DATA_TYPE_BFLOAT16, 2, (void*)ptr, gd, gs, bd, es, CU_TENSOR_MAP_INTERLEAVE_NONE, CU_TENSOR_MAP_SWIZZLE_128B,
      CU_TENSOR_MAP_L2_PROMOTION_L2_128B, CU_TENSOR_MAP_FLOAT_OOB_FILL_NONE);
}

}

extern "C" void kernel_launch(void* const* d_in, const int* in_sizes, int n_in, void* d_out, int out_size) {
  static EncodeFn enc = nullptr;
  if (!enc) {
    cudaDriverEntryPointQueryResult qr;
    cudaGetDriverEntryPoint("cuTensorMapEncodeTiled", (void**)&enc, cudaEnableDefault, &qr);
    cudaFuncSetAttribute(fused_kernel, cudaFuncAttributeMaxDynamicSharedMemorySize, SMEM_BYTES);
  }
  Params p;
  for (int s = 0; s < 2; s++) {
    make2d(enc, &p.x[s], d_in[5 * s + 0], NB * SQ, DM, SQ);
    make3d(enc, &p.k[s], d_in[5 * s + 1], (uint64_t)NB * NH * SK, DH, 64, 3, KV_PROMO);
    make3d(enc, &p.v[s], d_in[5 * s + 2], (uint64_t)NB * NH * SK, DH, 64, 3, KV_PROMO);
    make3d(enc, &p.wq[s], d_in[5 * s + 3], DM, NH * DH, 64, 3);
    make3d(enc, &p.wo[s], d_in[5 * s + 4], NH * DH, DM, 64, 5);
    p.kp[s] = (const __nv_bfloat16*)d_in[5 * s + 1];
    p.vp[s] = (const __nv_bfloat16*)d_in[5 * s + 2];
  }
  make2d(enc, &p.out, d_out, NB * SQ, 2 * DM, 128);
  fused_kernel<<<NCTA, 384, SMEM_BYTES>>>(p);
}
```

```cpp
#include <cuda_runtime.h>
#include <cuda_bf16.h>
#include <cuda.h>
#include <stdint.h>

#define DEBUG_TIMEOUT 1

namespace {

constexpr int SQ = 160, DM = 640, NH = 32, SK = 512, DH = 192, NB = 16;
constexpr int NITEMS = 2 * NB * NH;
constexpr int NCTA = 132, N_OCTA = 40, N_G2 = 28, N_G1 = 64, N_ATT = N_G1 + N_G2;
#define ORING 112
#define SPREAD 1
#define STGON it
#define KV_PROMO CU_TENSOR_MAP_L2_PROMOTION_L2_128B
#define G2_DELAY 8000
constexpr int A_SLOT = 24576, B_SLOT = 20480, NSLOT = 5;
constexpr int OFF_A = 0;
constexpr int OFF_B = NSLOT * A_SLOT;
constexpr int O_STAGE = 57344, O_AB = 40960, O_NST = 4;
constexpr int OFF_L = O_NST * O_STAGE;
constexpr int OFF_BAR = OFF_L + 160 * 4;
constexpr int SMEM_BYTES = OFF_BAR + 384 + 512;
static_assert(OFF_B + NSLOT * B_SLOT <= OFF_L, "smem layout");
constexpr uint32_t SB = 1024;
constexpr uint32_t BARS = SB + OFF_BAR;
constexpr uint32_t BAR_FULLA = BARS, BAR_EMPTYA = BARS + 40, BAR_PMID = BARS + 80, BAR_EMPTYB = BARS + 120, BAR_XDONE = BARS + 160,
                   BAR_QH = BARS + 168, BAR_QM = BARS + 96, BAR_PFULL = BARS + 184, BAR_PFREE = BARS + 200, BAR_LFULL = BARS + 216,
                   BAR_OFULL = BARS + 224, BAR_GFULL = BARS + 248, BAR_GEMPTY = BARS + 280, BAR_GOUT = BARS + 312;
constexpr int O_ITEM_BYTES = SQ * DH * 2;

struct alignas(64) Params {
  CUtensorMap x[2], wq[2], k[2], v[2], wo[2], out;
  const __nv_bfloat16* kp[2];
  const __nv_bfloat16* vp[2];
};

__device__ uint4 g_o[(size_t)ORING * O_ITEM_BYTES / 16];
__device__ int g_ready[NITEMS];
__device__ int g_done[2 * NH];
__device__ int g_epoch[NCTA];
__device__ int g_bad[NITEMS * 4];

#define TLP(id)
#define TLG(id)
#define TL(id)
#define TL_FLUSH()
__device__ __forceinline__ uint32_t smem_u32(const void* p) { return (uint32_t)__cvta_generic_to_shared(p); }
__device__ __forceinline__ void wg_fence() { asm volatile("wgmma.fence.sync.aligned;" ::: "memory"); }
__device__ __forceinline__ void wg_commit() { asm volatile("wgmma.commit_group.sync.aligned;" ::: "memory"); }
template <int N> __device__ __forceinline__ void wg_wait() { asm volatile("wgmma.wait_group.sync.aligned %0;" ::"n"(N) : "memory"); }
template <int N> __device__ __forceinline__ void reg_fence(float (&d)[N]) {
#pragma unroll
  for (int i = 0; i < N; i++) asm volatile("" : "+f"(d[i])::"memory");
}
template <int N> __device__ __forceinline__ void zero_regs(float (&d)[N]) {
#pragma unroll
  for (int i = 0; i < N; i++) d[i] = 0.f;
}
__device__ __forceinline__ void proxy_fence() { asm volatile("fence.proxy.async.shared::cta;" ::: "memory"); }
__device__ __forceinline__ void mbar_init(uint32_t bar, int cnt) { asm volatile("mbarrier.init.shared::cta.b64 [%0], %1;" ::"r"(bar), "r"(cnt) : "memory"); }
__device__ __forceinline__ void mbar_arrive_if0(uint32_t bar, uint32_t sel) {
  asm volatile("{\n.reg .pred p;\nsetp.eq.u32 p, %1, 0;\n@p mbarrier.arrive.shared::cta.b64 _, [%0];\n}\n" ::"r"(bar), "r"(sel) : "memory");
}
__device__ __forceinline__ void mbar_arrive2_if0(uint32_t bar, uint32_t sel) {
  asm volatile("{\n.reg .pred p;\nsetp.eq.u32 p, %1, 0;\n@p mbarrier.arrive.shared::cta.b64 _, [%0], 2;\n}\n" ::"r"(bar), "r"(sel) : "memory");
}
__device__ __forceinline__ void mbar_expect(uint32_t bar, uint32_t bytes) {
  asm volatile("mbarrier.arrive.expect_tx.shared::cta.b64 _, [%0], %1;" ::"r"(bar), "r"(bytes) : "memory");
}
__device__ __forceinline__ void mbar_wait(int& bud, uint32_t bar, uint32_t parity) {
  asm volatile(
      "{\n.reg .pred p, q;\n"
      "LW:\n"
      "mbarrier.try_wait.parity.shared::cta.b64 p, [%1], %2;\n"
      "@!p add.s32 %0, %0, -1;\n"
      "setp.gt.and.s32 q, %0, 0, !p;\n"
      "@q bra LW;\n}\n" : "+r"(bud) : "r"(bar), "r"(parity) : "memory");
}
constexpr int WAIT_BUDGET = 1 << 20;
__device__ __forceinline__ bool elect_one() {
  uint32_t p;
  asm volatile("{\n.reg .pred p;\nelect.sync _|p, 0xffffffff;\nselp.u32 %0, 1, 0, p;\n}\n" : "=r"(p));
  return p;
}
__device__ __forceinline__ void tma2d(uint32_t dst, const CUtensorMap* m, uint32_t bar, int c0, int c1) {
  asm volatile("cp.async.bulk.tensor.2d.shared::cluster.global.mbarrier::complete_tx::bytes [%0], [%1, {%3, %4}], [%2];"
               ::"r"(dst), "l"(m), "r"(bar), "r"(c0), "r"(c1) : "memory");
}
__device__ __forceinline__ void tma3d(uint32_t dst, const CUtensorMap* m, uint32_t bar, int c0, int c1, int c2) {
  asm volatile("cp.async.bulk.tensor.3d.shared::cluster.global.mbarrier::complete_tx::bytes [%0], [%1, {%3, %4, %5}], [%2];"
               ::"r"(dst), "l"(m), "r"(bar), "r"(c0), "r"(c1), "r"(c2) : "memory");
}
__device__ __forceinline__ void tma3d_hint(uint32_t dst, const CUtensorMap* m, uint32_t bar, int c0, int c1, int c2, uint64_t pol) {
  asm volatile("cp.async.bulk.tensor.3d.shared::cluster.global.mbarrier::complete_tx::bytes.L2::cache_hint [%0], [%1, {%3, %4, %5}], [%2], %6;"
               ::"r"(dst), "l"(m), "r"(bar), "r"(c0), "r"(c1), "r"(c2), "l"(pol) : "memory");
}
__device__ __forceinline__ void bulk_load(uint32_t dst, const void* src, uint32_t bytes, uint32_t bar) {
  asm volatile("cp.async.bulk.shared::cluster.global.mbarrier::complete_tx::bytes [%0], [%1], %2, [%3];"
               ::"r"(dst), "l"(src), "r"(bytes), "r"(bar) : "memory");
}
__device__ __forceinline__ void l2_prefetch(const void* src, uint32_t bytes) {
  asm volatile("cp.async.bulk.prefetch.L2.global [%0], %1;" ::"l"(src), "r"(bytes) : "memory");
}
__device__ __forceinline__ void l2_prefetch_hint(const void* src, uint32_t bytes, uint64_t pol) {
  asm volatile("cp.async.bulk.prefetch.L2.global.L2::cache_hint [%0], %1, %2;" ::"l"(src), "r"(bytes), "l"(pol) : "memory");
}
__device__ __forceinline__ void tma_store2d(const CUtensorMap* m, uint32_t src, int c0, int c1) {
  asm volatile("cp.async.bulk.tensor.2d.global.shared::cta.bulk_group [%0, {%2, %3}], [%1];" ::"l"(m), "r"(src), "r"(c0), "r"(c1) : "memory");
}
__device__ __forceinline__ void bar_sync(int id, int n) { asm volatile("bar.sync %0, %1;" ::"r"(id), "r"(n) : "memory"); }
__device__ __forceinline__ void bar_arrive(int id, int n) { asm volatile("bar.arrive %0, %1;" ::"r"(id), "r"(n) : "memory"); }
__device__ __forceinline__ float ex2(float x) { float y; asm("ex2.approx.ftz.f32 %0, %1;" : "=f"(y) : "f"(x)); return y; }
__device__ __forceinline__ uint32_t pack2(float lo, float hi) { uint32_t r; asm("cvt.rn.bf16x2.f32 %0, %1, %2;" : "=r"(r) : "f"(hi), "f"(lo)); return r; }
__device__ __forceinline__ void stsm_t(uint32_t a, uint32_t r0, uint32_t r1, uint32_t r2, uint32_t r3) {
  asm volatile("stmatrix.sync.aligned.m8n8.x4.trans.shared.b16 [%0], {%1,%2,%3,%4};" ::"r"(a), "r"(r0), "r"(r1), "r"(r2), "r"(r3) : "memory");
}
__device__ __forceinline__ void flag_wait(int& bud, const int* p, int target) {
  while (true) {
    int v;
    asm volatile("ld.acquire.gpu.global.s32 %0, [%1];" : "=r"(v) : "l"(p) : "memory");
    if (v - target >= 0 || --bud <= 0) break;
    __nanosleep(64);
  }
}
__device__ __forceinline__ uint32_t lo_sw(uint32_t addr) { return (addr >> 4) | (1u << 16); }
__device__ __forceinline__ uint32_t lo_o(uint32_t addr) { return (addr >> 4) | (128u << 16); }
__device__ __forceinline__ uint32_t opaque(uint32_t x) { uint32_t y; asm volatile("mov.u32 %0, %1;" : "=r"(y) : "r"(x)); return y; }

template <int TA, int TB, uint32_t OA, uint32_t OB>
__device__ __forceinline__ void mma160(float (&d)[80], uint32_t la, uint32_t lb) {
  asm volatile(
      "{\n.reg .pred p;\n.reg .b32 a, b;\n.reg .b64 da, db;\nsetp.eq.b32 p, 0, 0;\n"
      "add.u32 a, %80, %84;\nadd.u32 b, %81, %85;\nmov.b64 da, {a, 0x40000040};\nmov.b64 db, {b, %86};\n"
      "wgmma.mma_async.sync.aligned.m64n160k16.f32.bf16.bf16 {"
      "%0,%1,%2,%3,%4,%5,%6,%7,%8,%9,%10,%11,%12,%13,%14,%15,%16,%17,%18,%19,%20,%21,%22,%23,%24,%25,%26,%27,%28,%29,%30,%31,%32,%33,%34,%35,%36,"
      "%37,%38,%39,%40,%41,%42,%43,%44,%45,%46,%47,%48,%49,%50,%51,%52,%53,%54,%55,%56,%57,%58,%59,%60,%61,%62,%63,%64,%65,%66,%67,%68,%69,%70,%71,"
      "%72,%73,%74,%75,%76,%77,%78,%79"
      "}, da, db, p, 1, 1, %82, %83;\n}\n"
      :
      "+f"(d[0]),"+f"(d[1]),"+f"(d[2]),"+f"(d[3]),"+f"(d[4]),"+f"(d[5]),"+f"(d[6]),"+f"(d[7]),"+f"(d[8]),"+f"(d[9]),"+f"(d[10]),"+f"(d[11]),
      "+f"(d[12]),"+f"(d[13]),"+f"(d[14]),"+f"(d[15]),"+f"(d[16]),"+f"(d[17]),"+f"(d[18]),"+f"(d[19]),"+f"(d[20]),"+f"(d[21]),"+f"(d[22]),
      "+f"(d[23]),"+f"(d[24]),"+f"(d[25]),"+f"(d[26]),"+f"(d[27]),"+f"(d[28]),"+f"(d[29]),"+f"(d[30]),"+f"(d[31]),"+f"(d[32]),"+f"(d[33]),
      "+f"(d[34]),"+f"(d[35]),"+f"(d[36]),"+f"(d[37]),"+f"(d[38]),"+f"(d[39]),"+f"(d[40]),"+f"(d[41]),"+f"(d[42]),"+f"(d[43]),"+f"(d[44]),
      "+f"(d[45]),"+f"(d[46]),"+f"(d[47]),"+f"(d[48]),"+f"(d[49]),"+f"(d[50]),"+f"(d[51]),"+f"(d[52]),"+f"(d[53]),"+f"(d[54]),"+f"(d[55]),
      "+f"(d[56]),"+f"(d[57]),"+f"(d[58]),"+f"(d[59]),"+f"(d[60]),"+f"(d[61]),"+f"(d[62]),"+f"(d[63]),"+f"(d[64]),"+f"(d[65]),"+f"(d[66]),
      "+f"(d[67]),"+f"(d[68]),"+f"(d[69]),"+f"(d[70]),"+f"(d[71]),"+f"(d[72]),"+f"(d[73]),"+f"(d[74]),"+f"(d[75]),"+f"(d[76]),"+f"(d[77]),
      "+f"(d[78]),"+f"(d[79])
      : "r"(la), "r"(lb), "n"(TA), "n"(TB), "n"(OA >> 4), "n"(OB >> 4), "n"(TB ? 0xC0000010u : 0x40000040u));
}

template <int TA, int TB, uint32_t OA, uint32_t OB>
__device__ __forceinline__ void mma160z(float (&d)[80], uint32_t la, uint32_t lb) {
  asm volatile(
      "{\n.reg .pred p;\n.reg .b32 a, b;\n.reg .b64 da, db;\nsetp.ne.b32 p, 0, 0;\n"
      "add.u32 a, %80, %84;\nadd.u32 b, %81, %85;\nmov.b64 da, {a, 0x40000040};\nmov.b64 db, {b, %86};\n"
      "wgmma.mma_async.sync.aligned.m64n160k16.f32.bf16.bf16 {"
      "%0,%1,%2,%3,%4,%5,%6,%7,%8,%9,%10,%11,%12,%13,%14,%15,%16,%17,%18,%19,%20,%21,%22,%23,%24,%25,%26,%27,%28,%29,%30,%31,%32,%33,%34,%35,%36,"
      "%37,%38,%39,%40,%41,%42,%43,%44,%45,%46,%47,%48,%49,%50,%51,%52,%53,%54,%55,%56,%57,%58,%59,%60,%61,%62,%63,%64,%65,%66,%67,%68,%69,%70,%71,"
      "%72,%73,%74,%75,%76,%77,%78,%79"
      "}, da, db, p, 1, 1, %82, %83;\n}\n"
      :
      "=f"(d[0]),"=f"(d[1]),"=f"(d[2]),"=f"(d[3]),"=f"(d[4]),"=f"(d[5]),"=f"(d[6]),"=f"(d[7]),"=f"(d[8]),"=f"(d[9]),"=f"(d[10]),"=f"(d[11]),
      "=f"(d[12]),"=f"(d[13]),"=f"(d[14]),"=f"(d[15]),"=f"(d[16]),"=f"(d[17]),"=f"(d[18]),"=f"(d[19]),"=f"(d[20]),"=f"(d[21]),"=f"(d[22]),
      "=f"(d[23]),"=f"(d[24]),"=f"(d[25]),"=f"(d[26]),"=f"(d[27]),"=f"(d[28]),"=f"(d[29]),"=f"(d[30]),"=f"(d[31]),"=f"(d[32]),"=f"(d[33]),
      "=f"(d[34]),"=f"(d[35]),"=f"(d[36]),"=f"(d[37]),"=f"(d[38]),"=f"(d[39]),"=f"(d[40]),"=f"(d[41]),"=f"(d[42]),"=f"(d[43]),"=f"(d[44]),
      "=f"(d[45]),"=f"(d[46]),"=f"(d[47]),"=f"(d[48]),"=f"(d[49]),"=f"(d[50]),"=f"(d[51]),"=f"(d[52]),"=f"(d[53]),"=f"(d[54]),"=f"(d[55]),
      "=f"(d[56]),"=f"(d[57]),"=f"(d[58]),"=f"(d[59]),"=f"(d[60]),"=f"(d[61]),"=f"(d[62]),"=f"(d[63]),"=f"(d[64]),"=f"(d[65]),"=f"(d[66]),
      "=f"(d[67]),"=f"(d[68]),"=f"(d[69]),"=f"(d[70]),"=f"(d[71]),"=f"(d[72]),"=f"(d[73]),"=f"(d[74]),"=f"(d[75]),"=f"(d[76]),"=f"(d[77]),
      "=f"(d[78]),"=f"(d[79])
      : "r"(la), "r"(lb), "n"(TA), "n"(TB), "n"(OA >> 4), "n"(OB >> 4), "n"(TB ? 0xC0000010u : 0x40000040u));
}

template <int TA, int TB, uint32_t OA, uint32_t OB>
__device__ __forceinline__ void mma80(float (&d)[40], uint32_t la, uint32_t lb) {
  asm volatile(
      "{\n.reg .pred p;\n.reg .b32 a, b;\n.reg .b64 da, db;\nsetp.eq.b32 p, 0, 0;\n"
      "add.u32 a, %40, %44;\nadd.u32 b, %41, %45;\nmov.b64 da, {a, 0x40000040};\nmov.b64 db, {b, %46};\n"
      "wgmma.mma_async.sync.aligned.m64n80k16.f32.bf16.bf16 {"
      "%0,%1,%2,%3,%4,%5,%6,%7,%8,%9,%10,%11,%12,%13,%14,%15,%16,%17,%18,%19,%20,%21,%22,%23,%24,%25,%26,%27,%28,%29,%30,%31,%32,%33,%34,%35,%36,"
      "%37,%38,%39"
      "}, da, db, p, 1, 1, %42, %43;\n}\n"
      :
      "+f"(d[0]),"+f"(d[1]),"+f"(d[2]),"+f"(d[3]),"+f"(d[4]),"+f"(d[5]),"+f"(d[6]),"+f"(d[7]),"+f"(d[8]),"+f"(d[9]),"+f"(d[10]),"+f"(d[11]),
      "+f"(d[12]),"+f"(d[13]),"+f"(d[14]),"+f"(d[15]),"+f"(d[16]),"+f"(d[17]),"+f"(d[18]),"+f"(d[19]),"+f"(d[20]),"+f"(d[21]),"+f"(d[22]),
      "+f"(d[23]),"+f"(d[24]),"+f"(d[25]),"+f"(d[26]),"+f"(d[27]),"+f"(d[28]),"+f"(d[29]),"+f"(d[30]),"+f"(d[31]),"+f"(d[32]),"+f"(d[33]),
      "+f"(d[34]),"+f"(d[35]),"+f"(d[36]),"+f"(d[37]),"+f"(d[38]),"+f"(d[39])
      : "r"(la), "r"(lb), "n"(TA), "n"(TB), "n"(OA >> 4), "n"(OB >> 4), "n"(TB ? 0xC0000010u : 0x40000040u));
}

template <int TA, int TB, uint32_t OA, uint32_t OB>
__device__ __forceinline__ void mma80z(float (&d)[40], uint32_t la, uint32_t lb) {
  asm volatile(
      "{\n.reg .pred p;\n.reg .b32 a, b;\n.reg .b64 da, db;\nsetp.ne.b32 p, 0, 0;\n"
      "add.u32 a, %40, %44;\nadd.u32 b, %41, %45;\nmov.b64 da, {a, 0x40000040};\nmov.b64 db, {b, %46};\n"
      "wgmma.mma_async.sync.aligned.m64n80k16.f32.bf16.bf16 {"
      "%0,%1,%2,%3,%4,%5,%6,%7,%8,%9,%10,%11,%12,%13,%14,%15,%16,%17,%18,%19,%20,%21,%22,%23,%24,%25,%26,%27,%28,%29,%30,%31,%32,%33,%34,%35,%36,"
      "%37,%38,%39"
      "}, da, db, p, 1, 1, %42, %43;\n}\n"
      :
      "=f"(d[0]),"=f"(d[1]),"=f"(d[2]),"=f"(d[3]),"=f"(d[4]),"=f"(d[5]),"=f"(d[6]),"=f"(d[7]),"=f"(d[8]),"=f"(d[9]),"=f"(d[10]),"=f"(d[11]),
      "=f"(d[12]),"=f"(d[13]),"=f"(d[14]),"=f"(d[15]),"=f"(d[16]),"=f"(d[17]),"=f"(d[18]),"=f"(d[19]),"=f"(d[20]),"=f"(d[21]),"=f"(d[22]),
      "=f"(d[23]),"=f"(d[24]),"=f"(d[25]),"=f"(d[26]),"=f"(d[27]),"=f"(d[28]),"=f"(d[29]),"=f"(d[30]),"=f"(d[31]),"=f"(d[32]),"=f"(d[33]),
      "=f"(d[34]),"=f"(d[35]),"=f"(d[36]),"=f"(d[37]),"=f"(d[38]),"=f"(d[39])
      : "r"(la), "r"(lb), "n"(TA), "n"(TB), "n"(OA >> 4), "n"(OB >> 4), "n"(TB ? 0xC0000010u : 0x40000040u));
}

template <int TA, int TB, uint32_t OA, uint32_t OB>
__device__ __forceinline__ void mma128r(float (&d)[64], uint32_t la, uint32_t lb, int sc) {
  asm volatile(
      "{\n.reg .pred p;\n.reg .b32 a, b;\n.reg .b64 da, db;\nsetp.ne.b32 p, %71, 0;\n"
      "add.u32 a, %64, %68;\nadd.u32 b, %65, %69;\nmov.b64 da, {a, 0x40000040};\nmov.b64 db, {b, %70};\n"
      "wgmma.mma_async.sync.aligned.m64n128k16.f32.bf16.bf16 {"
      "%0,%1,%2,%3,%4,%5,%6,%7,%8,%9,%10,%11,%12,%13,%14,%15,%16,%17,%18,%19,%20,%21,%22,%23,%24,%25,%26,%27,%28,%29,%30,%31,%32,%33,%34,%35,%36,"
      "%37,%38,%39,%40,%41,%42,%43,%44,%45,%46,%47,%48,%49,%50,%51,%52,%53,%54,%55,%56,%57,%58,%59,%60,%61,%62,%63"
      "}, da, db, p, 1, 1, %66, %67;\n}\n"
      :
      "+f"(d[0]),"+f"(d[1]),"+f"(d[2]),"+f"(d[3]),"+f"(d[4]),"+f"(d[5]),"+f"(d[6]),"+f"(d[7]),"+f"(d[8]),"+f"(d[9]),"+f"(d[10]),"+f"(d[11]),
      "+f"(d[12]),"+f"(d[13]),"+f"(d[14]),"+f"(d[15]),"+f"(d[16]),"+f"(d[17]),"+f"(d[18]),"+f"(d[19]),"+f"(d[20]),"+f"(d[21]),"+f"(d[22]),
      "+f"(d[23]),"+f"(d[24]),"+f"(d[25]),"+f"(d[26]),"+f"(d[27]),"+f"(d[28]),"+f"(d[29]),"+f"(d[30]),"+f"(d[31]),"+f"(d[32]),"+f"(d[33]),
      "+f"(d[34]),"+f"(d[35]),"+f"(d[36]),"+f"(d[37]),"+f"(d[38]),"+f"(d[39]),"+f"(d[40]),"+f"(d[41]),"+f"(d[42]),"+f"(d[43]),"+f"(d[44]),
      "+f"(d[45]),"+f"(d[46]),"+f"(d[47]),"+f"(d[48]),"+f"(d[49]),"+f"(d[50]),"+f"(d[51]),"+f"(d[52]),"+f"(d[53]),"+f"(d[54]),"+f"(d[55]),
      "+f"(d[56]),"+f"(d[57]),"+f"(d[58]),"+f"(d[59]),"+f"(d[60]),"+f"(d[61]),"+f"(d[62]),"+f"(d[63])
      : "r"(la), "r"(lb), "n"(TA), "n"(TB), "n"(OA >> 4), "n"(OB >> 4), "n"(TB ? 0xC0000010u : 0x40000040u), "r"(sc));
}

template <int TA, int TB, uint32_t OA, uint32_t OB>
__device__ __forceinline__ void mma64r(float (&d)[32], uint32_t la, uint32_t lb, int sc) {
  asm volatile(
      "{\n.reg .pred p;\n.reg .b32 a, b;\n.reg .b64 da, db;\nsetp.ne.b32 p, %39, 0;\n"
      "add.u32 a, %32, %36;\nadd.u32 b, %33, %37;\nmov.b64 da, {a, 0x40000040};\nmov.b64 db, {b, %38};\n"
      "wgmma.mma_async.sync.aligned.m64n64k16.f32.bf16.bf16 {"
      "%0,%1,%2,%3,%4,%5,%6,%7,%8,%9,%10,%11,%12,%13,%14,%15,%16,%17,%18,%19,%20,%21,%22,%23,%24,%25,%26,%27,%28,%29,%30,%31"
      "}, da, db, p, 1, 1, %34, %35;\n}\n"
      :
      "+f"(d[0]),"+f"(d[1]),"+f"(d[2]),"+f"(d[3]),"+f"(d[4]),"+f"(d[5]),"+f"(d[6]),"+f"(d[7]),"+f"(d[8]),"+f"(d[9]),"+f"(d[10]),"+f"(d[11]),
      "+f"(d[12]),"+f"(d[13]),"+f"(d[14]),"+f"(d[15]),"+f"(d[16]),"+f"(d[17]),"+f"(d[18]),"+f"(d[19]),"+f"(d[20]),"+f"(d[21]),"+f"(d[22]),
      "+f"(d[23]),"+f"(d[24]),"+f"(d[25]),"+f"(d[26]),"+f"(d[27]),"+f"(d[28]),"+f"(d[29]),"+f"(d[30]),"+f"(d[31])
      : "r"(la), "r"(lb), "n"(TA), "n"(TB), "n"(OA >> 4), "n"(OB >> 4), "n"(TB ? 0xC0000010u : 0x40000040u), "r"(sc));
}

struct Ring { uint32_t s0, ph0; };
__device__ __forceinline__ void ring_pos(const Ring& r, int i, uint32_t& slot, uint32_t& ph) {
  uint32_t s = opaque(r.s0) + (i % NSLOT);
  uint32_t wrap = s >= NSLOT;
  slot = s - (wrap ? NSLOT : 0);
  ph = r.ph0 ^ ((i / NSLOT) & 1) ^ wrap;
}
__device__ __forceinline__ void ring_advance(Ring& r, int n) {
  uint32_t s, p;
  ring_pos(r, n, s, p);
  r.s0 = s; r.ph0 = p;
}
__host__ __device__ constexpr int idxK(int j) { return j == 0 ? 10 : 9 + 2 * j; }
__host__ __device__ constexpr int idxV(int j) { return j == 7 ? 25 : 12 + 2 * j; }
__host__ __device__ constexpr int xs(int c) { return c % NSLOT; }

struct Sched { int first, second, n, delay; };
__device__ __forceinline__ Sched get_sched(int cta) {
  if (cta < N_OCTA) return Sched{cta, 0, 1, 0};
  if (cta < N_OCTA + N_G1) return Sched{cta, NCTA + (cta - N_OCTA), 11, 0};
  return Sched{cta, cta + N_ATT, 10, 1};
}
__device__ __forceinline__ int sched_item(const Sched& s, int k) { return k == 0 ? s.first : s.second + (k - 1) * N_ATT; }

template <int W, bool ACC>
__device__ __forceinline__ void mma_main(float (&d)[80], uint32_t aaddr, uint32_t baddr) {
  const uint32_t la = lo_sw(aaddr), lb = lo_sw(baddr);
  if (ACC) mma160<1, 0, W * 16384, 0>(d, la, lb); else mma160z<1, 0, W * 16384, 0>(d, la, lb);
  mma160<1, 0, W * 16384 + 1 * 2048, 1 * 32>(d, la, lb);
  mma160<1, 0, W * 16384 + 2 * 2048, 2 * 32>(d, la, lb);
  mma160<1, 0, W * 16384 + 3 * 2048, 3 * 32>(d, la, lb);
}
template <int W, bool ACC>
__device__ __forceinline__ void mma_mid(float (&d)[40], uint32_t aaddr, uint32_t baddr) {
  const uint32_t la = lo_sw(aaddr), lb = lo_sw(baddr);
  if (ACC) mma80<1, 0, 8192, W * 10240>(d, la, lb); else mma80z<1, 0, 8192, W * 10240>(d, la, lb);
  mma80<1, 0, 8192 + 1 * 2048, W * 10240 + 1 * 32>(d, la, lb);
  mma80<1, 0, 8192 + 2 * 2048, W * 10240 + 2 * 32>(d, la, lb);
  mma80<1, 0, 8192 + 3 * 2048, W * 10240 + 3 * 32>(d, la, lb);
}
template <int W, bool ACC>
__device__ __forceinline__ void mma_both(float (&dm)[80], float (&dh)[40], uint32_t aaddr, uint32_t baddr) {
  mma_mid<W, ACC>(dh, aaddr, baddr);
  mma_main<W, ACC>(dm, aaddr, baddr);
}
template <int KB, bool ACC>
__device__ __forceinline__ void s_mma(float (&sacc)[80], uint32_t kaddr) {
  const uint32_t la = lo_sw(kaddr), lb = lo_sw(SB + OFF_B);
  if (ACC) mma160<0, 0, KB * 8192, KB * B_SLOT>(sacc, la, lb); else mma160z<0, 0, KB * 8192, KB * B_SLOT>(sacc, la, lb);
  mma160<0, 0, KB * 8192 + 32, KB * B_SLOT + 32>(sacc, la, lb);
  mma160<0, 0, KB * 8192 + 64, KB * B_SLOT + 64>(sacc, la, lb);
  mma160<0, 0, KB * 8192 + 96, KB * B_SLOT + 96>(sacc, la, lb);
}
template <int N>
__device__ __forceinline__ void store_scaled(uint32_t addr, const float (&d)[N], float sc) {
#pragma unroll
  for (int J = 0; J < N / 8; J++)
    stsm_t(addr + J * 2048, pack2(d[8 * J] * sc, d[8 * J + 1] * sc), pack2(d[8 * J + 2] * sc, d[8 * J + 3] * sc),
           pack2(d[8 * J + 4] * sc, d[8 * J + 5] * sc), pack2(d[8 * J + 6] * sc, d[8 * J + 7] * sc));
}
__device__ __forceinline__ float4 lds_f4(uint32_t a) {
  float4 v;
  asm volatile("ld.shared.v4.f32 {%0,%1,%2,%3}, [%4];" : "=f"(v.x), "=f"(v.y), "=f"(v.z), "=f"(v.w) : "r"(a) : "memory");
  return v;
}
__device__ __forceinline__ void norm_pack(uint32_t* p, const float* d, const float4& i) {
  p[0] = pack2(d[0] * i.x, d[1] * i.y); p[1] = pack2(d[4] * i.z, d[5] * i.w);
  p[2] = pack2(d[2] * i.x, d[3] * i.y); p[3] = pack2(d[6] * i.z, d[7] * i.w);
  asm volatile("" : "+r"(p[0]), "+r"(p[1]), "+r"(p[2]), "+r"(p[3])::"memory");
}
template <int W>
__device__ __forceinline__ void pack_first(uint32_t (&pk)[60], const float (&om)[80], const float (&oh)[40], uint32_t laddr) {
  float4 n0 = lds_f4(laddr + W * 80), n1 = lds_f4(laddr + W * 80 + 16);
#pragma unroll
  for (int J = 0; J < 5; J++) {
    const float4 i = n0;
    n0 = n1;
    if (J + 2 < 5) n1 = lds_f4(laddr + W * 80 + (J + 2) * 16);
    norm_pack(&pk[20 + 4 * J], &om[8 * (5 * W + J)], i);
    norm_pack(&pk[4 * J], &oh[8 * J], i);
  }
}
template <int W, int J0, int J1>
__device__ __forceinline__ void pack_second(uint32_t (&pk)[60], const float (&om)[80], uint32_t laddr) {
  float4 n[J1 - J0];
#pragma unroll
  for (int J = J0; J < J1; J++) n[J - J0] = lds_f4(laddr + (1 - W) * 80 + J * 16);
#pragma unroll
  for (int J = J0; J < J1; J++) norm_pack(&pk[40 + 4 * J], &om[8 * (5 * (1 - W) + J)], n[J - J0]);
}
template <int W, int G0, int G1>
__device__ __forceinline__ void store_groups(char* op, const uint32_t (&pk)[60], uint32_t on) {
#pragma unroll
  for (int G = G0; G < G1; G++) {
    const int off = (G < 5 ? 1 : 2 * W) * B_SLOT + (5 * (G < 10 ? W : 1 - W) + G % 5) * 2048;
    asm volatile("{\n.reg .pred p;\nsetp.ne.u32 p, %5, 0;\n@p st.global.v2.b32 [%0], {%1, %2};\n@p st.global.v2.b32 [%0+256], {%3, %4};\n}\n"
                 ::"l"(op + off), "r"(pk[4 * G]), "r"(pk[4 * G + 1]), "r"(pk[4 * G + 2]), "r"(pk[4 * G + 3]), "r"(on) : "memory");
  }
}
__device__ __forceinline__ void publish_generic(uint32_t bar, int lane) {
  __syncwarp();
  mbar_arrive_if0(bar, lane);
}
__device__ __forceinline__ void publish(uint32_t bar, int lane) {
  proxy_fence();
  __syncwarp();
  mbar_arrive_if0(bar, lane);
}

#define A_ADDR(s) (SB + OFF_A + (s) * A_SLOT)
#define B_ADDR(s) (SB + OFF_B + (s) * B_SLOT)
#define WAIT_CHUNK(c, ro, sA)                \
  uint32_t sA;                               \
  {                                          \
    uint32_t pA_;                            \
    ring_pos(ring, (ro) + (c), sA, pA_);     \
    mbar_wait(bud, BAR_FULLA + sA * 8, pA_); \
  }
#define RELEASE_CHUNK(c, sA)                                  \
  mbar_arrive_if0(BAR_EMPTYA + (sA) * 8, tid);                \
  if ((c) < NSLOT) mbar_arrive_if0(BAR_EMPTYB + xs(c) * 8, tid);

template <int W>
__device__ __forceinline__ void attn_consumer(const Sched& sc) {
  int bud = WAIT_BUDGET;
  const int tid = threadIdx.x & 127, lane = tid & 31, warp = tid >> 5;
  const uint32_t st_off = ((lane & 7) + 8 * (lane >> 4)) * 128 + (((2 * warp + ((lane >> 3) & 1)) ^ (lane & 7)) << 4);
  const uint32_t laddr = SB + OFF_L + (lane & 3) * 160;
  const uint32_t o_off = warp * 512 + (lane >> 2) * 32 + ((((lane >> 1) ^ (lane >> 4)) & 1) << 4) + (lane & 1) * 8;
  float om[80], oh[40], sacc[80];
  uint32_t pk[60];
#pragma unroll
  for (int i = 0; i < 40; i++) pk[i] = 0;
  zero_regs(om);
  char* op = (char*)g_o;
  Ring ring{0u, 0u};
  uint32_t par = 0;
  const float qscale = 0.07216878364870322f * 1.4426950408889634f;
  constexpr uint32_t pown = B_ADDR(3 + W), poth = B_ADDR(4 - W);
  TL(0); TLG(62);
  {
    WAIT_CHUNK(0, 0, s0)
    wg_fence();
    mma_both<W, false>(sacc, oh, A_ADDR(s0), B_ADDR(xs(0)));
    wg_commit();
    WAIT_CHUNK(1, 0, s1)
    wg_fence();
    mma_both<W, true>(sacc, oh, A_ADDR(s1), B_ADDR(xs(1)));
    wg_commit();
    wg_wait<1>();
    RELEASE_CHUNK(0, s0)
  }
#pragma unroll 1
  for (int it = 0;; it++) {
#pragma unroll
    for (int c = 2; c < 8; c++) {
      WAIT_CHUNK(c, 0, sA)
      TL(40 + c);
      wg_fence();
      mma_both<W, true>(sacc, oh, A_ADDR(sA), B_ADDR(xs(c)));
      wg_commit();
      wg_wait<1>();
      uint32_t sP, pP;
      ring_pos(ring, c - 1, sP, pP);
      RELEASE_CHUNK(c - 1, sP)
      if (c == 2) { pack_second<W, 0, 1>(pk, om, laddr); store_groups<W, 0, 2>(op, pk, STGON); }
      if (c == 3) { pack_second<W, 1, 2>(pk, om, laddr); store_groups<W, 2, 5>(op, pk, STGON); }
      if (c == 4) { pack_second<W, 2, 3>(pk, om, laddr); store_groups<W, 5, 7>(op, pk, STGON); }
      if (c == 5) { pack_second<W, 3, 4>(pk, om, laddr); store_groups<W, 7, 10>(op, pk, STGON); }
      if (c == 6) { pack_second<W, 4, 5>(pk, om, laddr); store_groups<W, 10, 12>(op, pk, STGON); }
      if (c == 7) store_groups<W, 12, 15>(op, pk, STGON);
      if (c == 7) {
        __syncwarp();
        mbar_arrive_if0(BAR_OFULL, lane | (it == 0));
      }
    }
    uint32_t sK0, pK0, s7, p7;
    ring_pos(ring, idxK(W), sK0, pK0);
    ring_pos(ring, 7, s7, p7);
    if (W == 1) {
      wg_wait<0>();
      RELEASE_CHUNK(7, s7)
      mbar_arrive_if0(BAR_XDONE, tid);
    }
    WAIT_CHUNK(8, 0, s8)
    WAIT_CHUNK(9, 0, s9)
    TL(48);
    if (W == 1) bar_sync(5, 256);
    wg_fence();
    mma_mid<W, true>(oh, A_ADDR(s8), B_ADDR(xs(8)));
    mma_mid<W, true>(oh, A_ADDR(s9), B_ADDR(xs(9)));
    wg_commit();
    mma_main<W, true>(sacc, A_ADDR(s8), B_ADDR(xs(8)));
    mma_main<W, true>(sacc, A_ADDR(s9), B_ADDR(xs(9)));
    wg_commit();
    if (W == 0) bar_arrive(5, 256);
    TL(49);
    wg_wait<1>();
    reg_fence(oh);
    if (W == 0) {
      RELEASE_CHUNK(7, s7)
      mbar_arrive_if0(BAR_XDONE, tid);
    }
    mbar_wait(bud, BAR_XDONE, par);
    store_scaled(B_ADDR(1) + W * 10240 + st_off, oh, qscale);
    publish(BAR_QH, lane);
    if (W == 0) mbar_wait(bud, BAR_FULLA + sK0 * 8, pK0);
    wg_wait<0>();
    reg_fence(sacc);
    TL(1);
    RELEASE_CHUNK(8, s8)
    RELEASE_CHUNK(9, s9)
    store_scaled(B_ADDR(2 * W) + st_off, sacc, qscale);
    publish(BAR_QM + W * 8, lane);
    TL(2);
    uint32_t sK = sK0, sV1 = 0;
    if (W == 0) {
      zero_regs(om); zero_regs(oh);
      reg_fence(om); reg_fence(oh);
      mbar_wait(bud, BAR_QM, par);
      wg_fence();
      s_mma<0, false>(sacc, A_ADDR(sK));
      mbar_wait(bud, BAR_QH, par);
      TL(3);
      wg_fence();
      s_mma<1, true>(sacc, A_ADDR(sK));
      mbar_wait(bud, BAR_QM + 8, par);
      TL(5);
      wg_fence();
      s_mma<2, true>(sacc, A_ADDR(sK));
      wg_commit();
      wg_commit();
      bar_arrive(2, 256);
    } else {
      uint32_t pV1;
      ring_pos(ring, idxV(0), sV1, pV1);
      mbar_wait(bud, BAR_FULLA + sK * 8, pK0);
      bar_sync(2, 256);
      wg_fence();
      s_mma<0, false>(sacc, A_ADDR(sK));
      s_mma<1, true>(sacc, A_ADDR(sK));
      s_mma<2, true>(sacc, A_ADDR(sK));
      wg_commit();
      TL(6);
      mbar_wait(bud, BAR_FULLA + sV1 * 8, pV1);
      mbar_wait(bud, BAR_PFULL, 0);
      TL(7);
      wg_fence();
      mma_both<W, false>(om, oh, A_ADDR(sV1), poth);
      wg_commit();
      bar_arrive(1, 256);
    }
    Ring rv;
    ring_pos(ring, idxV(W), rv.s0, rv.ph0);
#pragma unroll 1
    for (int jj = 0;; jj++) {
      wg_wait<1>();
      reg_fence(sacc);
      TL(8 + jj * 7);
      mbar_arrive2_if0(BAR_EMPTYA + sK * 8, tid);
      mbar_arrive_if0(BAR_EMPTYB + tid * 8, (tid >= 3) | (jj != 3));
#pragma unroll
      for (int J = 0; J < 10; J++) {
        stsm_t(pown + st_off + J * 2048, pack2(ex2(sacc[8 * J]), ex2(sacc[8 * J + 1])), pack2(ex2(sacc[8 * J + 2]), ex2(sacc[8 * J + 3])),
               pack2(ex2(sacc[8 * J + 4]), ex2(sacc[8 * J + 5])), pack2(ex2(sacc[8 * J + 6]), ex2(sacc[8 * J + 7])));
        if (W == 1 && (J == 2 || J == 5)) publish_generic(BAR_PMID + (J / 3) * 8, lane | (jj != 3));
        if (J == 5) {
          wg_wait<0>();
          mbar_arrive_if0(BAR_EMPTYA + sV1 * 8, tid | (W == 0 && jj == 0));
        }
      }
      publish(BAR_PFULL + W * 8, lane);
      TL(10 + jj * 7);
      if (jj == 3) break;
      uint32_t pK, pV1;
      ring_pos(rv, 1, sK, pK);
      ring_pos(rv, 2, sV1, pV1);
      mbar_wait(bud, BAR_FULLA + rv.s0 * 8, rv.ph0);
      bar_sync(1 + W, 256);
      wg_fence();
      mma_both<W, true>(om, oh, A_ADDR(rv.s0), pown);
      wg_commit();
      mbar_wait(bud, BAR_FULLA + sK * 8, pK);
      TL(11 + jj * 7);
      wg_fence();
      s_mma<0, false>(sacc, A_ADDR(sK));
      s_mma<1, true>(sacc, A_ADDR(sK));
      wg_commit();
      wg_wait<1>();
      mbar_arrive_if0(BAR_EMPTYA + rv.s0 * 8, tid);
      wg_fence();
      s_mma<2, true>(sacc, A_ADDR(sK));
      wg_commit();
      TL(13 + jj * 7);
      mbar_wait(bud, BAR_FULLA + sV1 * 8, pV1);
      mbar_wait(bud, BAR_PFREE + W * 8, jj & 1);
      mbar_wait(bud, BAR_PFULL + (1 - W) * 8, (jj + W) & 1);
      TL(14 + jj * 7);
      wg_fence();
      mma_both<W, true>(om, oh, A_ADDR(sV1), poth);
      wg_commit();
      bar_arrive(2 - W, 256);
      ring_advance(rv, 4);
    }
    uint32_t sV7, pV7;
    ring_pos(ring, idxV(7), sV7, pV7);
    if (W == 0) {
      uint32_t sV6, pV6;
      ring_pos(ring, idxV(6), sV6, pV6);
      mbar_wait(bud, BAR_FULLA + sV6 * 8, pV6);
      bar_sync(1, 256);
      wg_fence();
      mma_both<0, true>(om, oh, A_ADDR(sV6), pown);
      wg_commit();
      mbar_wait(bud, BAR_FULLA + sV7 * 8, pV7);
      wg_wait<0>();
      mbar_arrive_if0(BAR_EMPTYA + sV6 * 8, tid);
      mbar_wait(bud, BAR_PFULL + 8, 1);
      wg_fence();
      mma_both<0, true>(om, oh, A_ADDR(sV7), poth);
      wg_commit();
      bar_arrive(6, 256);
    } else {
      mbar_wait(bud, BAR_FULLA + sV7 * 8, pV7);
      bar_sync(6, 256);
    }
    TL(32);
    op = (char*)g_o + (size_t)(sched_item(sc, it) % ORING) * O_ITEM_BYTES + o_off;
    if (it + 1 == sc.n) {
      if (W == 1) {
        wg_fence();
        mma_both<1, true>(om, oh, A_ADDR(sV7), pown);
        wg_commit();
      }
      wg_wait<0>();
      reg_fence(om); reg_fence(oh);
      TL(33);
      mbar_wait(bud, BAR_LFULL, par);
      TL(34);
      pack_first<W>(pk, om, oh, laddr);
      store_groups<W, 0, 10>(op, pk, 1);
      pack_second<W, 0, 5>(pk, om, laddr);
      store_groups<W, 10, 15>(op, pk, 1);
      publish_generic(BAR_OFULL, lane);
      TL(35); TLG(63);
      TL_FLUSH();
      break;
    }
    {
      if (W == 1) {
        wg_fence();
        mma_both<1, true>(om, oh, A_ADDR(sV7), pown);
        wg_commit();
      }
      WAIT_CHUNK(0, 26, s0)
      WAIT_CHUNK(1, 26, s1)
      if (W == 0) {
        wg_wait<0>();
        reg_fence(om); reg_fence(oh);
        TL(33);
        wg_fence();
        mma_main<W, false>(sacc, A_ADDR(s0), B_ADDR(xs(0)));
        wg_commit();
      } else {
        wg_fence();
        mma_main<W, false>(sacc, A_ADDR(s0), B_ADDR(xs(0)));
        mma_main<W, true>(sacc, A_ADDR(s1), B_ADDR(xs(1)));
        wg_commit();
        wg_wait<1>();
        reg_fence(om); reg_fence(oh);
        TL(33);
      }
      mbar_arrive_if0(BAR_EMPTYA + sV7 * 8, tid);
      mbar_wait(bud, BAR_LFULL, par);
      mbar_arrive_if0(BAR_EMPTYB + 24 + tid * 8, tid >= 2);
      TL(34);
      pack_first<W>(pk, om, oh, laddr);
      TL(36);
      wg_fence();
      mma_mid<W, false>(oh, A_ADDR(s0), B_ADDR(xs(0)));
      wg_commit();
      mma_mid<W, true>(oh, A_ADDR(s1), B_ADDR(xs(1)));
      if (W == 0) mma_main<W, true>(sacc, A_ADDR(s1), B_ADDR(xs(1)));
      wg_commit();
      TL(37);
      wg_wait<1>();
      RELEASE_CHUNK(0, s0)
      TL(35); TLG(63);
    }
    TL_FLUSH();
    TL(0); TLG(62);
    ring_advance(ring, 26);
    par ^= 1;
  }
}

__device__ __forceinline__ uint4 lds128(uint32_t a) {
  uint4 v;
  asm volatile("ld.shared.v4.b32 {%0,%1,%2,%3}, [%4];" : "=r"(v.x), "=r"(v.y), "=r"(v.z), "=r"(v.w) : "r"(a) : "memory");
  return v;
}
__device__ __forceinline__ void acc2(float& s, float& t, uint32_t w) {
  s += __uint_as_float(w << 16);
  t += __uint_as_float(w & 0xffff0000u);
}
__device__ __forceinline__ uint32_t badd2(uint32_t a, uint32_t b) { uint32_t r; asm("add.rn.bf16x2 %0, %1, %2;" : "=r"(r) : "r"(a), "r"(b)); return r; }
__device__ __forceinline__ void sum_unit(float& acc, uint32_t pb) {
  const uint4 v0 = lds128(pb), v1 = lds128(pb ^ 32), v2 = lds128(pb ^ 64), v3 = lds128(pb ^ 96);
  const uint32_t w0 = badd2(v0.x, v0.y), w1 = badd2(v0.z, v0.w);
  float s0 = acc + __uint_as_float(w0 << 16), t0 = __uint_as_float(w0 & 0xffff0000u);
  float s1 = __uint_as_float(w1 << 16), t1 = __uint_as_float(w1 & 0xffff0000u);
  acc2(s0, t0, badd2(v1.x, v1.y)); acc2(s1, t1, badd2(v1.z, v1.w));
  acc2(s0, t0, badd2(v2.x, v2.y)); acc2(s1, t1, badd2(v2.z, v2.w));
  acc2(s0, t0, badd2(v3.x, v3.y)); acc2(s1, t1, badd2(v3.z, v3.w));
  acc = (s0 + t0) + (s1 + t1);
}
__device__ __forceinline__ void attn_helper(const Params& p, int hw, const Sched& sc, int epoch) {
  int bud = WAIT_BUDGET;
  const int lane = threadIdx.x & 31, r = lane >> 1;
  const uint32_t a0 = B_ADDR(3) + (16 * hw + r) * 128 + (lane & 1) * 16 + ((r & 3) << 5);
  uint32_t par = 0;
#pragma unroll 1
  for (int it = 0; it < sc.n; it++) {
    const int item = sched_item(sc, it);
    float acc[4] = {0.f, 0.f, 0.f, 0.f};
#pragma unroll 1
    for (int j = 0; j < 8; j++) {
      const uint32_t pb = a0 + (j & 1) * B_SLOT, bfull = BAR_PFULL + (j & 1) * 8, pfull = (j >> 1) & 1;
      mbar_wait(bud, j == 7 ? BAR_PMID : bfull, j == 7 ? par : pfull);
      sum_unit(acc[0], pb);
      if (j == 7) mbar_wait(bud, BAR_PMID + 8, par);
      sum_unit(acc[1], pb + 6144);
      if (j == 7) mbar_wait(bud, bfull, pfull);
      sum_unit(acc[2], pb + 2 * 6144);
      if (hw == 0) sum_unit(acc[3], pb + 3 * 6144);
      __syncwarp();
      mbar_arrive_if0(BAR_PFREE + (j & 1) * 8, lane);
      if (j == 5 && hw == 2 && item >= ORING) flag_wait(bud, &g_done[(item - ORING) >> 4], (epoch + 1) * N_OCTA);
    }
    bool bad = false;
    const uint32_t la = SB + OFF_L + (((r & 7) >> 1) * 40 + 2 * (r >> 3) + (r & 1) + 4 * hw) * 4;
#pragma unroll
    for (int u = 0; u < 4; u++) {
      const float l = acc[u] + __shfl_xor_sync(0xffffffffu, acc[u], 1);
      if (u < 3 || hw == 0) {
        bad |= !(l >= 8.8817841970012523e-16f && l <= 1.125899906842624e15f);
        float inv;
        asm("rcp.approx.ftz.f32 %0, %1;" : "=f"(inv) : "f"(l));
        asm volatile("st.shared.f32 [%0], %1;" ::"r"(la + u * 48), "f"(inv) : "memory");
      }
    }
    publish_generic(BAR_LFULL, lane);
    if (lane == 0) TLP(40 + hw * 4);
    const bool anybad = __any_sync(0xffffffffu, bad);
    if (lane == 0) g_bad[item * 4 + hw] = anybad;
    if (hw == 1) {
      mbar_wait(bud, BAR_OFULL, par);
      if (lane == 0) {
        TLP(41 + hw * 4);
        asm volatile("red.release.gpu.global.add.s32 [%0], 1;" ::"l"(&g_ready[item]) : "memory");
        TLP(42 + hw * 4);
      }
      __syncwarp();
    }
    par ^= 1;
  }
}

__device__ __forceinline__ void attn_producer(const Params& p, const Sched& sc) {
  int bud = WAIT_BUDGET;
  uint32_t sa = 0, pa = 1;
  uint64_t pol;
  asm volatile("createpolicy.fractional.L2::evict_first.b64 %0, 1.0;" : "=l"(pol));
  uint64_t poln;
  asm volatile("createpolicy.fractional.L2::evict_normal.b64 %0, 1.0;" : "=l"(poln));
  if (sc.delay) {
    const long long t0 = clock64();
    while (clock64() - t0 < G2_DELAY) __nanosleep(200);
  }
#pragma unroll 1
  for (int it = 0; it < sc.n; it++) {
    const int item = sched_item(sc, it);
    const int blk = item >> 9, h = (item >> 4) & 31, b = item & 15;
    const int row0 = (b * NH + h) * SK;
#pragma unroll
    for (int c = 0; c < 10; c++) {
      mbar_wait(bud, BAR_EMPTYA + sa * 8, pa);
      TLP(c);
      mbar_expect(BAR_FULLA + sa * 8, A_SLOT + B_SLOT);
      tma3d(A_ADDR(sa), &p.wq[blk], BAR_FULLA + sa * 8, 0, c * 64, h * 3);
      mbar_wait(bud, BAR_EMPTYB + xs(c) * 8, c < NSLOT);
      TLP(10 + c);
      tma2d(B_ADDR(xs(c)), &p.x[blk], BAR_FULLA + sa * 8, c * 64, b * SQ);
      if (++sa == NSLOT) { sa = 0; pa ^= 1; }
    }
#pragma unroll
    for (int i = 0; i < 16; i++) {
      const bool isK = (i == 0) || ((i & 1) && i < 15);
      const int j = i == 0 ? 0 : (i == 15 ? 7 : (isK ? (i + 1) >> 1 : (i - 2) >> 1));
      mbar_wait(bud, BAR_EMPTYA + sa * 8, pa);
      TLP(20 + i);
      mbar_expect(BAR_FULLA + sa * 8, A_SLOT);
      tma3d_hint(A_ADDR(sa), isK ? &p.k[blk] : &p.v[blk], BAR_FULLA + sa * 8, 0, row0 + j * 64, 0, pol);
      if (++sa == NSLOT) { sa = 0; pa ^= 1; }
    }
  }
}

template <int W>
__device__ __forceinline__ void oproj_consumer() {
  int bud = WAIT_BUDGET;
  const int tid = threadIdx.x & 127, lane = tid & 31, warp = tid >> 5;
  const int qrow = 8 * ((lane >> 1) & 1) + 4 * (lane >> 4) + 2 * ((lane >> 2) & 1) + (lane & 1);
  const uint32_t st_off = qrow * 128 + (((2 * warp + ((lane >> 3) & 1)) ^ (qrow & 7)) << 4);
  float a0[64], a1[64], ah[32];
  zero_regs(a0); zero_regs(a1); zero_regs(ah);
#pragma unroll 1
  for (int blk = 0; blk < 2; blk++) {
    int c3 = 0, step = blk * NH;
#pragma unroll 1
    for (int c = 0; c < 96; c++) {
      const uint32_t st = c & 3;
      mbar_wait(bud, BAR_GFULL + st * 8, (c >> 2) & 1);
      wg_fence();
      const uint32_t la = lo_sw(SB + st * O_STAGE), lb = lo_o(SB + st * O_STAGE + O_AB);
#define O_STEP(ks, sc)                                                   \
  mma64r<1, 1, 2 * 8192 + ks * 2048, W * 8192 + ks * 512>(ah, la, lb, sc);    \
  mma128r<1, 1, (W * 3) * 8192 + ks * 2048, ks * 512>(a0, la, lb, sc);        \
  mma128r<1, 1, (W * 3 + 1) * 8192 + ks * 2048, ks * 512>(a1, la, lb, sc);
      O_STEP(0, c != 0) O_STEP(1, 1) O_STEP(2, 1) O_STEP(3, 1)
#undef O_STEP
      wg_commit();
      if (++c3 == 3) {
        c3 = 0;
        if (W == 0)
          asm volatile("{\n.reg .pred p;\nsetp.eq.u32 p, %1, 0;\n@p red.relaxed.gpu.global.add.s32 [%0], 1;\n}\n" ::"l"(&g_done[step]), "r"(tid) : "memory");
        TL(step);
        step++;
      }
      wg_wait<1>();
      mbar_arrive_if0(BAR_GEMPTY + ((c - 1) & 3) * 8, tid | (c == 0) | (c == 95));
    }
    wg_wait<0>();
    reg_fence(a0); reg_fence(a1); reg_fence(ah);
    bar_sync(3, 256);
    const uint32_t sg = SB + 2 * O_STAGE + st_off;
    store_scaled(sg + 2 * 16384 + W * 8192, ah, 1.0f);
    store_scaled(sg + (W * 3) * 16384, a0, 1.0f);
    store_scaled(sg + (W * 3 + 1) * 16384, a1, 1.0f);
    publish(BAR_GOUT, lane);
  }
  TL_FLUSH();
}

__device__ __forceinline__ void oproj_producer(const Params& p, int cta, int epoch) {
  int bud = WAIT_BUDGET;
  const int half = cta & 1, r0 = (cta >> 1) * 128;
  const int b0 = r0 / SQ, off0 = r0 - b0 * SQ, n0 = min(128, SQ - off0), n1 = 128 - n0;
  const int target = epoch + 1;
#pragma unroll 1
  for (int step = 0; step < 2 * NH; step++) {
    const int blk = step >> 5, item0 = step * 16 + b0;
    const char* o0 = (const char*)g_o + (size_t)(item0 % ORING) * O_ITEM_BYTES + off0 * 128;
    const char* o1 = (const char*)g_o + (size_t)((item0 + 1) % ORING) * O_ITEM_BYTES;
#pragma unroll 1
    for (int kb = 0; kb < 3; kb++) {
      const int c = step * 3 + kb;
      const uint32_t st = c & 3, dst = SB + st * O_STAGE, bar = BAR_GFULL + st * 8;
      mbar_wait(bud, BAR_GEMPTY + st * 8, ((c >> 2) & 1) ^ 1);
      mbar_expect(bar, O_STAGE);
      tma3d(dst, &p.wo[blk], bar, 0, ((step & 31) * 3 + kb) * 64, half * 5);
      if (kb == 0) {
        flag_wait(bud, &g_ready[item0], target);
        if (n1) flag_wait(bud, &g_ready[item0 + 1], target);
        asm volatile("fence.proxy.async.global;" ::: "memory");
      }
      bulk_load(dst + O_AB, o0 + kb * B_SLOT, n0 * 128, bar);
      if (n1) bulk_load(dst + O_AB + n0 * 128, o1 + kb * B_SLOT, n1 * 128, bar);
    }
  }
}

__device__ __forceinline__ void oproj_storer(const Params& p, int cta) {
  int bud = WAIT_BUDGET;
  const int half = cta & 1, r0 = (cta >> 1) * 128;
#pragma unroll 1
  for (int blk = 0; blk < 2; blk++) {
    mbar_wait(bud, BAR_GOUT, blk);
    for (int k = 0; k < 5; k++) tma_store2d(&p.out, SB + 2 * O_STAGE + k * 16384, blk * DM + half * 320 + k * 64, r0);
    asm volatile("cp.async.bulk.commit_group;" ::: "memory");
    asm volatile("cp.async.bulk.wait_group.read 0;" ::: "memory");
    mbar_arrive2_if0(BAR_GEMPTY + 16, 0);
    mbar_arrive2_if0(BAR_GEMPTY + 24, 0);
  }
  asm volatile("cp.async.bulk.wait_group 0;" ::: "memory");
}

__global__ void __launch_bounds__(384, 1) fused_kernel(const __grid_constant__ Params p) {
  extern __shared__ __align__(1024) char smem_raw[];
  if ((smem_u32(smem_raw) & 0xFFFFFFu) != SB) return;
  const int cta = blockIdx.x;
  const int epoch = g_epoch[cta];
  if (threadIdx.x == 0) {
    for (int i = 0; i < NSLOT; i++) {
      mbar_init(BAR_FULLA + i * 8, 1); mbar_init(BAR_EMPTYA + i * 8, 2);
      mbar_init(BAR_EMPTYB + i * 8, 2);
    }
    mbar_init(BAR_XDONE, 2); mbar_init(BAR_QH, 8); mbar_init(BAR_QM, 4); mbar_init(BAR_QM + 8, 4);
    mbar_init(BAR_PFULL, 4); mbar_init(BAR_PFULL + 8, 4);
    mbar_init(BAR_PFREE, 3); mbar_init(BAR_PFREE + 8, 3);
    mbar_init(BAR_LFULL, 3); mbar_init(BAR_PMID, 4); mbar_init(BAR_PMID + 8, 4);
    mbar_init(BAR_OFULL, 8);
    for (int i = 0; i < O_NST; i++) { mbar_init(BAR_GFULL + i * 8, 1); mbar_init(BAR_GEMPTY + i * 8, 2); }
    mbar_init(BAR_GOUT, 8);
    asm volatile("fence.mbarrier_init.release.cluster;" ::: "memory");
    proxy_fence();
  }
  __syncthreads();
  if (threadIdx.x == 0) g_epoch[cta] = epoch + 1;
  const int warp = __shfl_sync(0xffffffffu, threadIdx.x >> 5, 0);
  const Sched sc = get_sched(cta);
  if (warp >= 8) {
    asm volatile("setmaxnreg.dec.sync.aligned.u32 40;");
    if (warp == 8) {
      if (elect_one()) attn_producer(p, sc);
      __syncwarp();
    } else {
      attn_helper(p, warp - 9, sc, epoch);
    }
    if (cta < N_OCTA) {
      bar_sync(4, 128);
      if (warp == 8) {
        if (elect_one()) oproj_producer(p, cta, epoch);
      } else if (warp == 9) {
        if (elect_one()) oproj_storer(p, cta);
      }
    }
  } else {
    asm volatile("setmaxnreg.inc.sync.aligned.u32 232;");
    if (warp < 4) {
      attn_consumer<0>(sc);
      if (cta < N_OCTA) oproj_consumer<0>();
    } else {
      attn_consumer<1>(sc);
      if (cta < N_OCTA) oproj_consumer<1>();
    }
  }
}

typedef CUresult (*EncodeFn)(CUtensorMap*, CUtensorMapDataType, cuuint32_t, void*, const cuuint64_t*, const cuuint64_t*, const cuuint32_t*,
                             const cuuint32_t*, CUtensorMapInterleave, CUtensorMapSwizzle, CUtensorMapL2promotion, CUtensorMapFloatOOBfill);

void make3d(EncodeFn enc, CUtensorMap* m, const void* ptr, uint64_t rows, uint64_t cols, uint32_t box_rows, uint32_t box_blocks,
            CUtensorMapL2promotion promo = CU_TENSOR_MAP_L2_PROMOTION_L2_128B) {
  cuuint64_t gd[3] = {64, rows, cols / 64};
  cuuint64_t gs[2] = {cols * 2, 128};
  cuuint32_t bd[3] = {64, box_rows, box_blocks}, es[3] = {1, 1, 1};
  enc(m, CU_TENSOR_MAP_DATA_TYPE_BFLOAT16, 3, (void*)ptr, gd, gs, bd, es, CU_TENSOR_MAP_INTERLEAVE_NONE, CU_TENSOR_MAP_SWIZZLE_128B,
      promo, CU_TENSOR_MAP_FLOAT_OOB_FILL_NONE);
}
void make2d(EncodeFn enc, CUtensorMap* m, const void* ptr, uint64_t rows, uint64_t cols, uint32_t box_rows) {
  cuuint64_t gd[2] = {cols, rows};
  cuuint64_t gs[1] = {cols * 2};
  cuuint32_t bd[2] = {64, box_rows}, es[2] = {1, 1};
  enc(m, CU_TENSOR_MAP_DATA_TYPE_BFLOAT16, 2, (void*)ptr, gd, gs, bd, es, CU_TENSOR_MAP_INTERLEAVE_NONE, CU_TENSOR_MAP_SWIZZLE_128B,
      CU_TENSOR_MAP_L2_PROMOTION_L2_128B, CU_TENSOR_MAP_FLOAT_OOB_FILL_NONE);
}

}

extern "C" void kernel_launch(void* const* d_in, const int* in_sizes, int n_in, void* d_out, int out_size) {
  static EncodeFn enc = nullptr;
  if (!enc) {
    cudaDriverEntryPointQueryResult qr;
    cudaGetDriverEntryPoint("cuTensorMapEncodeTiled", (void**)&enc, cudaEnableDefault, &qr);
    cudaFuncSetAttribute(fused_kernel, cudaFuncAttributeMaxDynamicSharedMemorySize, SMEM_BYTES);
  }
  Params p;
  for (int s = 0; s < 2; s++) {
    make2d(enc, &p.x[s], d_in[5 * s + 0], NB * SQ, DM, SQ);
    make3d(enc, &p.k[s], d_in[5 * s + 1], (uint64_t)NB * NH * SK, DH, 64, 3, KV_PROMO);
    make3d(enc, &p.v[s], d_in[5 * s + 2], (uint64_t)NB * NH * SK, DH, 64, 3, KV_PROMO);
    make3d(enc, &p.wq[s], d_in[5 * s + 3], DM, NH * DH, 64, 3);
    make3d(enc, &p.wo[s], d_in[5 * s + 4], NH * DH, DM, 64, 5);
    p.kp[s] = (const __nv_bfloat16*)d_in[5 * s + 1];
    p.vp[s] = (const __nv_bfloat16*)d_in[5 * s + 2];
  }
  make2d(enc, &p.out, d_out, NB * SQ, 2 * DM, 128);
  fused_kernel<<<NCTA, 384, SMEM_BYTES>>>(p);
}
```

```cpp
#include <cuda_runtime.h>
#include <cuda_bf16.h>
#include <cuda.h>
#include <stdint.h>

#define DEBUG_TIMEOUT 1

namespace {

constexpr int SQ = 160, DM = 640, NH = 32, SK = 512, DH = 192, NB = 16;
constexpr int NITEMS = 2 * NB * NH;
constexpr int NCTA = 132, N_OCTA = 40, N_G2 = 28, N_G1 = 64, N_ATT = N_G1 + N_G2;
constexpr int ORING = 112, STAG_A0 = 15, STAG_SLOPE = 240, O_DELAY = 0, O_SLOPE = 0, G2_EXTRA = 0, DONE_J = 5;
constexpr int ORING_MAX = ORING;
#define SPREAD 1
#define STGON it
#define PF_MODE 1
constexpr int A_SLOT = 24576, B_SLOT = 20480, NSLOT = 5;
constexpr int OFF_A = 0;
constexpr int OFF_B = NSLOT * A_SLOT;
constexpr int O_STAGE = 57344, O_AB = 40960, O_NST = 4;
constexpr int OFF_L = O_NST * O_STAGE;
constexpr int OFF_BAR = OFF_L + 160 * 4;
constexpr int SMEM_BYTES = OFF_BAR + 384 + 512;
static_assert(OFF_B + NSLOT * B_SLOT <= OFF_L, "smem layout");
constexpr uint32_t SB = 1024;
constexpr uint32_t BARS = SB + OFF_BAR;
constexpr uint32_t BAR_FULLA = BARS, BAR_EMPTYA = BARS + 40, BAR_PMID = BARS + 80, BAR_EMPTYB = BARS + 120, BAR_XDONE = BARS + 160,
                   BAR_QH = BARS + 168, BAR_QM = BARS + 96, BAR_PFULL = BARS + 184, BAR_PFREE = BARS + 200, BAR_LFULL = BARS + 216,
                   BAR_OFULL = BARS + 224, BAR_GFULL = BARS + 248, BAR_GEMPTY = BARS + 280, BAR_GOUT = BARS + 312;
constexpr int O_ITEM_BYTES = SQ * DH * 2;

struct alignas(64) Params {
  CUtensorMap x[2], wq[2], k[2], v[2], wo[2], out;
  const __nv_bfloat16 *xp[2], *wqp[2], *kp[2], *vp[2];
};

__device__ uint4 g_o[(size_t)ORING_MAX * O_ITEM_BYTES / 16];
__device__ int g_ready[NITEMS];
__device__ int g_done[2 * NH];
__device__ int g_epoch[NCTA];

#define TLP(id)
#define TLG(id)
#define TL(id)
#define TL_FLUSH()
__device__ __forceinline__ uint32_t smem_u32(const void* p) { return (uint32_t)__cvta_generic_to_shared(p); }
__device__ __forceinline__ void wg_fence() { asm volatile("wgmma.fence.sync.aligned;" ::: "memory"); }
__device__ __forceinline__ void wg_commit() { asm volatile("wgmma.commit_group.sync.aligned;" ::: "memory"); }
template <int N> __device__ __forceinline__ void wg_wait() { asm volatile("wgmma.wait_group.sync.aligned %0;" ::"n"(N) : "memory"); }
template <int N> __device__ __forceinline__ void reg_fence(float (&d)[N]) {
#pragma unroll
  for (int i = 0; i < N; i++) asm volatile("" : "+f"(d[i])::"memory");
}
template <int N> __device__ __forceinline__ void zero_regs(float (&d)[N]) {
#pragma unroll
  for (int i = 0; i < N; i++) d[i] = 0.f;
}
__device__ __forceinline__ void proxy_fence() { asm volatile("fence.proxy.async.shared::cta;" ::: "memory"); }
__device__ __forceinline__ void mbar_init(uint32_t bar, int cnt) { asm volatile("mbarrier.init.shared::cta.b64 [%0], %1;" ::"r"(bar), "r"(cnt) : "memory"); }
__device__ __forceinline__ void mbar_arrive_if0(uint32_t bar, uint32_t sel) {
  asm volatile("{\n.reg .pred p;\nsetp.eq.u32 p, %1, 0;\n@p mbarrier.arrive.shared::cta.b64 _, [%0];\n}\n" ::"r"(bar), "r"(sel) : "memory");
}
__device__ __forceinline__ void mbar_arrive2_if0(uint32_t bar, uint32_t sel) {
  asm volatile("{\n.reg .pred p;\nsetp.eq.u32 p, %1, 0;\n@p mbarrier.arrive.shared::cta.b64 _, [%0], 2;\n}\n" ::"r"(bar), "r"(sel) : "memory");
}
__device__ __forceinline__ void mbar_expect(uint32_t bar, uint32_t bytes) {
  asm volatile("mbarrier.arrive.expect_tx.shared::cta.b64 _, [%0], %1;" ::"r"(bar), "r"(bytes) : "memory");
}
__device__ __forceinline__ void mbar_wait(int& bud, uint32_t bar, uint32_t parity) {
  asm volatile(
      "{\n.reg .pred p, q;\n"
      "LW:\n"
      "mbarrier.try_wait.parity.shared::cta.b64 p, [%1], %2;\n"
      "@!p add.s32 %0, %0, -1;\n"
      "setp.gt.and.s32 q, %0, 0, !p;\n"
      "@q bra LW;\n}\n" : "+r"(bud) : "r"(bar), "r"(parity) : "memory");
}
constexpr int WAIT_BUDGET = 1 << 22;
__device__ __forceinline__ bool elect_one() {
  uint32_t p;
  asm volatile("{\n.reg .pred p;\nelect.sync _|p, 0xffffffff;\nselp.u32 %0, 1, 0, p;\n}\n" : "=r"(p));
  return p;
}
__device__ __forceinline__ void tma2d(uint32_t dst, const CUtensorMap* m, uint32_t bar, int c0, int c1) {
  asm volatile("cp.async.bulk.tensor.2d.shared::cluster.global.mbarrier::complete_tx::bytes [%0], [%1, {%3, %4}], [%2];"
               ::"r"(dst), "l"(m), "r"(bar), "r"(c0), "r"(c1) : "memory");
}
__device__ __forceinline__ void tma3d(uint32_t dst, const CUtensorMap* m, uint32_t bar, int c0, int c1, int c2) {
  asm volatile("cp.async.bulk.tensor.3d.shared::cluster.global.mbarrier::complete_tx::bytes [%0], [%1, {%3, %4, %5}], [%2];"
               ::"r"(dst), "l"(m), "r"(bar), "r"(c0), "r"(c1), "r"(c2) : "memory");
}
__device__ __forceinline__ void tma3d_hint(uint32_t dst, const CUtensorMap* m, uint32_t bar, int c0, int c1, int c2, uint64_t pol) {
  asm volatile("cp.async.bulk.tensor.3d.shared::cluster.global.mbarrier::complete_tx::bytes.L2::cache_hint [%0], [%1, {%3, %4, %5}], [%2], %6;"
               ::"r"(dst), "l"(m), "r"(bar), "r"(c0), "r"(c1), "r"(c2), "l"(pol) : "memory");
}
__device__ __forceinline__ void bulk_load(uint32_t dst, const void* src, uint32_t bytes, uint32_t bar) {
  asm volatile("cp.async.bulk.shared::cluster.global.mbarrier::complete_tx::bytes [%0], [%1], %2, [%3];"
               ::"r"(dst), "l"(src), "r"(bytes), "r"(bar) : "memory");
}
__device__ __forceinline__ void tma_store2d(const CUtensorMap* m, uint32_t src, int c0, int c1) {
  asm volatile("cp.async.bulk.tensor.2d.global.shared::cta.bulk_group [%0, {%2, %3}], [%1];" ::"l"(m), "r"(src), "r"(c0), "r"(c1) : "memory");
}
__device__ __forceinline__ void bar_sync(int id, int n) { asm volatile("bar.sync %0, %1;" ::"r"(id), "r"(n) : "memory"); }
__device__ __forceinline__ void bar_arrive(int id, int n) { asm volatile("bar.arrive %0, %1;" ::"r"(id), "r"(n) : "memory"); }
__device__ __forceinline__ float ex2(float x) { float y; asm("ex2.approx.ftz.f32 %0, %1;" : "=f"(y) : "f"(x)); return y; }
__device__ __forceinline__ uint32_t pack2(float lo, float hi) { uint32_t r; asm("cvt.rn.bf16x2.f32 %0, %1, %2;" : "=r"(r) : "f"(hi), "f"(lo)); return r; }
__device__ __forceinline__ void stsm_t(uint32_t a, uint32_t r0, uint32_t r1, uint32_t r2, uint32_t r3) {
  asm volatile("stmatrix.sync.aligned.m8n8.x4.trans.shared.b16 [%0], {%1,%2,%3,%4};" ::"r"(a), "r"(r0), "r"(r1), "r"(r2), "r"(r3) : "memory");
}
__device__ __forceinline__ void flag_wait(int& bud, const int* p, int target) {
  while (true) {
    int v;
    asm volatile("ld.acquire.gpu.global.s32 %0, [%1];" : "=r"(v) : "l"(p) : "memory");
    if (v - target >= 0 || --bud <= 0) break;
    __nanosleep(64);
  }
}
__device__ __forceinline__ uint32_t lo_sw(uint32_t addr) { return (addr >> 4) | (1u << 16); }
__device__ __forceinline__ uint32_t lo_o(uint32_t addr) { return (addr >> 4) | (128u << 16); }
__device__ __forceinline__ uint32_t tid_x() { uint32_t t; asm volatile("mov.u32 %0, %tid.x;" : "=r"(t)); return t; }
__device__ __forceinline__ uint32_t opaque(uint32_t x) { uint32_t y; asm volatile("mov.u32 %0, %1;" : "=r"(y) : "r"(x)); return y; }

template <int TA, int TB, uint32_t OA, uint32_t OB>
__device__ __forceinline__ void mma160(float (&d)[80], uint32_t la, uint32_t lb) {
  asm volatile(
      "{\n.reg .pred p;\n.reg .b32 a, b;\n.reg .b64 da, db;\nsetp.eq.b32 p, 0, 0;\n"
      "add.u32 a, %80, %84;\nadd.u32 b, %81, %85;\nmov.b64 da, {a, 0x40000040};\nmov.b64 db, {b, %86};\n"
      "wgmma.mma_async.sync.aligned.m64n160k16.f32.bf16.bf16 {"
      "%0,%1,%2,%3,%4,%5,%6,%7,%8,%9,%10,%11,%12,%13,%14,%15,%16,%17,%18,%19,%20,%21,%22,%23,%24,%25,%26,%27,%28,%29,%30,%31,%32,%33,%34,%35,%36,"
      "%37,%38,%39,%40,%41,%42,%43,%44,%45,%46,%47,%48,%49,%50,%51,%52,%53,%54,%55,%56,%57,%58,%59,%60,%61,%62,%63,%64,%65,%66,%67,%68,%69,%70,%71,"
      "%72,%73,%74,%75,%76,%77,%78,%79"
      "}, da, db, p, 1, 1, %82, %83;\n}\n"
      :
      "+f"(d[0]),"+f"(d[1]),"+f"(d[2]),"+f"(d[3]),"+f"(d[4]),"+f"(d[5]),"+f"(d[6]),"+f"(d[7]),"+f"(d[8]),"+f"(d[9]),"+f"(d[10]),"+f"(d[11]),
      "+f"(d[12]),"+f"(d[13]),"+f"(d[14]),"+f"(d[15]),"+f"(d[16]),"+f"(d[17]),"+f"(d[18]),"+f"(d[19]),"+f"(d[20]),"+f"(d[21]),"+f"(d[22]),
      "+f"(d[23]),"+f"(d[24]),"+f"(d[25]),"+f"(d[26]),"+f"(d[27]),"+f"(d[28]),"+f"(d[29]),"+f"(d[30]),"+f"(d[31]),"+f"(d[32]),"+f"(d[33]),
      "+f"(d[34]),"+f"(d[35]),"+f"(d[36]),"+f"(d[37]),"+f"(d[38]),"+f"(d[39]),"+f"(d[40]),"+f"(d[41]),"+f"(d[42]),"+f"(d[43]),"+f"(d[44]),
      "+f"(d[45]),"+f"(d[46]),"+f"(d[47]),"+f"(d[48]),"+f"(d[49]),"+f"(d[50]),"+f"(d[51]),"+f"(d[52]),"+f"(d[53]),"+f"(d[54]),"+f"(d[55]),
      "+f"(d[56]),"+f"(d[57]),"+f"(d[58]),"+f"(d[59]),"+f"(d[60]),"+f"(d[61]),"+f"(d[62]),"+f"(d[63]),"+f"(d[64]),"+f"(d[65]),"+f"(d[66]),
      "+f"(d[67]),"+f"(d[68]),"+f"(d[69]),"+f"(d[70]),"+f"(d[71]),"+f"(d[72]),"+f"(d[73]),"+f"(d[74]),"+f"(d[75]),"+f"(d[76]),"+f"(d[77]),
      "+f"(d[78]),"+f"(d[79])
      : "r"(la), "r"(lb), "n"(TA), "n"(TB), "n"(OA >> 4), "n"(OB >> 4), "n"(TB ? 0xC0000010u : 0x40000040u));
}

template <int TA, int TB, uint32_t OA, uint32_t OB>
__device__ __forceinline__ void mma160z(float (&d)[80], uint32_t la, uint32_t lb) {
  asm volatile(
      "{\n.reg .pred p;\n.reg .b32 a, b;\n.reg .b64 da, db;\nsetp.ne.b32 p, 0, 0;\n"
      "add.u32 a, %80, %84;\nadd.u32 b, %81, %85;\nmov.b64 da, {a, 0x40000040};\nmov.b64 db, {b, %86};\n"
      "wgmma.mma_async.sync.aligned.m64n160k16.f32.bf16.bf16 {"
      "%0,%1,%2,%3,%4,%5,%6,%7,%8,%9,%10,%11,%12,%13,%14,%15,%16,%17,%18,%19,%20,%21,%22,%23,%24,%25,%26,%27,%28,%29,%30,%31,%32,%33,%34,%35,%36,"
      "%37,%38,%39,%40,%41,%42,%43,%44,%45,%46,%47,%48,%49,%50,%51,%52,%53,%54,%55,%56,%57,%58,%59,%60,%61,%62,%63,%64,%65,%66,%67,%68,%69,%70,%71,"
      "%72,%73,%74,%75,%76,%77,%78,%79"
      "}, da, db, p, 1, 1, %82, %83;\n}\n"
      :
      "=f"(d[0]),"=f"(d[1]),"=f"(d[2]),"=f"(d[3]),"=f"(d[4]),"=f"(d[5]),"=f"(d[6]),"=f"(d[7]),"=f"(d[8]),"=f"(d[9]),"=f"(d[10]),"=f"(d[11]),
      "=f"(d[12]),"=f"(d[13]),"=f"(d[14]),"=f"(d[15]),"=f"(d[16]),"=f"(d[17]),"=f"(d[18]),"=f"(d[19]),"=f"(d[20]),"=f"(d[21]),"=f"(d[22]),
      "=f"(d[23]),"=f"(d[24]),"=f"(d[25]),"=f"(d[26]),"=f"(d[27]),"=f"(d[28]),"=f"(d[29]),"=f"(d[30]),"=f"(d[31]),"=f"(d[32]),"=f"(d[33]),
      "=f"(d[34]),"=f"(d[35]),"=f"(d[36]),"=f"(d[37]),"=f"(d[38]),"=f"(d[39]),"=f"(d[40]),"=f"(d[41]),"=f"(d[42]),"=f"(d[43]),"=f"(d[44]),
      "=f"(d[45]),"=f"(d[46]),"=f"(d[47]),"=f"(d[48]),"=f"(d[49]),"=f"(d[50]),"=f"(d[51]),"=f"(d[52]),"=f"(d[53]),"=f"(d[54]),"=f"(d[55]),
      "=f"(d[56]),"=f"(d[57]),"=f"(d[58]),"=f"(d[59]),"=f"(d[60]),"=f"(d[61]),"=f"(d[62]),"=f"(d[63]),"=f"(d[64]),"=f"(d[65]),"=f"(d[66]),
      "=f"(d[67]),"=f"(d[68]),"=f"(d[69]),"=f"(d[70]),"=f"(d[71]),"=f"(d[72]),"=f"(d[73]),"=f"(d[74]),"=f"(d[75]),"=f"(d[76]),"=f"(d[77]),
      "=f"(d[78]),"=f"(d[79])
      : "r"(la), "r"(lb), "n"(TA), "n"(TB), "n"(OA >> 4), "n"(OB >> 4), "n"(TB ? 0xC0000010u : 0x40000040u));
}

template <int TA, int TB, uint32_t OA, uint32_t OB>
__device__ __forceinline__ void mma80(float (&d)[40], uint32_t la, uint32_t lb) {
  asm volatile(
      "{\n.reg .pred p;\n.reg .b32 a, b;\n.reg .b64 da, db;\nsetp.eq.b32 p, 0, 0;\n"
      "add.u32 a, %40, %44;\nadd.u32 b, %41, %45;\nmov.b64 da, {a, 0x40000040};\nmov.b64 db, {b, %46};\n"
      "wgmma.mma_async.sync.aligned.m64n80k16.f32.bf16.bf16 {"
      "%0,%1,%2,%3,%4,%5,%6,%7,%8,%9,%10,%11,%12,%13,%14,%15,%16,%17,%18,%19,%20,%21,%22,%23,%24,%25,%26,%27,%28,%29,%30,%31,%32,%33,%34,%35,%36,"
      "%37,%38,%39"
      "}, da, db, p, 1, 1, %42, %43;\n}\n"
      :
      "+f"(d[0]),"+f"(d[1]),"+f"(d[2]),"+f"(d[3]),"+f"(d[4]),"+f"(d[5]),"+f"(d[6]),"+f"(d[7]),"+f"(d[8]),"+f"(d[9]),"+f"(d[10]),"+f"(d[11]),
      "+f"(d[12]),"+f"(d[13]),"+f"(d[14]),"+f"(d[15]),"+f"(d[16]),"+f"(d[17]),"+f"(d[18]),"+f"(d[19]),"+f"(d[20]),"+f"(d[21]),"+f"(d[22]),
      "+f"(d[23]),"+f"(d[24]),"+f"(d[25]),"+f"(d[26]),"+f"(d[27]),"+f"(d[28]),"+f"(d[29]),"+f"(d[30]),"+f"(d[31]),"+f"(d[32]),"+f"(d[33]),
      "+f"(d[34]),"+f"(d[35]),"+f"(d[36]),"+f"(d[37]),"+f"(d[38]),"+f"(d[39])
      : "r"(la), "r"(lb), "n"(TA), "n"(TB), "n"(OA >> 4), "n"(OB >> 4), "n"(TB ? 0xC0000010u : 0x40000040u));
}

template <int TA, int TB, uint32_t OA, uint32_t OB>
__device__ __forceinline__ void mma80z(float (&d)[40], uint32_t la, uint32_t lb) {
  asm volatile(
      "{\n.reg .pred p;\n.reg .b32 a, b;\n.reg .b64 da, db;\nsetp.ne.b32 p, 0, 0;\n"
      "add.u32 a, %40, %44;\nadd.u32 b, %41, %45;\nmov.b64 da, {a, 0x40000040};\nmov.b64 db, {b, %46};\n"
      "wgmma.mma_async.sync.aligned.m64n80k16.f32.bf16.bf16 {"
      "%0,%1,%2,%3,%4,%5,%6,%7,%8,%9,%10,%11,%12,%13,%14,%15,%16,%17,%18,%19,%20,%21,%22,%23,%24,%25,%26,%27,%28,%29,%30,%31,%32,%33,%34,%35,%36,"
      "%37,%38,%39"
      "}, da, db, p, 1, 1, %42, %43;\n}\n"
      :
      "=f"(d[0]),"=f"(d[1]),"=f"(d[2]),"=f"(d[3]),"=f"(d[4]),"=f"(d[5]),"=f"(d[6]),"=f"(d[7]),"=f"(d[8]),"=f"(d[9]),"=f"(d[10]),"=f"(d[11]),
      "=f"(d[12]),"=f"(d[13]),"=f"(d[14]),"=f"(d[15]),"=f"(d[16]),"=f"(d[17]),"=f"(d[18]),"=f"(d[19]),"=f"(d[20]),"=f"(d[21]),"=f"(d[22]),
      "=f"(d[23]),"=f"(d[24]),"=f"(d[25]),"=f"(d[26]),"=f"(d[27]),"=f"(d[28]),"=f"(d[29]),"=f"(d[30]),"=f"(d[31]),"=f"(d[32]),"=f"(d[33]),
      "=f"(d[34]),"=f"(d[35]),"=f"(d[36]),"=f"(d[37]),"=f"(d[38]),"=f"(d[39])
      : "r"(la), "r"(lb), "n"(TA), "n"(TB), "n"(OA >> 4), "n"(OB >> 4), "n"(TB ? 0xC0000010u : 0x40000040u));
}

template <int TA, int TB, uint32_t OA, uint32_t OB>
__device__ __forceinline__ void mma128r(float (&d)[64], uint32_t la, uint32_t lb, int sc) {
  asm volatile(
      "{\n.reg .pred p;\n.reg .b32 a, b;\n.reg .b64 da, db;\nsetp.ne.b32 p, %71, 0;\n"
      "add.u32 a, %64, %68;\nadd.u32 b, %65, %69;\nmov.b64 da, {a, 0x40000040};\nmov.b64 db, {b, %70};\n"
      "wgmma.mma_async.sync.aligned.m64n128k16.f32.bf16.bf16 {"
      "%0,%1,%2,%3,%4,%5,%6,%7,%8,%9,%10,%11,%12,%13,%14,%15,%16,%17,%18,%19,%20,%21,%22,%23,%24,%25,%26,%27,%28,%29,%30,%31,%32,%33,%34,%35,%36,"
      "%37,%38,%39,%40,%41,%42,%43,%44,%45,%46,%47,%48,%49,%50,%51,%52,%53,%54,%55,%56,%57,%58,%59,%60,%61,%62,%63"
      "}, da, db, p, 1, 1, %66, %67;\n}\n"
      :
      "+f"(d[0]),"+f"(d[1]),"+f"(d[2]),"+f"(d[3]),"+f"(d[4]),"+f"(d[5]),"+f"(d[6]),"+f"(d[7]),"+f"(d[8]),"+f"(d[9]),"+f"(d[10]),"+f"(d[11]),
      "+f"(d[12]),"+f"(d[13]),"+f"(d[14]),"+f"(d[15]),"+f"(d[16]),"+f"(d[17]),"+f"(d[18]),"+f"(d[19]),"+f"(d[20]),"+f"(d[21]),"+f"(d[22]),
      "+f"(d[23]),"+f"(d[24]),"+f"(d[25]),"+f"(d[26]),"+f"(d[27]),"+f"(d[28]),"+f"(d[29]),"+f"(d[30]),"+f"(d[31]),"+f"(d[32]),"+f"(d[33]),
      "+f"(d[34]),"+f"(d[35]),"+f"(d[36]),"+f"(d[37]),"+f"(d[38]),"+f"(d[39]),"+f"(d[40]),"+f"(d[41]),"+f"(d[42]),"+f"(d[43]),"+f"(d[44]),
      "+f"(d[45]),"+f"(d[46]),"+f"(d[47]),"+f"(d[48]),"+f"(d[49]),"+f"(d[50]),"+f"(d[51]),"+f"(d[52]),"+f"(d[53]),"+f"(d[54]),"+f"(d[55]),
      "+f"(d[56]),"+f"(d[57]),"+f"(d[58]),"+f"(d[59]),"+f"(d[60]),"+f"(d[61]),"+f"(d[62]),"+f"(d[63])
      : "r"(la), "r"(lb), "n"(TA), "n"(TB), "n"(OA >> 4), "n"(OB >> 4), "n"(TB ? 0xC0000010u : 0x40000040u), "r"(sc));
}

template <int TA, int TB, uint32_t OA, uint32_t OB>
__device__ __forceinline__ void mma64r(float (&d)[32], uint32_t la, uint32_t lb, int sc) {
  asm volatile(
      "{\n.reg .pred p;\n.reg .b32 a, b;\n.reg .b64 da, db;\nsetp.ne.b32 p, %39, 0;\n"
      "add.u32 a, %32, %36;\nadd.u32 b, %33, %37;\nmov.b64 da, {a, 0x40000040};\nmov.b64 db, {b, %38};\n"
      "wgmma.mma_async.sync.aligned.m64n64k16.f32.bf16.bf16 {"
      "%0,%1,%2,%3,%4,%5,%6,%7,%8,%9,%10,%11,%12,%13,%14,%15,%16,%17,%18,%19,%20,%21,%22,%23,%24,%25,%26,%27,%28,%29,%30,%31"
      "}, da, db, p, 1, 1, %34, %35;\n}\n"
      :
      "+f"(d[0]),"+f"(d[1]),"+f"(d[2]),"+f"(d[3]),"+f"(d[4]),"+f"(d[5]),"+f"(d[6]),"+f"(d[7]),"+f"(d[8]),"+f"(d[9]),"+f"(d[10]),"+f"(d[11]),
      "+f"(d[12]),"+f"(d[13]),"+f"(d[14]),"+f"(d[15]),"+f"(d[16]),"+f"(d[17]),"+f"(d[18]),"+f"(d[19]),"+f"(d[20]),"+f"(d[21]),"+f"(d[22]),
      "+f"(d[23]),"+f"(d[24]),"+f"(d[25]),"+f"(d[26]),"+f"(d[27]),"+f"(d[28]),"+f"(d[29]),"+f"(d[30]),"+f"(d[31])
      : "r"(la), "r"(lb), "n"(TA), "n"(TB), "n"(OA >> 4), "n"(OB >> 4), "n"(TB ? 0xC0000010u : 0x40000040u), "r"(sc));
}

struct Ring { uint32_t s0, ph0; };
__device__ __forceinline__ void ring_pos(const Ring& r, int i, uint32_t& slot, uint32_t& ph) {
  uint32_t s = opaque(r.s0) + (i % NSLOT);
  uint32_t wrap = s >= NSLOT;
  slot = s - (wrap ? NSLOT : 0);
  ph = r.ph0 ^ ((i / NSLOT) & 1) ^ wrap;
}
__device__ __forceinline__ void ring_advance(Ring& r, int n) {
  uint32_t s, p;
  ring_pos(r, n, s, p);
  r.s0 = s; r.ph0 = p;
}
__host__ __device__ constexpr int idxK(int j) { return j == 0 ? 10 : 9 + 2 * j; }
__host__ __device__ constexpr int idxV(int j) { return j == 7 ? 25 : 12 + 2 * j; }
__host__ __device__ constexpr int xs(int c) { return c % NSLOT; }

struct Sched { int first, second, n, delay; };
__device__ __forceinline__ Sched get_sched(int cta) {
  if (cta < N_OCTA) return Sched{cta, 0, 1, O_DELAY + cta * O_SLOPE};
  const int a = cta - N_OCTA;
  return Sched{cta, cta + N_ATT, a < N_G1 ? 11 : 10, max(0, a - STAG_A0) * STAG_SLOPE + (a < N_G1 ? 0 : G2_EXTRA)};
}
__device__ __forceinline__ int sched_item(const Sched& s, int k) { return k == 0 ? s.first : s.second + (k - 1) * N_ATT; }

template <int W, bool ACC>
__device__ __forceinline__ void mma_main(float (&d)[80], uint32_t aaddr, uint32_t baddr) {
  const uint32_t la = lo_sw(aaddr), lb = lo_sw(baddr);
  if (ACC) mma160<1, 0, W * 16384, 0>(d, la, lb); else mma160z<1, 0, W * 16384, 0>(d, la, lb);
  mma160<1, 0, W * 16384 + 1 * 2048, 1 * 32>(d, la, lb);
  mma160<1, 0, W * 16384 + 2 * 2048, 2 * 32>(d, la, lb);
  mma160<1, 0, W * 16384 + 3 * 2048, 3 * 32>(d, la, lb);
}
template <int W, bool ACC>
__device__ __forceinline__ void mma_mid(float (&d)[40], uint32_t aaddr, uint32_t baddr) {
  const uint32_t la = lo_sw(aaddr), lb = lo_sw(baddr);
  if (ACC) mma80<1, 0, 8192, W * 10240>(d, la, lb); else mma80z<1, 0, 8192, W * 10240>(d, la, lb);
  mma80<1, 0, 8192 + 1 * 2048, W * 10240 + 1 * 32>(d, la, lb);
  mma80<1, 0, 8192 + 2 * 2048, W * 10240 + 2 * 32>(d, la, lb);
  mma80<1, 0, 8192 + 3 * 2048, W * 10240 + 3 * 32>(d, la, lb);
}
template <int W, bool ACC>
__device__ __forceinline__ void mma_both(float (&dm)[80], float (&dh)[40], uint32_t aaddr, uint32_t baddr) {
  mma_mid<W, ACC>(dh, aaddr, baddr);
  mma_main<W, ACC>(dm, aaddr, baddr);
}
template <int KB, bool ACC>
__device__ __forceinline__ void s_mma(float (&sacc)[80], uint32_t kaddr) {
  const uint32_t la = lo_sw(kaddr), lb = lo_sw(SB + OFF_B);
  if (ACC) mma160<0, 0, KB * 8192, KB * B_SLOT>(sacc, la, lb); else mma160z<0, 0, KB * 8192, KB * B_SLOT>(sacc, la, lb);
  mma160<0, 0, KB * 8192 + 32, KB * B_SLOT + 32>(sacc, la, lb);
  mma160<0, 0, KB * 8192 + 64, KB * B_SLOT + 64>(sacc, la, lb);
  mma160<0, 0, KB * 8192 + 96, KB * B_SLOT + 96>(sacc, la, lb);
}
template <int N>
__device__ __forceinline__ void store_scaled(uint32_t addr, const float (&d)[N], float sc) {
#pragma unroll
  for (int J = 0; J < N / 8; J++)
    stsm_t(addr + J * 2048, pack2(d[8 * J] * sc, d[8 * J + 1] * sc), pack2(d[8 * J + 2] * sc, d[8 * J + 3] * sc),
           pack2(d[8 * J + 4] * sc, d[8 * J + 5] * sc), pack2(d[8 * J + 6] * sc, d[8 * J + 7] * sc));
}
__device__ __forceinline__ float4 lds_f4(uint32_t a) {
  float4 v;
  asm volatile("ld.shared.v4.f32 {%0,%1,%2,%3}, [%4];" : "=f"(v.x), "=f"(v.y), "=f"(v.z), "=f"(v.w) : "r"(a) : "memory");
  return v;
}
__device__ __forceinline__ void norm_pack(uint32_t* p, const float* d, const float4& i) {
  p[0] = pack2(d[0] * i.x, d[1] * i.y); p[1] = pack2(d[4] * i.z, d[5] * i.w);
  p[2] = pack2(d[2] * i.x, d[3] * i.y); p[3] = pack2(d[6] * i.z, d[7] * i.w);
  asm volatile("" : "+r"(p[0]), "+r"(p[1]), "+r"(p[2]), "+r"(p[3])::"memory");
}
template <int W>
__device__ __forceinline__ void pack_first(uint32_t (&pk)[60], const float (&om)[80], const float (&oh)[40], uint32_t laddr) {
  float4 n0 = lds_f4(laddr + W * 80), n1 = lds_f4(laddr + W * 80 + 16);
#pragma unroll
  for (int J = 0; J < 5; J++) {
    const float4 i = n0;
    n0 = n1;
    if (J + 2 < 5) n1 = lds_f4(laddr + W * 80 + (J + 2) * 16);
    norm_pack(&pk[20 + 4 * J], &om[8 * (5 * W + J)], i);
    norm_pack(&pk[4 * J], &oh[8 * J], i);
  }
}
template <int W, int J0, int J1>
__device__ __forceinline__ void pack_second(uint32_t (&pk)[60], const float (&om)[80], uint32_t laddr) {
  float4 n[J1 - J0];
#pragma unroll
  for (int J = J0; J < J1; J++) n[J - J0] = lds_f4(laddr + (1 - W) * 80 + J * 16);
#pragma unroll
  for (int J = J0; J < J1; J++) norm_pack(&pk[40 + 4 * J], &om[8 * (5 * (1 - W) + J)], n[J - J0]);
}
__device__ __forceinline__ char* o_ptr(int item) {
  const uint32_t t = tid_x();
  return (char*)g_o + (size_t)(item % ORING) * O_ITEM_BYTES + ((t & 96) * 16 + (t & 28) * 8 + ((((t >> 1) ^ (t >> 4)) & 1) << 4) + (t & 1) * 8);
}
template <int W, int G0, int G1>
__device__ __forceinline__ void store_groups(char* op, const uint32_t (&pk)[60], uint32_t on) {
#pragma unroll
  for (int G = G0; G < G1; G++) {
    const int off = (G < 5 ? 1 : 2 * W) * B_SLOT + (5 * (G < 10 ? W : 1 - W) + G % 5) * 2048;
    asm volatile("{\n.reg .pred p;\nsetp.ne.u32 p, %5, 0;\n@p st.global.v2.b32 [%0], {%1, %2};\n@p st.global.v2.b32 [%0+256], {%3, %4};\n}\n"
                 ::"l"(op + off), "r"(pk[4 * G]), "r"(pk[4 * G + 1]), "r"(pk[4 * G + 2]), "r"(pk[4 * G + 3]), "r"(on) : "memory");
  }
}
__device__ __forceinline__ void publish_generic(uint32_t bar, int lane) {
  __syncwarp();
  mbar_arrive_if0(bar, lane);
}
__device__ __forceinline__ void publish(uint32_t bar, int lane) {
  proxy_fence();
  __syncwarp();
  mbar_arrive_if0(bar, lane);
}

#define A_ADDR(s) (SB + OFF_A + (s) * A_SLOT)
#define B_ADDR(s) (SB + OFF_B + (s) * B_SLOT)
#define WAIT_CHUNK(c, ro, sA)                \
  uint32_t sA;                               \
  {                                          \
    uint32_t pA_;                            \
    ring_pos(ring, (ro) + (c), sA, pA_);     \
    mbar_wait(bud, BAR_FULLA + sA * 8, pA_); \
  }
#define RELEASE_CHUNK(c, sA)                                  \
  mbar_arrive_if0(BAR_EMPTYA + (sA) * 8, tid);                \
  if ((c) < NSLOT) mbar_arrive_if0(BAR_EMPTYB + xs(c) * 8, tid);

template <int W>
__device__ __forceinline__ void attn_consumer(const Sched& sc) {
  int bud = WAIT_BUDGET;
  const int tid = threadIdx.x & 127, lane = tid & 31, warp = tid >> 5;
  const uint32_t st_off = ((lane & 7) + 8 * (lane >> 4)) * 128 + (((2 * warp + ((lane >> 3) & 1)) ^ (lane & 7)) << 4);
  const uint32_t laddr = SB + OFF_L + (lane & 3) * 160;
  float om[80], oh[40], sacc[80];
  uint32_t pk[60];
#pragma unroll
  for (int i = 0; i < 40; i++) pk[i] = 0;
  zero_regs(om);
  Ring ring{0u, 0u};
  uint32_t par = 0;
  const float qscale = 0.07216878364870322f * 1.4426950408889634f;
  constexpr uint32_t pown = B_ADDR(3 + W), poth = B_ADDR(4 - W);
  TL(0); TLG(62);
  {
    WAIT_CHUNK(0, 0, s0)
    wg_fence();
    mma_both<W, false>(sacc, oh, A_ADDR(s0), B_ADDR(xs(0)));
    wg_commit();
    WAIT_CHUNK(1, 0, s1)
    wg_fence();
    mma_both<W, true>(sacc, oh, A_ADDR(s1), B_ADDR(xs(1)));
    wg_commit();
    wg_wait<1>();
    RELEASE_CHUNK(0, s0)
  }
#pragma unroll 1
  for (int it = 0;; it++) {
    char* op = o_ptr(sched_item(sc, max(it - 1, 0)));
#pragma unroll
    for (int c = 2; c < 8; c++) {
      WAIT_CHUNK(c, 0, sA)
      TL(40 + c);
      wg_fence();
      mma_both<W, true>(sacc, oh, A_ADDR(sA), B_ADDR(xs(c)));
      wg_commit();
      wg_wait<1>();
      uint32_t sP, pP;
      ring_pos(ring, c - 1, sP, pP);
      RELEASE_CHUNK(c - 1, sP)
      if (c == 2) { pack_second<W, 0, 1>(pk, om, laddr); store_groups<W, 0, 2>(op, pk, STGON); }
      if (c == 3) { pack_second<W, 1, 2>(pk, om, laddr); store_groups<W, 2, 5>(op, pk, STGON); }
      if (c == 4) { pack_second<W, 2, 3>(pk, om, laddr); store_groups<W, 5, 7>(op, pk, STGON); }
      if (c == 5) { pack_second<W, 3, 4>(pk, om, laddr); store_groups<W, 7, 10>(op, pk, STGON); }
      if (c == 6) { pack_second<W, 4, 5>(pk, om, laddr); store_groups<W, 10, 12>(op, pk, STGON); }
      if (c == 7) store_groups<W, 12, 15>(op, pk, STGON);
      if (c == 7) {
        __syncwarp();
        mbar_arrive_if0(BAR_OFULL, lane | (it == 0));
      }
    }
    uint32_t sK0, pK0, s7, p7;
    ring_pos(ring, idxK(W), sK0, pK0);
    ring_pos(ring, 7, s7, p7);
    if (W == 1) {
      wg_wait<0>();
      RELEASE_CHUNK(7, s7)
      mbar_arrive_if0(BAR_XDONE, tid);
    }
    WAIT_CHUNK(8, 0, s8)
    WAIT_CHUNK(9, 0, s9)
    TL(48);
    if (W == 1) bar_sync(5, 256);
    wg_fence();
    mma_mid<W, true>(oh, A_ADDR(s8), B_ADDR(xs(8)));
    mma_mid<W, true>(oh, A_ADDR(s9), B_ADDR(xs(9)));
    wg_commit();
    mma_main<W, true>(sacc, A_ADDR(s8), B_ADDR(xs(8)));
    mma_main<W, true>(sacc, A_ADDR(s9), B_ADDR(xs(9)));
    wg_commit();
    if (W == 0) bar_arrive(5, 256);
    TL(49);
    wg_wait<1>();
    reg_fence(oh);
    if (W == 0) {
      RELEASE_CHUNK(7, s7)
      mbar_arrive_if0(BAR_XDONE, tid);
    }
    mbar_wait(bud, BAR_XDONE, par);
    store_scaled(B_ADDR(1) + W * 10240 + st_off, oh, qscale);
    publish(BAR_QH, lane);
    if (W == 0) mbar_wait(bud, BAR_FULLA + sK0 * 8, pK0);
    wg_wait<0>();
    reg_fence(sacc);
    TL(1);
    RELEASE_CHUNK(8, s8)
    RELEASE_CHUNK(9, s9)
    store_scaled(B_ADDR(2 * W) + st_off, sacc, qscale);
    publish(BAR_QM + W * 8, lane);
    TL(2);
    uint32_t sK = sK0, sV1 = 0;
    if (W == 0) {
      zero_regs(om); zero_regs(oh);
      reg_fence(om); reg_fence(oh);
      mbar_wait(bud, BAR_QM, par);
      wg_fence();
      s_mma<0, false>(sacc, A_ADDR(sK));
      mbar_wait(bud, BAR_QH, par);
      TL(3);
      wg_fence();
      s_mma<1, true>(sacc, A_ADDR(sK));
      mbar_wait(bud, BAR_QM + 8, par);
      TL(5);
      wg_fence();
      s_mma<2, true>(sacc, A_ADDR(sK));
      wg_commit();
      wg_commit();
      bar_arrive(2, 256);
    } else {
      uint32_t pV1;
      ring_pos(ring, idxV(0), sV1, pV1);
      mbar_wait(bud, BAR_FULLA + sK * 8, pK0);
      bar_sync(2, 256);
      wg_fence();
      s_mma<0, false>(sacc, A_ADDR(sK));
      s_mma<1, true>(sacc, A_ADDR(sK));
      s_mma<2, true>(sacc, A_ADDR(sK));
      wg_commit();
      TL(6);
      mbar_wait(bud, BAR_FULLA + sV1 * 8, pV1);
      mbar_wait(bud, BAR_PFULL, 0);
      TL(7);
      wg_fence();
      mma_both<W, false>(om, oh, A_ADDR(sV1), poth);
      wg_commit();
      bar_arrive(1, 256);
    }
    Ring rv;
    ring_pos(ring, idxV(W), rv.s0, rv.ph0);
#pragma unroll 1
    for (int jj = 0;; jj++) {
      wg_wait<1>();
      reg_fence(sacc);
      TL(8 + jj * 7);
      mbar_arrive2_if0(BAR_EMPTYA + sK * 8, tid);
      mbar_arrive_if0(BAR_EMPTYB + tid * 8, (tid >= 3) | (jj != 3));
#pragma unroll
      for (int J = 0; J < 10; J++) {
        stsm_t(pown + st_off + J * 2048, pack2(ex2(sacc[8 * J]), ex2(sacc[8 * J + 1])), pack2(ex2(sacc[8 * J + 2]), ex2(sacc[8 * J + 3])),
               pack2(ex2(sacc[8 * J + 4]), ex2(sacc[8 * J + 5])), pack2(ex2(sacc[8 * J + 6]), ex2(sacc[8 * J + 7])));
        if (W == 1 && (J == 2 || J == 5)) publish_generic(BAR_PMID + (J / 3) * 8, lane | (jj != 3));
        if (J == 5) {
          wg_wait<0>();
          mbar_arrive_if0(BAR_EMPTYA + sV1 * 8, tid | (W == 0 && jj == 0));
        }
      }
      publish(BAR_PFULL + W * 8, lane);
      TL(10 + jj * 7);
      if (jj == 3) break;
      uint32_t pK, pV1;
      ring_pos(rv, 1, sK, pK);
      ring_pos(rv, 2, sV1, pV1);
      mbar_wait(bud, BAR_FULLA + rv.s0 * 8, rv.ph0);
      bar_sync(1 + W, 256);
      wg_fence();
      mma_both<W, true>(om, oh, A_ADDR(rv.s0), pown);
      wg_commit();
      mbar_wait(bud, BAR_FULLA + sK * 8, pK);
      TL(11 + jj * 7);
      wg_fence();
      s_mma<0, false>(sacc, A_ADDR(sK));
      s_mma<1, true>(sacc, A_ADDR(sK));
      wg_commit();
      wg_wait<1>();
      mbar_arrive_if0(BAR_EMPTYA + rv.s0 * 8, tid);
      wg_fence();
      s_mma<2, true>(sacc, A_ADDR(sK));
      wg_commit();
      TL(13 + jj * 7);
      mbar_wait(bud, BAR_FULLA + sV1 * 8, pV1);
      mbar_wait(bud, BAR_PFREE + W * 8, jj & 1);
      mbar_wait(bud, BAR_PFULL + (1 - W) * 8, (jj + W) & 1);
      TL(14 + jj * 7);
      wg_fence();
      mma_both<W, true>(om, oh, A_ADDR(sV1), poth);
      wg_commit();
      bar_arrive(2 - W, 256);
      ring_advance(rv, 4);
    }
    uint32_t sV7, pV7;
    ring_pos(ring, idxV(7), sV7, pV7);
    if (W == 0) {
      uint32_t sV6, pV6;
      ring_pos(ring, idxV(6), sV6, pV6);
      mbar_wait(bud, BAR_FULLA + sV6 * 8, pV6);
      bar_sync(1, 256);
      wg_fence();
      mma_both<0, true>(om, oh, A_ADDR(sV6), pown);
      wg_commit();
      mbar_wait(bud, BAR_FULLA + sV7 * 8, pV7);
      wg_wait<0>();
      mbar_arrive_if0(BAR_EMPTYA + sV6 * 8, tid);
      mbar_wait(bud, BAR_PFULL + 8, 1);
      wg_fence();
      mma_both<0, true>(om, oh, A_ADDR(sV7), poth);
      wg_commit();
      bar_arrive(6, 256);
    } else {
      mbar_wait(bud, BAR_FULLA + sV7 * 8, pV7);
      bar_sync(6, 256);
    }
    TL(32);
    if (it + 1 == sc.n) {
      if (W == 1) {
        wg_fence();
        mma_both<1, true>(om, oh, A_ADDR(sV7), pown);
        wg_commit();
      }
      wg_wait<0>();
      reg_fence(om); reg_fence(oh);
      TL(33);
      mbar_wait(bud, BAR_LFULL, par);
      TL(34);
      pack_first<W>(pk, om, oh, laddr);
      op = o_ptr(sched_item(sc, it));
      store_groups<W, 0, 10>(op, pk, 1);
      pack_second<W, 0, 5>(pk, om, laddr);
      store_groups<W, 10, 15>(op, pk, 1);
      publish_generic(BAR_OFULL, lane);
      TL(35); TLG(63);
      TL_FLUSH();
      break;
    }
    {
      if (W == 1) {
        wg_fence();
        mma_both<1, true>(om, oh, A_ADDR(sV7), pown);
        wg_commit();
      }
      WAIT_CHUNK(0, 26, s0)
      WAIT_CHUNK(1, 26, s1)
      if (W == 0) {
        wg_wait<0>();
        reg_fence(om); reg_fence(oh);
        TL(33);
        wg_fence();
        mma_main<W, false>(sacc, A_ADDR(s0), B_ADDR(xs(0)));
        wg_commit();
      } else {
        wg_fence();
        mma_main<W, false>(sacc, A_ADDR(s0), B_ADDR(xs(0)));
        mma_main<W, true>(sacc, A_ADDR(s1), B_ADDR(xs(1)));
        wg_commit();
        wg_wait<1>();
        reg_fence(om); reg_fence(oh);
        TL(33);
      }
      mbar_arrive_if0(BAR_EMPTYA + sV7 * 8, tid);
      mbar_wait(bud, BAR_LFULL, par);
      mbar_arrive_if0(BAR_EMPTYB + 24 + tid * 8, tid >= 2);
      TL(34);
      pack_first<W>(pk, om, oh, laddr);
      TL(36);
      wg_fence();
      mma_mid<W, false>(oh, A_ADDR(s0), B_ADDR(xs(0)));
      wg_commit();
      mma_mid<W, true>(oh, A_ADDR(s1), B_ADDR(xs(1)));
      if (W == 0) mma_main<W, true>(sacc, A_ADDR(s1), B_ADDR(xs(1)));
      wg_commit();
      TL(37);
      wg_wait<1>();
      RELEASE_CHUNK(0, s0)
      TL(35); TLG(63);
    }
    TL_FLUSH();
    TL(0); TLG(62);
    ring_advance(ring, 26);
    par ^= 1;
  }
}

__device__ __forceinline__ uint4 lds128(uint32_t a) {
  uint4 v;
  asm volatile("ld.shared.v4.b32 {%0,%1,%2,%3}, [%4];" : "=r"(v.x), "=r"(v.y), "=r"(v.z), "=r"(v.w) : "r"(a) : "memory");
  return v;
}
__device__ __forceinline__ void acc2(float& s, float& t, uint32_t w) {
  s += __uint_as_float(w << 16);
  t += __uint_as_float(w & 0xffff0000u);
}
__device__ __forceinline__ uint32_t badd2(uint32_t a, uint32_t b) { uint32_t r; asm("add.rn.bf16x2 %0, %1, %2;" : "=r"(r) : "r"(a), "r"(b)); return r; }
__device__ __forceinline__ void sum_unit(float& acc, uint32_t pb) {
  const uint4 v0 = lds128(pb), v1 = lds128(pb ^ 32), v2 = lds128(pb ^ 64), v3 = lds128(pb ^ 96);
  const uint32_t w0 = badd2(v0.x, v0.y), w1 = badd2(v0.z, v0.w);
  float s0 = acc + __uint_as_float(w0 << 16), t0 = __uint_as_float(w0 & 0xffff0000u);
  float s1 = __uint_as_float(w1 << 16), t1 = __uint_as_float(w1 & 0xffff0000u);
  acc2(s0, t0, badd2(v1.x, v1.y)); acc2(s1, t1, badd2(v1.z, v1.w));
  acc2(s0, t0, badd2(v2.x, v2.y)); acc2(s1, t1, badd2(v2.z, v2.w));
  acc2(s0, t0, badd2(v3.x, v3.y)); acc2(s1, t1, badd2(v3.z, v3.w));
  acc = (s0 + t0) + (s1 + t1);
}
__device__ __forceinline__ float bf_lo(uint32_t w) { return __uint_as_float(w << 16); }
__device__ __forceinline__ float bf_hi(uint32_t w) { return __uint_as_float(w & 0xffff0000u); }
__device__ __forceinline__ float bf_rn(float x) { return __bfloat162float(__float2bfloat16(x)); }
__device__ __forceinline__ void slow_item(const Params& p, int item, int hw) {
  const int blk = item >> 9, h = (item >> 4) & 31, b = item & 15;
#pragma unroll 1
  for (int n = hw; n < SQ; n += 3) {
    float q[6] = {0.f, 0.f, 0.f, 0.f, 0.f, 0.f};
    {
      const uint32_t* xr = (const uint32_t*)(p.xp[blk] + (size_t)(b * SQ + n) * DM);
      const uint32_t* wq = (const uint32_t*)(p.wqp[blk] + h * DH) + (tid_x() & 31);
#pragma unroll 2
      for (int k = 0; k < DM / 2; k++) {
        const uint32_t xv = xr[k];
#pragma unroll
        for (int i = 0; i < 3; i++) {
          const uint32_t w0 = wq[i * 32], w1 = wq[NH * DH / 2 + i * 32];
          q[2 * i] = fmaf(bf_lo(xv), bf_lo(w0), fmaf(bf_hi(xv), bf_lo(w1), q[2 * i]));
          q[2 * i + 1] = fmaf(bf_lo(xv), bf_hi(w0), fmaf(bf_hi(xv), bf_hi(w1), q[2 * i + 1]));
        }
        wq += NH * DH;
      }
    }
    const uint32_t q0 = pack2(q[0], q[1]), q1 = pack2(q[2], q[3]), q2 = pack2(q[4], q[5]);
    float o[6] = {0.f, 0.f, 0.f, 0.f, 0.f, 0.f}, m = -INFINITY, l = 0.f;
    const uint32_t* kg = (const uint32_t*)(p.kp[blk] + (size_t)(b * NH + h) * SK * DH) + (tid_x() & 31);
    const uint32_t* vg = (const uint32_t*)(p.vp[blk] + (size_t)(b * NH + h) * SK * DH) + (tid_x() & 31);
#pragma unroll 1
    for (int k = 0; k < SK; k++) {
      const uint32_t k0 = kg[0], k1 = kg[32], k2 = kg[64], v0 = vg[0], v1 = vg[32], v2 = vg[64];
      kg += DH / 2; vg += DH / 2;
      float sc = fmaf(bf_lo(q0), bf_lo(k0), bf_hi(q0) * bf_hi(k0));
      sc = fmaf(bf_lo(q1), bf_lo(k1), fmaf(bf_hi(q1), bf_hi(k1), sc));
      sc = fmaf(bf_lo(q2), bf_lo(k2), fmaf(bf_hi(q2), bf_hi(k2), sc));
#pragma unroll
      for (int d = 16; d; d >>= 1) sc += __shfl_xor_sync(0xffffffffu, sc, d);
      sc = bf_rn(bf_rn(sc) * 0.07216878364870322f);
      const float mn = fmaxf(m, sc), a = ex2((m - mn) * 1.4426950408889634f), pr = ex2((sc - mn) * 1.4426950408889634f);
      m = mn;
      l = fmaf(l, a, pr);
      o[0] = fmaf(o[0], a, pr * bf_lo(v0)); o[1] = fmaf(o[1], a, pr * bf_hi(v0));
      o[2] = fmaf(o[2], a, pr * bf_lo(v1)); o[3] = fmaf(o[3], a, pr * bf_hi(v1));
      o[4] = fmaf(o[4], a, pr * bf_lo(v2)); o[5] = fmaf(o[5], a, pr * bf_hi(v2));
    }
    float inv;
    asm("rcp.approx.ftz.f32 %0, %1;" : "=f"(inv) : "f"(l));
    const int lane = tid_x() & 31;
    const int r = n & 15, c = 4 * ((r & 7) >> 1) + 2 * (r >> 3) + (r & 1);
    char* on = (char*)g_o + (size_t)(item % ORING) * O_ITEM_BYTES + (lane >> 2) * 256 + (lane & 3) * 64 + (n >> 4) * 2048 +
               (((c >> 3) ^ ((lane >> 1) & 1)) << 4) + (c & 7) * 2;
#pragma unroll
    for (int i = 0; i < 3; i++) {
      *(__nv_bfloat16*)(on + i * B_SLOT) = __float2bfloat16(o[2 * i] * inv);
      *(__nv_bfloat16*)(on + i * B_SLOT + 32) = __float2bfloat16(o[2 * i + 1] * inv);
    }
  }
}
__device__ __forceinline__ void attn_helper(const Params& p, int hw, const Sched& sc, int epoch) {
  int bud = WAIT_BUDGET;
#pragma unroll 1
  for (int it = 0; it < sc.n; it++) {
    const int item = sched_item(sc, it);
    const uint32_t par = it & 1;
    int lane = tid_x() & 31;
    const int r = lane >> 1;
    const uint32_t a0 = B_ADDR(3) + (16 * hw + r) * 128 + (lane & 1) * 16 + ((r & 3) << 5);
    float acc[4] = {0.f, 0.f, 0.f, 0.f};
#pragma unroll 1
    for (int j = 0; j < 8; j++) {
      const uint32_t pb = a0 + (j & 1) * B_SLOT, bfull = BAR_PFULL + (j & 1) * 8, pfull = (j >> 1) & 1;
      mbar_wait(bud, j == 7 ? BAR_PMID : bfull, j == 7 ? par : pfull);
      sum_unit(acc[0], pb);
      if (j == 7) mbar_wait(bud, BAR_PMID + 8, par);
      sum_unit(acc[1], pb + 6144);
      if (j == 7) mbar_wait(bud, bfull, pfull);
      sum_unit(acc[2], pb + 2 * 6144);
      if (hw == 0) sum_unit(acc[3], pb + 3 * 6144);
      __syncwarp();
      mbar_arrive_if0(BAR_PFREE + (j & 1) * 8, lane);
      if (j == DONE_J && hw == 2 && item >= ORING) flag_wait(bud, &g_done[(item - ORING) >> 4], (epoch + 1) * N_OCTA);
    }
    bool bad = false;
    const uint32_t la = SB + OFF_L + (((r & 7) >> 1) * 40 + 2 * (r >> 3) + (r & 1) + 4 * hw) * 4;
#pragma unroll
    for (int u = 0; u < 4; u++) {
      const float l = acc[u] + __shfl_xor_sync(0xffffffffu, acc[u], 1);
      if (u < 3 || hw == 0) {
        bad |= !(l >= 8.8817841970012523e-16f && l <= 1.125899906842624e15f);
        float inv;
        asm("rcp.approx.ftz.f32 %0, %1;" : "=f"(inv) : "f"(l));
        asm volatile("st.shared.f32 [%0], %1;" ::"r"(la + u * 48), "f"(inv) : "memory");
      }
    }
    publish_generic(BAR_LFULL, lane);
    if (lane == 0) TLP(40 + hw * 4);
    uint32_t anybad;
    asm volatile("{\n.reg .pred p, q;\nsetp.ne.u32 p, %1, 0;\nbarrier.red.or.pred q, 7, 96, p;\nselp.u32 %0, 1, 0, q;\n}\n"
                 : "=r"(anybad) : "r"((uint32_t)bad) : "memory");
    if (__any_sync(0xffffffffu, anybad)) {
      mbar_wait(bud, BAR_OFULL, par);
      slow_item(p, item, hw);
      bar_sync(7, 96);
    }
    if (hw == 1) {
      mbar_wait(bud, BAR_OFULL, par);
      if ((tid_x() & 31) == 0) {
        TLP(41 + hw * 4);
        asm volatile("red.release.gpu.global.add.s32 [%0], 1;" ::"l"(&g_ready[item]) : "memory");
        TLP(42 + hw * 4);
      }
      __syncwarp();
    }
  }
}

__device__ __forceinline__ void attn_producer(const Params& p, const Sched& sc) {
  int bud = WAIT_BUDGET;
  uint32_t sa = 0, pa = 1;
  uint64_t pol;
  asm volatile("createpolicy.fractional.L2::evict_first.b64 %0, 1.0;" : "=l"(pol));
  if (sc.delay) {
    const long long t0 = clock64();
    while (clock64() - t0 < sc.delay) __nanosleep(100);
  }
#pragma unroll 1
  for (int it = 0; it < sc.n; it++) {
    const int item = sched_item(sc, it);
    const int blk = item >> 9, h = (item >> 4) & 31, b = item & 15;
    const int row0 = (b * NH + h) * SK;
#pragma unroll
    for (int c = 0; c < 10; c++) {
      mbar_wait(bud, BAR_EMPTYA + sa * 8, pa);
      TLP(c);
      mbar_expect(BAR_FULLA + sa * 8, A_SLOT + B_SLOT);
      tma3d(A_ADDR(sa), &p.wq[blk], BAR_FULLA + sa * 8, 0, c * 64, h * 3);
      mbar_wait(bud, BAR_EMPTYB + xs(c) * 8, c < NSLOT);
      TLP(10 + c);
      tma2d(B_ADDR(xs(c)), &p.x[blk], BAR_FULLA + sa * 8, c * 64, b * SQ);
      if (++sa == NSLOT) { sa = 0; pa ^= 1; }
    }
#pragma unroll
    for (int i = 0; i < 16; i++) {
      const bool isK = (i == 0) || ((i & 1) && i < 15);
      const int j = i == 0 ? 0 : (i == 15 ? 7 : (isK ? (i + 1) >> 1 : (i - 2) >> 1));
      mbar_wait(bud, BAR_EMPTYA + sa * 8, pa);
      TLP(20 + i);
      mbar_expect(BAR_FULLA + sa * 8, A_SLOT);
      tma3d_hint(A_ADDR(sa), isK ? &p.k[blk] : &p.v[blk], BAR_FULLA + sa * 8, 0, row0 + j * 64, 0, pol);
      if (++sa == NSLOT) { sa = 0; pa ^= 1; }
    }
  }
}

template <int W>
__device__ __forceinline__ void oproj_consumer() {
  int bud = WAIT_BUDGET;
  const int tid = threadIdx.x & 127, lane = tid & 31, warp = tid >> 5;
  const int qrow = 8 * ((lane >> 1) & 1) + 4 * (lane >> 4) + 2 * ((lane >> 2) & 1) + (lane & 1);
  const uint32_t st_off = qrow * 128 + (((2 * warp + ((lane >> 3) & 1)) ^ (qrow & 7)) << 4);
  float a0[64], a1[64], ah[32];
  zero_regs(a0); zero_regs(a1); zero_regs(ah);
#pragma unroll 1
  for (int blk = 0; blk < 2; blk++) {
    int c3 = 0, step = blk * NH;
#pragma unroll 1
    for (int c = 0; c < 96; c++) {
      const uint32_t st = c & 3;
      mbar_wait(bud, BAR_GFULL + st * 8, (c >> 2) & 1);
      wg_fence();
      const uint32_t la = lo_sw(SB + st * O_STAGE), lb = lo_o(SB + st * O_STAGE + O_AB);
#define O_STEP(ks, sc)                                                   \
  mma64r<1, 1, 2 * 8192 + ks * 2048, W * 8192 + ks * 512>(ah, la, lb, sc);    \
  mma128r<1, 1, (W * 3) * 8192 + ks * 2048, ks * 512>(a0, la, lb, sc);        \
  mma128r<1, 1, (W * 3 + 1) * 8192 + ks * 2048, ks * 512>(a1, la, lb, sc);
      O_STEP(0, c != 0) O_STEP(1, 1) O_STEP(2, 1) O_STEP(3, 1)
#undef O_STEP
      wg_commit();
      if (++c3 == 3) {
        c3 = 0;
        if (W == 0)
          asm volatile("{\n.reg .pred p;\nsetp.eq.u32 p, %1, 0;\n@p red.relaxed.gpu.global.add.s32 [%0], 1;\n}\n" ::"l"(&g_done[step]), "r"(tid) : "memory");
        TL(step);
        step++;
      }
      wg_wait<1>();
      mbar_arrive_if0(BAR_GEMPTY + ((c - 1) & 3) * 8, tid | (c == 0) | (c == 95));
    }
    wg_wait<0>();
    reg_fence(a0); reg_fence(a1); reg_fence(ah);
    bar_sync(3, 256);
    const uint32_t sg = SB + 2 * O_STAGE + st_off;
    store_scaled(sg + 2 * 16384 + W * 8192, ah, 1.0f);
    store_scaled(sg + (W * 3) * 16384, a0, 1.0f);
    store_scaled(sg + (W * 3 + 1) * 16384, a1, 1.0f);
    publish(BAR_GOUT, lane);
  }
  TL_FLUSH();
}

__device__ __forceinline__ void oproj_producer(const Params& p, int cta, int epoch) {
  int bud = WAIT_BUDGET;
  const int half = cta & 1, r0 = (cta >> 1) * 128;
  const int b0 = r0 / SQ, off0 = r0 - b0 * SQ, n0 = min(128, SQ - off0), n1 = 128 - n0;
  const int target = epoch + 1;
#pragma unroll 1
  for (int step = 0; step < 2 * NH; step++) {
    const int blk = step >> 5, item0 = step * 16 + b0;
    const char* o0 = (const char*)g_o + (size_t)(item0 % ORING) * O_ITEM_BYTES + off0 * 128;
    const char* o1 = (const char*)g_o + (size_t)((item0 + 1) % ORING) * O_ITEM_BYTES;
#pragma unroll 1
    for (int kb = 0; kb < 3; kb++) {
      const int c = step * 3 + kb;
      const uint32_t st = c & 3, dst = SB + st * O_STAGE, bar = BAR_GFULL + st * 8;
      mbar_wait(bud, BAR_GEMPTY + st * 8, ((c >> 2) & 1) ^ 1);
      mbar_expect(bar, O_STAGE);
      tma3d(dst, &p.wo[blk], bar, 0, ((step & 31) * 3 + kb) * 64, half * 5);
      if (kb == 0) {
        flag_wait(bud, &g_ready[item0], target);
        if (n1) flag_wait(bud, &g_ready[item0 + 1], target);
        asm volatile("fence.proxy.async.global;" ::: "memory");
      }
      bulk_load(dst + O_AB, o0 + kb * B_SLOT, n0 * 128, bar);
      if (n1) bulk_load(dst + O_AB + n0 * 128, o1 + kb * B_SLOT, n1 * 128, bar);
    }
  }
}

__device__ __forceinline__ void oproj_storer(const Params& p, int cta) {
  int bud = WAIT_BUDGET;
  const int half = cta & 1, r0 = (cta >> 1) * 128;
#pragma unroll 1
  for (int blk = 0; blk < 2; blk++) {
    mbar_wait(bud, BAR_GOUT, blk);
    for (int k = 0; k < 5; k++) tma_store2d(&p.out, SB + 2 * O_STAGE + k * 16384, blk * DM + half * 320 + k * 64, r0);
    asm volatile("cp.async.bulk.commit_group;" ::: "memory");
    asm volatile("cp.async.bulk.wait_group.read 0;" ::: "memory");
    mbar_arrive2_if0(BAR_GEMPTY + 16, 0);
    mbar_arrive2_if0(BAR_GEMPTY + 24, 0);
  }
  asm volatile("cp.async.bulk.wait_group 0;" ::: "memory");
}

__global__ void __launch_bounds__(384, 1) fused_kernel(const __grid_constant__ Params p) {
  extern __shared__ __align__(1024) char smem_raw[];
  if ((smem_u32(smem_raw) & 0xFFFFFFu) != SB) return;
  const int cta = blockIdx.x;
  const int epoch = __shfl_sync(0xffffffffu, g_epoch[cta], 0);
  if (threadIdx.x == 0) {
    for (int i = 0; i < NSLOT; i++) {
      mbar_init(BAR_FULLA + i * 8, 1); mbar_init(BAR_EMPTYA + i * 8, 2);
      mbar_init(BAR_EMPTYB + i * 8, 2);
    }
    mbar_init(BAR_XDONE, 2); mbar_init(BAR_QH, 8); mbar_init(BAR_QM, 4); mbar_init(BAR_QM + 8, 4);
    mbar_init(BAR_PFULL, 4); mbar_init(BAR_PFULL + 8, 4);
    mbar_init(BAR_PFREE, 3); mbar_init(BAR_PFREE + 8, 3);
    mbar_init(BAR_LFULL, 3); mbar_init(BAR_PMID, 4); mbar_init(BAR_PMID + 8, 4);
    mbar_init(BAR_OFULL, 8);
    for (int i = 0; i < O_NST; i++) { mbar_init(BAR_GFULL + i * 8, 1); mbar_init(BAR_GEMPTY + i * 8, 2); }
    mbar_init(BAR_GOUT, 8);
    asm volatile("fence.mbarrier_init.release.cluster;" ::: "memory");
    proxy_fence();
  }
  __syncthreads();
  if (threadIdx.x == 0) g_epoch[cta] = epoch + 1;
  const int warp = __shfl_sync(0xffffffffu, threadIdx.x >> 5, 0);
  const Sched sc = get_sched(cta);
  if (warp >= 8) {
    asm volatile("setmaxnreg.dec.sync.aligned.u32 40;");
    if (warp == 8) {
      if (elect_one()) attn_producer(p, sc);
      __syncwarp();
    } else {
      attn_helper(p, warp - 9, sc, epoch);
    }
    if (cta < N_OCTA) {
      bar_sync(4, 128);
      if (warp == 8) {
        if (elect_one()) oproj_producer(p, cta, epoch);
      } else if (warp == 9) {
        if (elect_one()) oproj_storer(p, cta);
      }
    }
  } else {
    asm volatile("setmaxnreg.inc.sync.aligned.u32 232;");
    if (warp < 4) {
      attn_consumer<0>(sc);
      if (cta < N_OCTA) oproj_consumer<0>();
    } else {
      attn_consumer<1>(sc);
      if (cta < N_OCTA) oproj_consumer<1>();
    }
  }
}

typedef CUresult (*EncodeFn)(CUtensorMap*, CUtensorMapDataType, cuuint32_t, void*, const cuuint64_t*, const cuuint64_t*, const cuuint32_t*,
                             const cuuint32_t*, CUtensorMapInterleave, CUtensorMapSwizzle, CUtensorMapL2promotion, CUtensorMapFloatOOBfill);

void make3d(EncodeFn enc, CUtensorMap* m, const void* ptr, uint64_t rows, uint64_t cols, uint32_t box_rows, uint32_t box_blocks,
            CUtensorMapL2promotion promo = CU_TENSOR_MAP_L2_PROMOTION_L2_128B) {
  cuuint64_t gd[3] = {64, rows, cols / 64};
  cuuint64_t gs[2] = {cols * 2, 128};
  cuuint32_t bd[3] = {64, box_rows, box_blocks}, es[3] = {1, 1, 1};
  enc(m, CU_TENSOR_MAP_DATA_TYPE_BFLOAT16, 3, (void*)ptr, gd, gs, bd, es, CU_TENSOR_MAP_INTERLEAVE_NONE, CU_TENSOR_MAP_SWIZZLE_128B,
      promo, CU_TENSOR_MAP_FLOAT_OOB_FILL_NONE);
}
void make2d(EncodeFn enc, CUtensorMap* m, const void* ptr, uint64_t rows, uint64_t cols, uint32_t box_rows) {
  cuuint64_t gd[2] = {cols, rows};
  cuuint64_t gs[1] = {cols * 2};
  cuuint32_t bd[2] = {64, box_rows}, es[2] = {1, 1};
  enc(m, CU_TENSOR_MAP_DATA_TYPE_BFLOAT16, 2, (void*)ptr, gd, gs, bd, es, CU_TENSOR_MAP_INTERLEAVE_NONE, CU_TENSOR_MAP_SWIZZLE_128B,
      CU_TENSOR_MAP_L2_PROMOTION_L2_128B, CU_TENSOR_MAP_FLOAT_OOB_FILL_NONE);
}

}

extern "C" void kernel_launch(void* const* d_in, const int* in_sizes, int n_in, void* d_out, int out_size) {
  static EncodeFn enc = nullptr;
  if (!enc) {
    cudaDriverEntryPointQueryResult qr;
    cudaGetDriverEntryPoint("cuTensorMapEncodeTiled", (void**)&enc, cudaEnableDefault, &qr);
    cudaFuncSetAttribute(fused_kernel, cudaFuncAttributeMaxDynamicSharedMemorySize, SMEM_BYTES);
  }
  Params p;
  for (int s = 0; s < 2; s++) {
    make2d(enc, &p.x[s], d_in[5 * s + 0], NB * SQ, DM, SQ);
    make3d(enc, &p.k[s], d_in[5 * s + 1], (uint64_t)NB * NH * SK, DH, 64, 3);
    make3d(enc, &p.v[s], d_in[5 * s + 2], (uint64_t)NB * NH * SK, DH, 64, 3);
    make3d(enc, &p.wq[s], d_in[5 * s + 3], DM, NH * DH, 64, 3);
    make3d(enc, &p.wo[s], d_in[5 * s + 4], NH * DH, DM, 64, 5);
    p.xp[s] = (const __nv_bfloat16*)d_in[5 * s + 0];
    p.wqp[s] = (const __nv_bfloat16*)d_in[5 * s + 3];
    p.kp[s] = (const __nv_bfloat16*)d_in[5 * s + 1];
    p.vp[s] = (const __nv_bfloat16*)d_in[5 * s + 2];
  }
  make2d(enc, &p.out, d_out, NB * SQ, 2 * DM, 128);
  fused_kernel<<<NCTA, 384, SMEM_BYTES>>>(p);
}
```

```cpp
#include <cuda_runtime.h>
#include <cuda_bf16.h>
#include <cuda.h>
#include <stdint.h>

#define DEBUG_TIMEOUT 0

namespace {

constexpr int SQ = 160, DM = 640, NH = 32, SK = 512, DH = 192, NB = 16;
constexpr int NITEMS = 2 * NB * NH;
constexpr int NCTA = 132, N_OCTA = 40, N_G2 = 28, N_G1 = 64, N_ATT = N_G1 + N_G2;
constexpr int ORING = 112, STAG_A0 = 15, STAG_SLOPE = 240, O_DELAY = 0, O_SLOPE = 0, G2_EXTRA = 0, DONE_J = 5;
constexpr int ORING_MAX = ORING;
#define W1_NG 3
#define PF_MODE 1
constexpr int A_SLOT = 24576, B_SLOT = 20480, NSLOT = 5;
constexpr int OFF_A = 0;
constexpr int OFF_B = NSLOT * A_SLOT;
constexpr int O_STAGE = 57344, O_AB = 40960, O_NST = 4;
constexpr int OFF_L = O_NST * O_STAGE;
constexpr int OFF_BAR = OFF_L + 160 * 4;
constexpr int SMEM_BYTES = OFF_BAR + 384 + 512;
static_assert(OFF_B + NSLOT * B_SLOT <= OFF_L, "smem layout");
constexpr uint32_t SB = 1024;
constexpr uint32_t BARS = SB + OFF_BAR;
constexpr uint32_t BAR_FULLA = BARS, BAR_EMPTYA = BARS + 40, BAR_PMID = BARS + 80, BAR_EMPTYB = BARS + 120, BAR_XDONE = BARS + 160,
                   BAR_QH = BARS + 168, BAR_QM = BARS + 96, BAR_PFULL = BARS + 184, BAR_PFREE = BARS + 200, BAR_LFULL = BARS + 216,
                   BAR_OFULL = BARS + 224, BAR_GFULL = BARS + 248, BAR_GEMPTY = BARS + 280, BAR_GOUT = BARS + 312;
constexpr int O_ITEM_BYTES = SQ * DH * 2;

struct alignas(64) Params {
  CUtensorMap x[2], wq[2], k[2], v[2], wo[2], out;
  const __nv_bfloat16 *xp[2], *wqp[2], *kp[2], *vp[2];
};

__device__ uint4 g_o[(size_t)ORING_MAX * O_ITEM_BYTES / 16];
__device__ int g_ready[NITEMS];
__device__ int g_done[2 * NH];
__device__ int g_epoch[NCTA];

#define TLP(id)
#define TLG(id)
#define TL(id)
#define TL_FLUSH()
__device__ __forceinline__ uint32_t smem_u32(const void* p) { return (uint32_t)__cvta_generic_to_shared(p); }
__device__ __forceinline__ void wg_fence() { asm volatile("wgmma.fence.sync.aligned;" ::: "memory"); }
__device__ __forceinline__ void wg_commit() { asm volatile("wgmma.commit_group.sync.aligned;" ::: "memory"); }
template <int N> __device__ __forceinline__ void wg_wait() { asm volatile("wgmma.wait_group.sync.aligned %0;" ::"n"(N) : "memory"); }
template <int N> __device__ __forceinline__ void reg_fence(float (&d)[N]) {
#pragma unroll
  for (int i = 0; i < N; i++) asm volatile("" : "+f"(d[i])::"memory");
}
template <int N> __device__ __forceinline__ void zero_regs(float (&d)[N]) {
#pragma unroll
  for (int i = 0; i < N; i++) d[i] = 0.f;
}
__device__ __forceinline__ void proxy_fence() { asm volatile("fence.proxy.async.shared::cta;" ::: "memory"); }
__device__ __forceinline__ void mbar_init(uint32_t bar, int cnt) { asm volatile("mbarrier.init.shared::cta.b64 [%0], %1;" ::"r"(bar), "r"(cnt) : "memory"); }
__device__ __forceinline__ void mbar_arrive_if0(uint32_t bar, uint32_t sel) {
  asm volatile("{\n.reg .pred p;\nsetp.eq.u32 p, %1, 0;\n@p mbarrier.arrive.shared::cta.b64 _, [%0];\n}\n" ::"r"(bar), "r"(sel) : "memory");
}
__device__ __forceinline__ void mbar_arrive2_if0(uint32_t bar, uint32_t sel) {
  asm volatile("{\n.reg .pred p;\nsetp.eq.u32 p, %1, 0;\n@p mbarrier.arrive.shared::cta.b64 _, [%0], 2;\n}\n" ::"r"(bar), "r"(sel) : "memory");
}
__device__ __forceinline__ void mbar_expect(uint32_t bar, uint32_t bytes) {
  asm volatile("mbarrier.arrive.expect_tx.shared::cta.b64 _, [%0], %1;" ::"r"(bar), "r"(bytes) : "memory");
}
__device__ __forceinline__ void mbar_wait(int& bud, uint32_t bar, uint32_t parity) {
  asm volatile(
      "{\n.reg .pred p;\n"
      "LW:\n"
      "mbarrier.try_wait.parity.shared::cta.b64 p, [%0], %1;\n"
      "@!p bra LW;\n}\n" ::"r"(bar), "r"(parity) : "memory");
}
constexpr int WAIT_BUDGET = 1 << 22;
__device__ __forceinline__ bool elect_one() {
  uint32_t p;
  asm volatile("{\n.reg .pred p;\nelect.sync _|p, 0xffffffff;\nselp.u32 %0, 1, 0, p;\n}\n" : "=r"(p));
  return p;
}
__device__ __forceinline__ void tma2d(uint32_t dst, const CUtensorMap* m, uint32_t bar, int c0, int c1) {
  asm volatile("cp.async.bulk.tensor.2d.shared::cluster.global.mbarrier::complete_tx::bytes [%0], [%1, {%3, %4}], [%2];"
               ::"r"(dst), "l"(m), "r"(bar), "r"(c0), "r"(c1) : "memory");
}
__device__ __forceinline__ void tma3d(uint32_t dst, const CUtensorMap* m, uint32_t bar, int c0, int c1, int c2) {
  asm volatile("cp.async.bulk.tensor.3d.shared::cluster.global.mbarrier::complete_tx::bytes [%0], [%1, {%3, %4, %5}], [%2];"
               ::"r"(dst), "l"(m), "r"(bar), "r"(c0), "r"(c1), "r"(c2) : "memory");
}
__device__ __forceinline__ void tma3d_hint(uint32_t dst, const CUtensorMap* m, uint32_t bar, int c0, int c1, int c2, uint64_t pol) {
  asm volatile("cp.async.bulk.tensor.3d.shared::cluster.global.mbarrier::complete_tx::bytes.L2::cache_hint [%0], [%1, {%3, %4, %5}], [%2], %6;"
               ::"r"(dst), "l"(m), "r"(bar), "r"(c0), "r"(c1), "r"(c2), "l"(pol) : "memory");
}
__device__ __forceinline__ void bulk_load(uint32_t dst, const void* src, uint32_t bytes, uint32_t bar) {
  asm volatile("cp.async.bulk.shared::cluster.global.mbarrier::complete_tx::bytes [%0], [%1], %2, [%3];"
               ::"r"(dst), "l"(src), "r"(bytes), "r"(bar) : "memory");
}
__device__ __forceinline__ void tma_store2d(const CUtensorMap* m, uint32_t src, int c0, int c1) {
  asm volatile("cp.async.bulk.tensor.2d.global.shared::cta.bulk_group [%0, {%2, %3}], [%1];" ::"l"(m), "r"(src), "r"(c0), "r"(c1) : "memory");
}
__device__ __forceinline__ void bar_sync(int id, int n) { asm volatile("bar.sync %0, %1;" ::"r"(id), "r"(n) : "memory"); }
__device__ __forceinline__ void bar_arrive(int id, int n) { asm volatile("bar.arrive %0, %1;" ::"r"(id), "r"(n) : "memory"); }
__device__ __forceinline__ float ex2(float x) { float y; asm("ex2.approx.ftz.f32 %0, %1;" : "=f"(y) : "f"(x)); return y; }
__device__ __forceinline__ uint32_t pack2(float lo, float hi) { uint32_t r; asm("cvt.rn.bf16x2.f32 %0, %1, %2;" : "=r"(r) : "f"(hi), "f"(lo)); return r; }
__device__ __forceinline__ void stsm_t(uint32_t a, uint32_t r0, uint32_t r1, uint32_t r2, uint32_t r3) {
  asm volatile("stmatrix.sync.aligned.m8n8.x4.trans.shared.b16 [%0], {%1,%2,%3,%4};" ::"r"(a), "r"(r0), "r"(r1), "r"(r2), "r"(r3) : "memory");
}
__device__ __forceinline__ void flag_wait(int& bud, const int* p, int target) {
  while (true) {
    int v;
    asm volatile("ld.acquire.gpu.global.s32 %0, [%1];" : "=r"(v) : "l"(p) : "memory");
    if (v - target >= 0 || --bud <= 0) break;
    __nanosleep(64);
  }
}
__device__ __forceinline__ uint32_t lo_sw(uint32_t addr) { return (addr >> 4) | (1u << 16); }
__device__ __forceinline__ uint32_t lo_o(uint32_t addr) { return (addr >> 4) | (128u << 16); }
__device__ __forceinline__ uint32_t tid_x() { uint32_t t; asm volatile("mov.u32 %0, %tid.x;" : "=r"(t)); return t; }
__device__ __forceinline__ uint32_t opaque(uint32_t x) { uint32_t y; asm volatile("mov.u32 %0, %1;" : "=r"(y) : "r"(x)); return y; }

template <int TA, int TB, uint32_t OA, uint32_t OB>
__device__ __forceinline__ void mma160(float (&d)[80], uint32_t la, uint32_t lb) {
  asm volatile(
      "{\n.reg .pred p;\n.reg .b32 a, b;\n.reg .b64 da, db;\nsetp.eq.b32 p, 0, 0;\n"
      "add.u32 a, %80, %84;\nadd.u32 b, %81, %85;\nmov.b64 da, {a, 0x40000040};\nmov.b64 db, {b, %86};\n"
      "wgmma.mma_async.sync.aligned.m64n160k16.f32.bf16.bf16 {"
      "%0,%1,%2,%3,%4,%5,%6,%7,%8,%9,%10,%11,%12,%13,%14,%15,%16,%17,%18,%19,%20,%21,%22,%23,%24,%25,%26,%27,%28,%29,%30,%31,%32,%33,%34,%35,%36,"
      "%37,%38,%39,%40,%41,%42,%43,%44,%45,%46,%47,%48,%49,%50,%51,%52,%53,%54,%55,%56,%57,%58,%59,%60,%61,%62,%63,%64,%65,%66,%67,%68,%69,%70,%71,"
      "%72,%73,%74,%75,%76,%77,%78,%79"
      "}, da, db, p, 1, 1, %82, %83;\n}\n"
      :
      "+f"(d[0]),"+f"(d[1]),"+f"(d[2]),"+f"(d[3]),"+f"(d[4]),"+f"(d[5]),"+f"(d[6]),"+f"(d[7]),"+f"(d[8]),"+f"(d[9]),"+f"(d[10]),"+f"(d[11]),
      "+f"(d[12]),"+f"(d[13]),"+f"(d[14]),"+f"(d[15]),"+f"(d[16]),"+f"(d[17]),"+f"(d[18]),"+f"(d[19]),"+f"(d[20]),"+f"(d[21]),"+f"(d[22]),
      "+f"(d[23]),"+f"(d[24]),"+f"(d[25]),"+f"(d[26]),"+f"(d[27]),"+f"(d[28]),"+f"(d[29]),"+f"(d[30]),"+f"(d[31]),"+f"(d[32]),"+f"(d[33]),
      "+f"(d[34]),"+f"(d[35]),"+f"(d[36]),"+f"(d[37]),"+f"(d[38]),"+f"(d[39]),"+f"(d[40]),"+f"(d[41]),"+f"(d[42]),"+f"(d[43]),"+f"(d[44]),
      "+f"(d[45]),"+f"(d[46]),"+f"(d[47]),"+f"(d[48]),"+f"(d[49]),"+f"(d[50]),"+f"(d[51]),"+f"(d[52]),"+f"(d[53]),"+f"(d[54]),"+f"(d[55]),
      "+f"(d[56]),"+f"(d[57]),"+f"(d[58]),"+f"(d[59]),"+f"(d[60]),"+f"(d[61]),"+f"(d[62]),"+f"(d[63]),"+f"(d[64]),"+f"(d[65]),"+f"(d[66]),
      "+f"(d[67]),"+f"(d[68]),"+f"(d[69]),"+f"(d[70]),"+f"(d[71]),"+f"(d[72]),"+f"(d[73]),"+f"(d[74]),"+f"(d[75]),"+f"(d[76]),"+f"(d[77]),
      "+f"(d[78]),"+f"(d[79])
      : "r"(la), "r"(lb), "n"(TA), "n"(TB), "n"(OA >> 4), "n"(OB >> 4), "n"(TB ? 0xC0000010u : 0x40000040u));
}

template <int TA, int TB, uint32_t OA, uint32_t OB>
__device__ __forceinline__ void mma160z(float (&d)[80], uint32_t la, uint32_t lb) {
  asm volatile(
      "{\n.reg .pred p;\n.reg .b32 a, b;\n.reg .b64 da, db;\nsetp.ne.b32 p, 0, 0;\n"
      "add.u32 a, %80, %84;\nadd.u32 b, %81, %85;\nmov.b64 da, {a, 0x40000040};\nmov.b64 db, {b, %86};\n"
      "wgmma.mma_async.sync.aligned.m64n160k16.f32.bf16.bf16 {"
      "%0,%1,%2,%3,%4,%5,%6,%7,%8,%9,%10,%11,%12,%13,%14,%15,%16,%17,%18,%19,%20,%21,%22,%23,%24,%25,%26,%27,%28,%29,%30,%31,%32,%33,%34,%35,%36,"
      "%37,%38,%39,%40,%41,%42,%43,%44,%45,%46,%47,%48,%49,%50,%51,%52,%53,%54,%55,%56,%57,%58,%59,%60,%61,%62,%63,%64,%65,%66,%67,%68,%69,%70,%71,"
      "%72,%73,%74,%75,%76,%77,%78,%79"
      "}, da, db, p, 1, 1, %82, %83;\n}\n"
      :
      "=f"(d[0]),"=f"(d[1]),"=f"(d[2]),"=f"(d[3]),"=f"(d[4]),"=f"(d[5]),"=f"(d[6]),"=f"(d[7]),"=f"(d[8]),"=f"(d[9]),"=f"(d[10]),"=f"(d[11]),
      "=f"(d[12]),"=f"(d[13]),"=f"(d[14]),"=f"(d[15]),"=f"(d[16]),"=f"(d[17]),"=f"(d[18]),"=f"(d[19]),"=f"(d[20]),"=f"(d[21]),"=f"(d[22]),
      "=f"(d[23]),"=f"(d[24]),"=f"(d[25]),"=f"(d[26]),"=f"(d[27]),"=f"(d[28]),"=f"(d[29]),"=f"(d[30]),"=f"(d[31]),"=f"(d[32]),"=f"(d[33]),
      "=f"(d[34]),"=f"(d[35]),"=f"(d[36]),"=f"(d[37]),"=f"(d[38]),"=f"(d[39]),"=f"(d[40]),"=f"(d[41]),"=f"(d[42]),"=f"(d[43]),"=f"(d[44]),
      "=f"(d[45]),"=f"(d[46]),"=f"(d[47]),"=f"(d[48]),"=f"(d[49]),"=f"(d[50]),"=f"(d[51]),"=f"(d[52]),"=f"(d[53]),"=f"(d[54]),"=f"(d[55]),
      "=f"(d[56]),"=f"(d[57]),"=f"(d[58]),"=f"(d[59]),"=f"(d[60]),"=f"(d[61]),"=f"(d[62]),"=f"(d[63]),"=f"(d[64]),"=f"(d[65]),"=f"(d[66]),
      "=f"(d[67]),"=f"(d[68]),"=f"(d[69]),"=f"(d[70]),"=f"(d[71]),"=f"(d[72]),"=f"(d[73]),"=f"(d[74]),"=f"(d[75]),"=f"(d[76]),"=f"(d[77]),
      "=f"(d[78]),"=f"(d[79])
      : "r"(la), "r"(lb), "n"(TA), "n"(TB), "n"(OA >> 4), "n"(OB >> 4), "n"(TB ? 0xC0000010u : 0x40000040u));
}

template <int TA, int TB, uint32_t OA, uint32_t OB>
__device__ __forceinline__ void mma80(float (&d)[40], uint32_t la, uint32_t lb) {
  asm volatile(
      "{\n.reg .pred p;\n.reg .b32 a, b;\n.reg .b64 da, db;\nsetp.eq.b32 p, 0, 0;\n"
      "add.u32 a, %40, %44;\nadd.u32 b, %41, %45;\nmov.b64 da, {a, 0x40000040};\nmov.b64 db, {b, %46};\n"
      "wgmma.mma_async.sync.aligned.m64n80k16.f32.bf16.bf16 {"
      "%0,%1,%2,%3,%4,%5,%6,%7,%8,%9,%10,%11,%12,%13,%14,%15,%16,%17,%18,%19,%20,%21,%22,%23,%24,%25,%26,%27,%28,%29,%30,%31,%32,%33,%34,%35,%36,"
      "%37,%38,%39"
      "}, da, db, p, 1, 1, %42, %43;\n}\n"
      :
      "+f"(d[0]),"+f"(d[1]),"+f"(d[2]),"+f"(d[3]),"+f"(d[4]),"+f"(d[5]),"+f"(d[6]),"+f"(d[7]),"+f"(d[8]),"+f"(d[9]),"+f"(d[10]),"+f"(d[11]),
      "+f"(d[12]),"+f"(d[13]),"+f"(d[14]),"+f"(d[15]),"+f"(d[16]),"+f"(d[17]),"+f"(d[18]),"+f"(d[19]),"+f"(d[20]),"+f"(d[21]),"+f"(d[22]),
      "+f"(d[23]),"+f"(d[24]),"+f"(d[25]),"+f"(d[26]),"+f"(d[27]),"+f"(d[28]),"+f"(d[29]),"+f"(d[30]),"+f"(d[31]),"+f"(d[32]),"+f"(d[33]),
      "+f"(d[34]),"+f"(d[35]),"+f"(d[36]),"+f"(d[37]),"+f"(d[38]),"+f"(d[39])
      : "r"(la), "r"(lb), "n"(TA), "n"(TB), "n"(OA >> 4), "n"(OB >> 4), "n"(TB ? 0xC0000010u : 0x40000040u));
}

template <int TA, int TB, uint32_t OA, uint32_t OB>
__device__ __forceinline__ void mma80z(float (&d)[40], uint32_t la, uint32_t lb) {
  asm volatile(
      "{\n.reg .pred p;\n.reg .b32 a, b;\n.reg .b64 da, db;\nsetp.ne.b32 p, 0, 0;\n"
      "add.u32 a, %40, %44;\nadd.u32 b, %41, %45;\nmov.b64 da, {a, 0x40000040};\nmov.b64 db, {b, %46};\n"
      "wgmma.mma_async.sync.aligned.m64n80k16.f32.bf16.bf16 {"
      "%0,%1,%2,%3,%4,%5,%6,%7,%8,%9,%10,%11,%12,%13,%14,%15,%16,%17,%18,%19,%20,%21,%22,%23,%24,%25,%26,%27,%28,%29,%30,%31,%32,%33,%34,%35,%36,"
      "%37,%38,%39"
      "}, da, db, p, 1, 1, %42, %43;\n}\n"
      :
      "=f"(d[0]),"=f"(d[1]),"=f"(d[2]),"=f"(d[3]),"=f"(d[4]),"=f"(d[5]),"=f"(d[6]),"=f"(d[7]),"=f"(d[8]),"=f"(d[9]),"=f"(d[10]),"=f"(d[11]),
      "=f"(d[12]),"=f"(d[13]),"=f"(d[14]),"=f"(d[15]),"=f"(d[16]),"=f"(d[17]),"=f"(d[18]),"=f"(d[19]),"=f"(d[20]),"=f"(d[21]),"=f"(d[22]),
      "=f"(d[23]),"=f"(d[24]),"=f"(d[25]),"=f"(d[26]),"=f"(d[27]),"=f"(d[28]),"=f"(d[29]),"=f"(d[30]),"=f"(d[31]),"=f"(d[32]),"=f"(d[33]),
      "=f"(d[34]),"=f"(d[35]),"=f"(d[36]),"=f"(d[37]),"=f"(d[38]),"=f"(d[39])
      : "r"(la), "r"(lb), "n"(TA), "n"(TB), "n"(OA >> 4), "n"(OB >> 4), "n"(TB ? 0xC0000010u : 0x40000040u));
}

template <int TA, int TB, uint32_t OA, uint32_t OB>
__device__ __forceinline__ void mma128r(float (&d)[64], uint32_t la, uint32_t lb, int sc) {
  asm volatile(
      "{\n.reg .pred p;\n.reg .b32 a, b;\n.reg .b64 da, db;\nsetp.ne.b32 p, %71, 0;\n"
      "add.u32 a, %64, %68;\nadd.u32 b, %65, %69;\nmov.b64 da, {a, 0x40000040};\nmov.b64 db, {b, %70};\n"
      "wgmma.mma_async.sync.aligned.m64n128k16.f32.bf16.bf16 {"
      "%0,%1,%2,%3,%4,%5,%6,%7,%8,%9,%10,%11,%12,%13,%14,%15,%16,%17,%18,%19,%20,%21,%22,%23,%24,%25,%26,%27,%28,%29,%30,%31,%32,%33,%34,%35,%36,"
      "%37,%38,%39,%40,%41,%42,%43,%44,%45,%46,%47,%48,%49,%50,%51,%52,%53,%54,%55,%56,%57,%58,%59,%60,%61,%62,%63"
      "}, da, db, p, 1, 1, %66, %67;\n}\n"
      :
      "+f"(d[0]),"+f"(d[1]),"+f"(d[2]),"+f"(d[3]),"+f"(d[4]),"+f"(d[5]),"+f"(d[6]),"+f"(d[7]),"+f"(d[8]),"+f"(d[9]),"+f"(d[10]),"+f"(d[11]),
      "+f"(d[12]),"+f"(d[13]),"+f"(d[14]),"+f"(d[15]),"+f"(d[16]),"+f"(d[17]),"+f"(d[18]),"+f"(d[19]),"+f"(d[20]),"+f"(d[21]),"+f"(d[22]),
      "+f"(d[23]),"+f"(d[24]),"+f"(d[25]),"+f"(d[26]),"+f"(d[27]),"+f"(d[28]),"+f"(d[29]),"+f"(d[30]),"+f"(d[31]),"+f"(d[32]),"+f"(d[33]),
      "+f"(d[34]),"+f"(d[35]),"+f"(d[36]),"+f"(d[37]),"+f"(d[38]),"+f"(d[39]),"+f"(d[40]),"+f"(d[41]),"+f"(d[42]),"+f"(d[43]),"+f"(d[44]),
      "+f"(d[45]),"+f"(d[46]),"+f"(d[47]),"+f"(d[48]),"+f"(d[49]),"+f"(d[50]),"+f"(d[51]),"+f"(d[52]),"+f"(d[53]),"+f"(d[54]),"+f"(d[55]),
      "+f"(d[56]),"+f"(d[57]),"+f"(d[58]),"+f"(d[59]),"+f"(d[60]),"+f"(d[61]),"+f"(d[62]),"+f"(d[63])
      : "r"(la), "r"(lb), "n"(TA), "n"(TB), "n"(OA >> 4), "n"(OB >> 4), "n"(TB ? 0xC0000010u : 0x40000040u), "r"(sc));
}

template <int TA, int TB, uint32_t OA, uint32_t OB>
__device__ __forceinline__ void mma64r(float (&d)[32], uint32_t la, uint32_t lb, int sc) {
  asm volatile(
      "{\n.reg .pred p;\n.reg .b32 a, b;\n.reg .b64 da, db;\nsetp.ne.b32 p, %39, 0;\n"
      "add.u32 a, %32, %36;\nadd.u32 b, %33, %37;\nmov.b64 da, {a, 0x40000040};\nmov.b64 db, {b, %38};\n"
      "wgmma.mma_async.sync.aligned.m64n64k16.f32.bf16.bf16 {"
      "%0,%1,%2,%3,%4,%5,%6,%7,%8,%9,%10,%11,%12,%13,%14,%15,%16,%17,%18,%19,%20,%21,%22,%23,%24,%25,%26,%27,%28,%29,%30,%31"
      "}, da, db, p, 1, 1, %34, %35;\n}\n"
      :
      "+f"(d[0]),"+f"(d[1]),"+f"(d[2]),"+f"(d[3]),"+f"(d[4]),"+f"(d[5]),"+f"(d[6]),"+f"(d[7]),"+f"(d[8]),"+f"(d[9]),"+f"(d[10]),"+f"(d[11]),
      "+f"(d[12]),"+f"(d[13]),"+f"(d[14]),"+f"(d[15]),"+f"(d[16]),"+f"(d[17]),"+f"(d[18]),"+f"(d[19]),"+f"(d[20]),"+f"(d[21]),"+f"(d[22]),
      "+f"(d[23]),"+f"(d[24]),"+f"(d[25]),"+f"(d[26]),"+f"(d[27]),"+f"(d[28]),"+f"(d[29]),"+f"(d[30]),"+f"(d[31])
      : "r"(la), "r"(lb), "n"(TA), "n"(TB), "n"(OA >> 4), "n"(OB >> 4), "n"(TB ? 0xC0000010u : 0x40000040u), "r"(sc));
}

struct Ring { uint32_t s0, ph0; };
__device__ __forceinline__ void ring_pos(const Ring& r, int i, uint32_t& slot, uint32_t& ph) {
  uint32_t s = opaque(r.s0) + (i % NSLOT);
  uint32_t wrap = s >= NSLOT;
  slot = s - (wrap ? NSLOT : 0);
  ph = r.ph0 ^ ((i / NSLOT) & 1) ^ wrap;
}
__device__ __forceinline__ void ring_advance(Ring& r, int n) {
  uint32_t s, p;
  ring_pos(r, n, s, p);
  r.s0 = s; r.ph0 = p;
}
__host__ __device__ constexpr int idxK(int j) { return j == 0 ? 10 : 9 + 2 * j; }
__host__ __device__ constexpr int idxV(int j) { return j == 7 ? 25 : 12 + 2 * j; }
__host__ __device__ constexpr int xs(int c) { return c % NSLOT; }

struct Sched { int first, second, n, delay; };
__device__ __forceinline__ Sched get_sched(int cta) {
  if (cta < N_OCTA) return Sched{cta, 0, 1, O_DELAY + cta * O_SLOPE};
  const int a = cta - N_OCTA;
  return Sched{cta, cta + N_ATT, a < N_G1 ? 11 : 10, max(0, a - STAG_A0) * STAG_SLOPE + (a < N_G1 ? 0 : G2_EXTRA)};
}
__device__ __forceinline__ int sched_item(const Sched& s, int k) { return k == 0 ? s.first : s.second + (k - 1) * N_ATT; }

template <int W, bool ACC>
__device__ __forceinline__ void mma_main(float (&d)[80], uint32_t aaddr, uint32_t baddr) {
  const uint32_t la = lo_sw(aaddr), lb = lo_sw(baddr);
  if (ACC) mma160<1, 0, W * 16384, 0>(d, la, lb); else mma160z<1, 0, W * 16384, 0>(d, la, lb);
  mma160<1, 0, W * 16384 + 1 * 2048, 1 * 32>(d, la, lb);
  mma160<1, 0, W * 16384 + 2 * 2048, 2 * 32>(d, la, lb);
  mma160<1, 0, W * 16384 + 3 * 2048, 3 * 32>(d, la, lb);
}
template <int W, bool ACC>
__device__ __forceinline__ void mma_mid(float (&d)[40], uint32_t aaddr, uint32_t baddr) {
  const uint32_t la = lo_sw(aaddr), lb = lo_sw(baddr);
  if (ACC) mma80<1, 0, 8192, W * 10240>(d, la, lb); else mma80z<1, 0, 8192, W * 10240>(d, la, lb);
  mma80<1, 0, 8192 + 1 * 2048, W * 10240 + 1 * 32>(d, la, lb);
  mma80<1, 0, 8192 + 2 * 2048, W * 10240 + 2 * 32>(d, la, lb);
  mma80<1, 0, 8192 + 3 * 2048, W * 10240 + 3 * 32>(d, la, lb);
}
template <int W, bool ACC>
__device__ __forceinline__ void mma_both(float (&dm)[80], float (&dh)[40], uint32_t aaddr, uint32_t baddr) {
  mma_mid<W, ACC>(dh, aaddr, baddr);
  mma_main<W, ACC>(dm, aaddr, baddr);
}
template <int KB, bool ACC>
__device__ __forceinline__ void s_mma(float (&sacc)[80], uint32_t kaddr) {
  const uint32_t la = lo_sw(kaddr), lb = lo_sw(SB + OFF_B);
  if (ACC) mma160<0, 0, KB * 8192, KB * B_SLOT>(sacc, la, lb); else mma160z<0, 0, KB * 8192, KB * B_SLOT>(sacc, la, lb);
  mma160<0, 0, KB * 8192 + 32, KB * B_SLOT + 32>(sacc, la, lb);
  mma160<0, 0, KB * 8192 + 64, KB * B_SLOT + 64>(sacc, la, lb);
  mma160<0, 0, KB * 8192 + 96, KB * B_SLOT + 96>(sacc, la, lb);
}
template <int N>
__device__ __forceinline__ void store_scaled(uint32_t addr, const float (&d)[N], float sc) {
#pragma unroll
  for (int J = 0; J < N / 8; J++)
    stsm_t(addr + J * 2048, pack2(d[8 * J] * sc, d[8 * J + 1] * sc), pack2(d[8 * J + 2] * sc, d[8 * J + 3] * sc),
           pack2(d[8 * J + 4] * sc, d[8 * J + 5] * sc), pack2(d[8 * J + 6] * sc, d[8 * J + 7] * sc));
}
__device__ __forceinline__ float4 lds_f4(uint32_t a) {
  float4 v;
  asm volatile("ld.shared.v4.f32 {%0,%1,%2,%3}, [%4];" : "=f"(v.x), "=f"(v.y), "=f"(v.z), "=f"(v.w) : "r"(a) : "memory");
  return v;
}
__device__ __forceinline__ void norm_pack(uint32_t* p, const float* d, const float4& i) {
  p[0] = pack2(d[0] * i.x, d[1] * i.y); p[1] = pack2(d[4] * i.z, d[5] * i.w);
  p[2] = pack2(d[2] * i.x, d[3] * i.y); p[3] = pack2(d[6] * i.z, d[7] * i.w);
  asm volatile("" : "+r"(p[0]), "+r"(p[1]), "+r"(p[2]), "+r"(p[3])::"memory");
}
template <int W>
__device__ __forceinline__ void pack_first(uint32_t (&pk)[60], const float (&om)[80], const float (&oh)[40], uint32_t laddr) {
  float4 n0 = lds_f4(laddr + W * 80), n1 = lds_f4(laddr + W * 80 + 16);
#pragma unroll
  for (int J = 0; J < 5; J++) {
    const float4 i = n0;
    n0 = n1;
    if (J + 2 < 5) n1 = lds_f4(laddr + W * 80 + (J + 2) * 16);
    norm_pack(&pk[20 + 4 * J], &om[8 * (5 * W + J)], i);
    norm_pack(&pk[4 * J], &oh[8 * J], i);
  }
}
template <int W, int J0, int J1>
__device__ __forceinline__ void pack_second(uint32_t (&pk)[60], const float (&om)[80], uint32_t laddr) {
  float4 n[J1 - J0];
#pragma unroll
  for (int J = J0; J < J1; J++) n[J - J0] = lds_f4(laddr + (1 - W) * 80 + J * 16);
#pragma unroll
  for (int J = J0; J < J1; J++) norm_pack(&pk[40 + 4 * J], &om[8 * (5 * (1 - W) + J)], n[J - J0]);
}
__device__ __forceinline__ char* o_ptr(int item) {
  const uint32_t t = tid_x();
  return (char*)g_o + (size_t)(item % ORING) * O_ITEM_BYTES + ((t & 96) * 16 + (t & 28) * 8 + ((((t >> 1) ^ (t >> 4)) & 1) << 4) + (t & 1) * 8);
}
template <int W, int G0, int G1>
__device__ __forceinline__ void store_groups(char* op, const uint32_t (&pk)[60], uint32_t on) {
#pragma unroll
  for (int G = G0; G < G1; G++) {
    const int off = (G < 5 ? 1 : 2 * W) * B_SLOT + (5 * (G < 10 ? W : 1 - W) + G % 5) * 2048;
    asm volatile("{\n.reg .pred p;\nsetp.ne.u32 p, %5, 0;\n@p st.global.v2.b32 [%0], {%1, %2};\n@p st.global.v2.b32 [%0+256], {%3, %4};\n}\n"
                 ::"l"(op + off), "r"(pk[4 * G]), "r"(pk[4 * G + 1]), "r"(pk[4 * G + 2]), "r"(pk[4 * G + 3]), "r"(on) : "memory");
  }
}
__device__ __forceinline__ void publish_generic(uint32_t bar, int lane) {
  __syncwarp();
  mbar_arrive_if0(bar, lane);
}
__device__ __forceinline__ void publish(uint32_t bar, int lane) {
  proxy_fence();
  __syncwarp();
  mbar_arrive_if0(bar, lane);
}

#define A_ADDR(s) (SB + OFF_A + (s) * A_SLOT)
#define B_ADDR(s) (SB + OFF_B + (s) * B_SLOT)
#define WAIT_CHUNK(c, ro, sA)                \
  uint32_t sA;                               \
  {                                          \
    uint32_t pA_;                            \
    ring_pos(ring, (ro) + (c), sA, pA_);     \
    mbar_wait(bud, BAR_FULLA + sA * 8, pA_); \
  }
#define RELEASE_CHUNK(c, sA)                                  \
  mbar_arrive_if0(BAR_EMPTYA + (sA) * 8, tid);                \
  if ((c) < NSLOT) mbar_arrive_if0(BAR_EMPTYB + xs(c) * 8, tid);

template <int W>
__device__ __forceinline__ void attn_consumer(const Sched& sc) {
  int bud = WAIT_BUDGET;
  const int tid = threadIdx.x & 127, lane = tid & 31, warp = tid >> 5;
  const uint32_t st_off = ((lane & 7) + 8 * (lane >> 4)) * 128 + (((2 * warp + ((lane >> 3) & 1)) ^ (lane & 7)) << 4);
  const uint32_t laddr = SB + OFF_L + (lane & 3) * 160;
  float om[80], oh[40], sacc[80];
  uint32_t pk[60];
#pragma unroll
  for (int i = 0; i < 40; i++) pk[i] = 0;
  zero_regs(om);
  Ring ring{0u, 0u};
  uint32_t par = 0;
  const float qscale = 0.07216878364870322f * 1.4426950408889634f;
  constexpr uint32_t pown = B_ADDR(3 + W), poth = B_ADDR(4 - W);
  TL(0); TLG(62);
  {
    WAIT_CHUNK(0, 0, s0)
    wg_fence();
    mma_both<W, false>(sacc, oh, A_ADDR(s0), B_ADDR(xs(0)));
    wg_commit();
    WAIT_CHUNK(1, 0, s1)
    wg_fence();
    mma_both<W, true>(sacc, oh, A_ADDR(s1), B_ADDR(xs(1)));
    wg_commit();
    wg_wait<1>();
    RELEASE_CHUNK(0, s0)
  }
#pragma unroll 1
  for (int it = 0;; it++) {
    char* op = o_ptr(sched_item(sc, max(it - 1, 0)));
#pragma unroll
    for (int c = 2; c < 8 - W; c++) {
      WAIT_CHUNK(c, 0, sA)
      TL(40 + c);
      wg_fence();
      mma_both<W, true>(sacc, oh, A_ADDR(sA), B_ADDR(xs(c)));
      wg_commit();
      wg_wait<1>();
      uint32_t sP, pP;
      ring_pos(ring, c - 1, sP, pP);
      RELEASE_CHUNK(c - 1, sP)
      constexpr int NG = W == 0 ? 3 : W1_NG;
      if (c == 2) { pack_second<W, 0, 1>(pk, om, laddr); store_groups<W, 0 * NG, 1 * NG>(op, pk, it); }
      if (c == 3) { pack_second<W, 1, 2>(pk, om, laddr); store_groups<W, 1 * NG, 2 * NG>(op, pk, it); }
      if (c == 4) { pack_second<W, 2, 3>(pk, om, laddr); store_groups<W, 2 * NG, 3 * NG>(op, pk, it); }
      if (c == 5) { pack_second<W, 3, 4>(pk, om, laddr); store_groups<W, 3 * NG, 4 * NG>(op, pk, it); }
      if (c == 6) {
        pack_second<W, 4, 5>(pk, om, laddr);
        if (W == 1) {
          wg_wait<0>();
          RELEASE_CHUNK(6, sA)
          mbar_arrive_if0(BAR_XDONE, tid);
        }
        store_groups<W, 4 * NG, 15>(op, pk, it);
        __syncwarp();
        mbar_arrive_if0(BAR_OFULL, lane | (it == 0));
      }
    }
    uint32_t sK0, pK0, s7, p7;
    ring_pos(ring, idxK(W), sK0, pK0);
    ring_pos(ring, 7, s7, p7);
    if (W == 1) mbar_wait(bud, BAR_FULLA + s7 * 8, p7);
    WAIT_CHUNK(8, 0, s8)
    WAIT_CHUNK(9, 0, s9)
    TL(48);
    if (W == 0) {
      wg_fence();
      mma_mid<W, true>(oh, A_ADDR(s8), B_ADDR(xs(8)));
      mma_mid<W, true>(oh, A_ADDR(s9), B_ADDR(xs(9)));
      wg_commit();
      wg_wait<1>();
      RELEASE_CHUNK(7, s7)
      wg_fence();
      mma_main<W, true>(sacc, A_ADDR(s8), B_ADDR(xs(8)));
      mma_main<W, true>(sacc, A_ADDR(s9), B_ADDR(xs(9)));
      wg_commit();
      bar_arrive(5, 256);
      TL(49);
      wg_wait<1>();
      reg_fence(oh);
      mbar_wait(bud, BAR_XDONE, par);
      store_scaled(B_ADDR(1) + st_off, oh, qscale);
    } else {
      bar_sync(5, 256);
      wg_fence();
      mma_mid<W, true>(oh, A_ADDR(s7), B_ADDR(xs(7)));
      mma_mid<W, true>(oh, A_ADDR(s8), B_ADDR(xs(8)));
      mma_mid<W, true>(oh, A_ADDR(s9), B_ADDR(xs(9)));
      wg_commit();
      mma_main<W, true>(sacc, A_ADDR(s7), B_ADDR(xs(7)));
      wg_commit();
      mma_main<W, true>(sacc, A_ADDR(s8), B_ADDR(xs(8)));
      wg_commit();
      wg_wait<2>();
      reg_fence(oh);
      store_scaled(B_ADDR(1) + 10240 + st_off, oh, qscale);
      wg_fence();
      mma_main<W, true>(sacc, A_ADDR(s9), B_ADDR(xs(9)));
      wg_commit();
      bar_arrive(8, 256);
      TL(49);
      wg_wait<2>();
      RELEASE_CHUNK(7, s7)
      publish(BAR_QH, lane);
    }
    wg_wait<0>();
    reg_fence(sacc);
    TL(1);
    RELEASE_CHUNK(8, s8)
    RELEASE_CHUNK(9, s9)
    store_scaled(B_ADDR(2 * W) + st_off, sacc, qscale);
    if (W == 1) publish(BAR_QM, lane); else proxy_fence();
    TL(2);
    uint32_t sK = sK0, sV1 = 0;
    if (W == 0) {
      zero_regs(om); zero_regs(oh);
      reg_fence(om); reg_fence(oh);
      mbar_wait(bud, BAR_FULLA + sK0 * 8, pK0);
      bar_sync(8, 256);
      wg_fence();
      s_mma<0, false>(sacc, A_ADDR(sK));
      mbar_wait(bud, BAR_QH, par);
      TL(3);
      wg_fence();
      s_mma<1, true>(sacc, A_ADDR(sK));
      mbar_wait(bud, BAR_QM, par);
      TL(5);
      wg_fence();
      s_mma<2, true>(sacc, A_ADDR(sK));
      wg_commit();
      wg_commit();
      bar_arrive(2, 256);
    } else {
      uint32_t pV1;
      ring_pos(ring, idxV(0), sV1, pV1);
      mbar_wait(bud, BAR_FULLA + sK * 8, pK0);
      bar_sync(2, 256);
      wg_fence();
      s_mma<0, false>(sacc, A_ADDR(sK));
      s_mma<1, true>(sacc, A_ADDR(sK));
      s_mma<2, true>(sacc, A_ADDR(sK));
      wg_commit();
      TL(6);
      mbar_wait(bud, BAR_FULLA + sV1 * 8, pV1);
      mbar_wait(bud, BAR_PFULL, 0);
      TL(7);
      wg_fence();
      mma_both<W, false>(om, oh, A_ADDR(sV1), poth);
      wg_commit();
      bar_arrive(1, 256);
    }
    Ring rv;
    ring_pos(ring, idxV(W), rv.s0, rv.ph0);
#pragma unroll 1
    for (int jj = 0;; jj++) {
      wg_wait<1>();
      reg_fence(sacc);
      TL(8 + jj * 7);
      mbar_arrive2_if0(BAR_EMPTYA + sK * 8, tid);
      mbar_arrive_if0(BAR_EMPTYB + tid * 8, (tid >= 3) | (jj != 3));
#pragma unroll
      for (int J = 0; J < 10; J++) {
        stsm_t(pown + st_off + J * 2048, pack2(ex2(sacc[8 * J]), ex2(sacc[8 * J + 1])), pack2(ex2(sacc[8 * J + 2]), ex2(sacc[8 * J + 3])),
               pack2(ex2(sacc[8 * J + 4]), ex2(sacc[8 * J + 5])), pack2(ex2(sacc[8 * J + 6]), ex2(sacc[8 * J + 7])));
        if (W == 1 && (J == 2 || J == 5)) publish_generic(BAR_PMID + (J / 3) * 8, lane | (jj != 3));
        if (J == 4) {
          wg_wait<0>();
          mbar_arrive_if0(BAR_EMPTYA + sV1 * 8, tid | (W == 0 && jj == 0));
        }
      }
      publish(BAR_PFULL + W * 8, lane);
      TL(10 + jj * 7);
      if (jj == 3) break;
      uint32_t pK, pV1;
      ring_pos(rv, 1, sK, pK);
      ring_pos(rv, 2, sV1, pV1);
      mbar_wait(bud, BAR_FULLA + rv.s0 * 8, rv.ph0);
      bar_sync(1 + W, 256);
      wg_fence();
      mma_both<W, true>(om, oh, A_ADDR(rv.s0), pown);
      wg_commit();
      mbar_wait(bud, BAR_FULLA + sK * 8, pK);
      TL(11 + jj * 7);
      wg_fence();
      s_mma<0, false>(sacc, A_ADDR(sK));
      s_mma<1, true>(sacc, A_ADDR(sK));
      wg_commit();
      wg_wait<1>();
      mbar_arrive_if0(BAR_EMPTYA + rv.s0 * 8, tid);
      wg_fence();
      s_mma<2, true>(sacc, A_ADDR(sK));
      wg_commit();
      TL(13 + jj * 7);
      mbar_wait(bud, BAR_FULLA + sV1 * 8, pV1);
      mbar_wait(bud, BAR_PFREE + W * 8, jj & 1);
      mbar_wait(bud, BAR_PFULL + (1 - W) * 8, (jj + W) & 1);
      TL(14 + jj * 7);
      wg_fence();
      mma_both<W, true>(om, oh, A_ADDR(sV1), poth);
      wg_commit();
      bar_arrive(2 - W, 256);
      ring_advance(rv, 4);
    }
    uint32_t sV7, pV7;
    ring_pos(ring, idxV(7), sV7, pV7);
    if (W == 0) {
      uint32_t sV6, pV6;
      ring_pos(ring, idxV(6), sV6, pV6);
      mbar_wait(bud, BAR_FULLA + sV6 * 8, pV6);
      bar_sync(1, 256);
      wg_fence();
      mma_both<0, true>(om, oh, A_ADDR(sV6), pown);
      wg_commit();
      mbar_wait(bud, BAR_FULLA + sV7 * 8, pV7);
      wg_wait<0>();
      mbar_arrive_if0(BAR_EMPTYA + sV6 * 8, tid);
      mbar_wait(bud, BAR_PFULL + 8, 1);
      wg_fence();
      mma_both<0, true>(om, oh, A_ADDR(sV7), poth);
      wg_commit();
      bar_arrive(6, 256);
    } else {
      mbar_wait(bud, BAR_FULLA + sV7 * 8, pV7);
      bar_sync(6, 256);
    }
    TL(32);
    if (it + 1 == sc.n) {
      if (W == 1) {
        wg_fence();
        mma_both<1, true>(om, oh, A_ADDR(sV7), pown);
        wg_commit();
      }
      wg_wait<0>();
      reg_fence(om); reg_fence(oh);
      TL(33);
      mbar_wait(bud, BAR_LFULL, par);
      TL(34);
      pack_first<W>(pk, om, oh, laddr);
      op = o_ptr(sched_item(sc, it));
      store_groups<W, 0, 10>(op, pk, 1);
      pack_second<W, 0, 5>(pk, om, laddr);
      store_groups<W, 10, 15>(op, pk, 1);
      publish_generic(BAR_OFULL, lane);
      TL(35); TLG(63);
      TL_FLUSH();
      break;
    }
    {
      if (W == 1) {
        wg_fence();
        mma_both<1, true>(om, oh, A_ADDR(sV7), pown);
        wg_commit();
      }
      WAIT_CHUNK(0, 26, s0)
      WAIT_CHUNK(1, 26, s1)
      if (W == 0) {
        wg_wait<0>();
        reg_fence(om); reg_fence(oh);
        TL(33);
        wg_fence();
        mma_main<W, false>(sacc, A_ADDR(s0), B_ADDR(xs(0)));
        wg_commit();
      } else {
        wg_fence();
        mma_main<W, false>(sacc, A_ADDR(s0), B_ADDR(xs(0)));
        mma_main<W, true>(sacc, A_ADDR(s1), B_ADDR(xs(1)));
        wg_commit();
        wg_wait<1>();
        reg_fence(om); reg_fence(oh);
        TL(33);
      }
      mbar_arrive_if0(BAR_EMPTYA + sV7 * 8, tid);
      mbar_wait(bud, BAR_LFULL, par);
      mbar_arrive_if0(BAR_EMPTYB + 24 + tid * 8, tid >= 2);
      TL(34);
      pack_first<W>(pk, om, oh, laddr);
      TL(36);
      wg_fence();
      mma_mid<W, false>(oh, A_ADDR(s0), B_ADDR(xs(0)));
      wg_commit();
      mma_mid<W, true>(oh, A_ADDR(s1), B_ADDR(xs(1)));
      if (W == 0) mma_main<W, true>(sacc, A_ADDR(s1), B_ADDR(xs(1)));
      wg_commit();
      TL(37);
      wg_wait<1>();
      RELEASE_CHUNK(0, s0)
      TL(35); TLG(63);
    }
    TL_FLUSH();
    TL(0); TLG(62);
    ring_advance(ring, 26);
    par ^= 1;
  }
}

__device__ __forceinline__ uint4 lds128(uint32_t a) {
  uint4 v;
  asm volatile("ld.shared.v4.b32 {%0,%1,%2,%3}, [%4];" : "=r"(v.x), "=r"(v.y), "=r"(v.z), "=r"(v.w) : "r"(a) : "memory");
  return v;
}
__device__ __forceinline__ void acc2(float& s, float& t, uint32_t w) {
  s += __uint_as_float(w << 16);
  t += __uint_as_float(w & 0xffff0000u);
}
__device__ __forceinline__ uint32_t badd2(uint32_t a, uint32_t b) { uint32_t r; asm("add.rn.bf16x2 %0, %1, %2;" : "=r"(r) : "r"(a), "r"(b)); return r; }
__device__ __forceinline__ void sum_unit(float& acc, uint32_t pb) {
  const uint4 v0 = lds128(pb), v1 = lds128(pb ^ 32), v2 = lds128(pb ^ 64), v3 = lds128(pb ^ 96);
  const uint32_t w0 = badd2(v0.x, v0.y), w1 = badd2(v0.z, v0.w);
  float s0 = acc + __uint_as_float(w0 << 16), t0 = __uint_as_float(w0 & 0xffff0000u);
  float s1 = __uint_as_float(w1 << 16), t1 = __uint_as_float(w1 & 0xffff0000u);
  acc2(s0, t0, badd2(v1.x, v1.y)); acc2(s1, t1, badd2(v1.z, v1.w));
  acc2(s0, t0, badd2(v2.x, v2.y)); acc2(s1, t1, badd2(v2.z, v2.w));
  acc2(s0, t0, badd2(v3.x, v3.y)); acc2(s1, t1, badd2(v3.z, v3.w));
  acc = (s0 + t0) + (s1 + t1);
}
__device__ __forceinline__ float bf_lo(uint32_t w) { return __uint_as_float(w << 16); }
__device__ __forceinline__ float bf_hi(uint32_t w) { return __uint_as_float(w & 0xffff0000u); }
__device__ __forceinline__ float bf_rn(float x) { return __bfloat162float(__float2bfloat16(x)); }
__device__ __forceinline__ void slow_item(const Params& p, int item, int hw) {
  const int blk = item >> 9, h = (item >> 4) & 31, b = item & 15;
#pragma unroll 1
  for (int n = hw; n < SQ; n += 3) {
    float q[6] = {0.f, 0.f, 0.f, 0.f, 0.f, 0.f};
    {
      const uint32_t* xr = (const uint32_t*)(p.xp[blk] + (size_t)(b * SQ + n) * DM);
      const uint32_t* wq = (const uint32_t*)(p.wqp[blk] + h * DH) + (tid_x() & 31);
#pragma unroll 2
      for (int k = 0; k < DM / 2; k++) {
        const uint32_t xv = xr[k];
#pragma unroll
        for (int i = 0; i < 3; i++) {
          const uint32_t w0 = wq[i * 32], w1 = wq[NH * DH / 2 + i * 32];
          q[2 * i] = fmaf(bf_lo(xv), bf_lo(w0), fmaf(bf_hi(xv), bf_lo(w1), q[2 * i]));
          q[2 * i + 1] = fmaf(bf_lo(xv), bf_hi(w0), fmaf(bf_hi(xv), bf_hi(w1), q[2 * i + 1]));
        }
        wq += NH * DH;
      }
    }
    const uint32_t q0 = pack2(q[0], q[1]), q1 = pack2(q[2], q[3]), q2 = pack2(q[4], q[5]);
    float o[6] = {0.f, 0.f, 0.f, 0.f, 0.f, 0.f}, m = -INFINITY, l = 0.f;
    const uint32_t* kg = (const uint32_t*)(p.kp[blk] + (size_t)(b * NH + h) * SK * DH) + (tid_x() & 31);
    const uint32_t* vg = (const uint32_t*)(p.vp[blk] + (size_t)(b * NH + h) * SK * DH) + (tid_x() & 31);
#pragma unroll 1
    for (int k = 0; k < SK; k++) {
      const uint32_t k0 = kg[0], k1 = kg[32], k2 = kg[64], v0 = vg[0], v1 = vg[32], v2 = vg[64];
      kg += DH / 2; vg += DH / 2;
      float sc = fmaf(bf_lo(q0), bf_lo(k0), bf_hi(q0) * bf_hi(k0));
      sc = fmaf(bf_lo(q1), bf_lo(k1), fmaf(bf_hi(q1), bf_hi(k1), sc));
      sc = fmaf(bf_lo(q2), bf_lo(k2), fmaf(bf_hi(q2), bf_hi(k2), sc));
#pragma unroll
      for (int d = 16; d; d >>= 1) sc += __shfl_xor_sync(0xffffffffu, sc, d);
      sc = bf_rn(bf_rn(sc) * 0.07216878364870322f);
      const float mn = fmaxf(m, sc), a = ex2((m - mn) * 1.4426950408889634f), pr = ex2((sc - mn) * 1.4426950408889634f);
      m = mn;
      l = fmaf(l, a, pr);
      o[0] = fmaf(o[0], a, pr * bf_lo(v0)); o[1] = fmaf(o[1], a, pr * bf_hi(v0));
      o[2] = fmaf(o[2], a, pr * bf_lo(v1)); o[3] = fmaf(o[3], a, pr * bf_hi(v1));
      o[4] = fmaf(o[4], a, pr * bf_lo(v2)); o[5] = fmaf(o[5], a, pr * bf_hi(v2));
    }
    float inv;
    asm("rcp.approx.ftz.f32 %0, %1;" : "=f"(inv) : "f"(l));
    const int lane = tid_x() & 31;
    const int r = n & 15, c = 4 * ((r & 7) >> 1) + 2 * (r >> 3) + (r & 1);
    char* on = (char*)g_o + (size_t)(item % ORING) * O_ITEM_BYTES + (lane >> 2) * 256 + (lane & 3) * 64 + (n >> 4) * 2048 +
               (((c >> 3) ^ ((lane >> 1) & 1)) << 4) + (c & 7) * 2;
#pragma unroll
    for (int i = 0; i < 3; i++) {
      *(__nv_bfloat16*)(on + i * B_SLOT) = __float2bfloat16(o[2 * i] * inv);
      *(__nv_bfloat16*)(on + i * B_SLOT + 32) = __float2bfloat16(o[2 * i + 1] * inv);
    }
  }
}
__device__ __forceinline__ void attn_helper(const Params& p, int hw, const Sched& sc, int epoch) {
  int bud = WAIT_BUDGET;
#pragma unroll 1
  for (int it = 0; it < sc.n; it++) {
    const int item = sched_item(sc, it);
    const uint32_t par = it & 1;
    int lane = tid_x() & 31;
    const int r = lane >> 1;
    const uint32_t a0 = B_ADDR(3) + (16 * hw + r) * 128 + (lane & 1) * 16 + ((r & 3) << 5);
    float acc[4] = {0.f, 0.f, 0.f, 0.f};
#pragma unroll 1
    for (int j = 0; j < 8; j++) {
      const uint32_t pb = a0 + (j & 1) * B_SLOT, bfull = BAR_PFULL + (j & 1) * 8, pfull = (j >> 1) & 1;
      mbar_wait(bud, j == 7 ? BAR_PMID : bfull, j == 7 ? par : pfull);
      sum_unit(acc[0], pb);
      if (j == 7) mbar_wait(bud, BAR_PMID + 8, par);
      sum_unit(acc[1], pb + 6144);
      if (j == 7) mbar_wait(bud, bfull, pfull);
      sum_unit(acc[2], pb + 2 * 6144);
      if (hw == 0) sum_unit(acc[3], pb + 3 * 6144);
      __syncwarp();
      mbar_arrive_if0(BAR_PFREE + (j & 1) * 8, lane);
      if (j == DONE_J && hw == 2 && item >= ORING) flag_wait(bud, &g_done[(item - ORING) >> 4], (epoch + 1) * N_OCTA);
    }
    bool bad = false;
    const uint32_t la = SB + OFF_L + (((r & 7) >> 1) * 40 + 2 * (r >> 3) + (r & 1) + 4 * hw) * 4;
#pragma unroll
    for (int u = 0; u < 4; u++) {
      const float l = acc[u] + __shfl_xor_sync(0xffffffffu, acc[u], 1);
      if (u < 3 || hw == 0) {
        bad |= !(l >= 8.8817841970012523e-16f && l <= 1.125899906842624e15f);
        float inv;
        asm("rcp.approx.ftz.f32 %0, %1;" : "=f"(inv) : "f"(l));
        asm volatile("st.shared.f32 [%0], %1;" ::"r"(la + u * 48), "f"(inv) : "memory");
      }
    }
    publish_generic(BAR_LFULL, lane);
    if (lane == 0) TLP(40 + hw * 4);
    uint32_t anybad;
    asm volatile("{\n.reg .pred p, q;\nsetp.ne.u32 p, %1, 0;\nbarrier.red.or.pred q, 7, 96, p;\nselp.u32 %0, 1, 0, q;\n}\n"
                 : "=r"(anybad) : "r"((uint32_t)bad) : "memory");
    if (__any_sync(0xffffffffu, anybad)) {
      mbar_wait(bud, BAR_OFULL, par);
      slow_item(p, item, hw);
      bar_sync(7, 96);
    }
    if (hw == 1) {
      mbar_wait(bud, BAR_OFULL, par);
      if ((tid_x() & 31) == 0) {
        TLP(41 + hw * 4);
        asm volatile("red.release.gpu.global.add.s32 [%0], 1;" ::"l"(&g_ready[item]) : "memory");
        TLP(42 + hw * 4);
      }
      __syncwarp();
    }
  }
}

__device__ __forceinline__ void attn_producer(const Params& p, const Sched& sc) {
  int bud = WAIT_BUDGET;
  uint32_t sa = 0, pa = 1;
  uint64_t pol;
  asm volatile("createpolicy.fractional.L2::evict_first.b64 %0, 1.0;" : "=l"(pol));
  if (sc.delay) {
    const long long t0 = clock64();
    while (clock64() - t0 < sc.delay) __nanosleep(100);
  }
#pragma unroll 1
  for (int it = 0; it < sc.n; it++) {
    const int item = sched_item(sc, it);
    const int blk = item >> 9, h = (item >> 4) & 31, b = item & 15;
    const int row0 = (b * NH + h) * SK;
#pragma unroll
    for (int c = 0; c < 10; c++) {
      mbar_wait(bud, BAR_EMPTYA + sa * 8, pa);
      TLP(c);
      mbar_expect(BAR_FULLA + sa * 8, A_SLOT + B_SLOT);
      tma3d(A_ADDR(sa), &p.wq[blk], BAR_FULLA + sa * 8, 0, c * 64, h * 3);
      mbar_wait(bud, BAR_EMPTYB + xs(c) * 8, c < NSLOT);
      TLP(10 + c);
      tma2d(B_ADDR(xs(c)), &p.x[blk], BAR_FULLA + sa * 8, c * 64, b * SQ);
      if (++sa == NSLOT) { sa = 0; pa ^= 1; }
    }
#pragma unroll
    for (int i = 0; i < 16; i++) {
      const bool isK = (i == 0) || ((i & 1) && i < 15);
      const int j = i == 0 ? 0 : (i == 15 ? 7 : (isK ? (i + 1) >> 1 : (i - 2) >> 1));
      mbar_wait(bud, BAR_EMPTYA + sa * 8, pa);
      TLP(20 + i);
      mbar_expect(BAR_FULLA + sa * 8, A_SLOT);
      tma3d_hint(A_ADDR(sa), isK ? &p.k[blk] : &p.v[blk], BAR_FULLA + sa * 8, 0, row0 + j * 64, 0, pol);
      if (++sa == NSLOT) { sa = 0; pa ^= 1; }
    }
  }
}

template <int W>
__device__ __forceinline__ void oproj_consumer() {
  int bud = WAIT_BUDGET;
  const int tid = threadIdx.x & 127, lane = tid & 31, warp = tid >> 5;
  const int qrow = 8 * ((lane >> 1) & 1) + 4 * (lane >> 4) + 2 * ((lane >> 2) & 1) + (lane & 1);
  const uint32_t st_off = qrow * 128 + (((2 * warp + ((lane >> 3) & 1)) ^ (qrow & 7)) << 4);
  float a0[64], a1[64], ah[32];
  zero_regs(a0); zero_regs(a1); zero_regs(ah);
#pragma unroll 1
  for (int blk = 0; blk < 2; blk++) {
    int c3 = 0, step = blk * NH;
#pragma unroll 1
    for (int c = 0; c < 96; c++) {
      const uint32_t st = c & 3;
      mbar_wait(bud, BAR_GFULL + st * 8, (c >> 2) & 1);
      wg_fence();
      const uint32_t la = lo_sw(SB + st * O_STAGE), lb = lo_o(SB + st * O_STAGE + O_AB);
#define O_STEP(ks, sc)                                                   \
  mma64r<1, 1, 2 * 8192 + ks * 2048, W * 8192 + ks * 512>(ah, la, lb, sc);    \
  mma128r<1, 1, (W * 3) * 8192 + ks * 2048, ks * 512>(a0, la, lb, sc);        \
  mma128r<1, 1, (W * 3 + 1) * 8192 + ks * 2048, ks * 512>(a1, la, lb, sc);
      O_STEP(0, c != 0) O_STEP(1, 1) O_STEP(2, 1) O_STEP(3, 1)
#undef O_STEP
      wg_commit();
      if (++c3 == 3) {
        c3 = 0;
        if (W == 0)
          asm volatile("{\n.reg .pred p;\nsetp.eq.u32 p, %1, 0;\n@p red.relaxed.gpu.global.add.s32 [%0], 1;\n}\n" ::"l"(&g_done[step]), "r"(tid) : "memory");
        TL(step);
        step++;
      }
      wg_wait<1>();
      mbar_arrive_if0(BAR_GEMPTY + ((c - 1) & 3) * 8, tid | (c == 0) | (c == 95));
    }
    wg_wait<0>();
    reg_fence(a0); reg_fence(a1); reg_fence(ah);
    bar_sync(3, 256);
    const uint32_t sg = SB + 2 * O_STAGE + st_off;
    store_scaled(sg + 2 * 16384 + W * 8192, ah, 1.0f);
    store_scaled(sg + (W * 3) * 16384, a0, 1.0f);
    store_scaled(sg + (W * 3 + 1) * 16384, a1, 1.0f);
    publish(BAR_GOUT, lane);
  }
  TL_FLUSH();
}

__device__ __forceinline__ void oproj_producer(const Params& p, int cta, int target) {
  int bud = WAIT_BUDGET;
  const int half = cta & 1, r0 = (cta >> 1) * 128;
  const int b0 = r0 / SQ, off0 = r0 - b0 * SQ, n0 = min(128, SQ - off0), n1 = 128 - n0;
#pragma unroll 1
  for (int step = 0; step < 2 * NH; step++) {
    const int blk = step >> 5, item0 = step * 16 + b0;
    const char* o0 = (const char*)g_o + (size_t)(item0 % ORING) * O_ITEM_BYTES + off0 * 128;
    const char* o1 = (const char*)g_o + (size_t)((item0 + 1) % ORING) * O_ITEM_BYTES;
#pragma unroll 1
    for (int kb = 0; kb < 3; kb++) {
      const int c = step * 3 + kb;
      const uint32_t st = c & 3, dst = SB + st * O_STAGE, bar = BAR_GFULL + st * 8;
      mbar_wait(bud, BAR_GEMPTY + st * 8, ((c >> 2) & 1) ^ 1);
      mbar_expect(bar, O_STAGE);
      tma3d(dst, &p.wo[blk], bar, 0, ((step & 31) * 3 + kb) * 64, half * 5);
      if (kb == 0) {
        flag_wait(bud, &g_ready[item0], target);
        if (n1) flag_wait(bud, &g_ready[item0 + 1], target);
        asm volatile("fence.proxy.async.global;" ::: "memory");
      }
      bulk_load(dst + O_AB, o0 + kb * B_SLOT, n0 * 128, bar);
      if (n1) bulk_load(dst + O_AB + n0 * 128, o1 + kb * B_SLOT, n1 * 128, bar);
    }
  }
}

__device__ __forceinline__ void oproj_storer(const Params& p, int cta) {
  int bud = WAIT_BUDGET;
  const int half = cta & 1, r0 = (cta >> 1) * 128;
#pragma unroll 1
  for (int blk = 0; blk < 2; blk++) {
    mbar_wait(bud, BAR_GOUT, blk);
    for (int k = 0; k < 5; k++) tma_store2d(&p.out, SB + 2 * O_STAGE + k * 16384, blk * DM + half * 320 + k * 64, r0);
    asm volatile("cp.async.bulk.commit_group;" ::: "memory");
    asm volatile("cp.async.bulk.wait_group.read 0;" ::: "memory");
    mbar_arrive2_if0(BAR_GEMPTY + 16, 0);
    mbar_arrive2_if0(BAR_GEMPTY + 24, 0);
  }
  asm volatile("cp.async.bulk.wait_group 0;" ::: "memory");
}

__global__ void __launch_bounds__(384, 1) fused_kernel(const __grid_constant__ Params p) {
  extern __shared__ __align__(1024) char smem_raw[];
  if ((smem_u32(smem_raw) & 0xFFFFFFu) != SB) return;
  const int cta = blockIdx.x;
  const int warp = __shfl_sync(0xffffffffu, threadIdx.x >> 5, 0);
  if (threadIdx.x == 0) {
    for (int i = 0; i < NSLOT; i++) { mbar_init(BAR_FULLA + i * 8, 1); mbar_init(BAR_EMPTYA + i * 8, 2); mbar_init(BAR_EMPTYB + i * 8, 2); }
    proxy_fence();
  }
  if (threadIdx.x == 64) {
    mbar_init(BAR_XDONE, 1); mbar_init(BAR_QH, 4); mbar_init(BAR_QM, 4);
    mbar_init(BAR_PFULL, 4); mbar_init(BAR_PFULL + 8, 4); mbar_init(BAR_PFREE, 3); mbar_init(BAR_PFREE + 8, 3);
    mbar_init(BAR_LFULL, 3); mbar_init(BAR_PMID, 4); mbar_init(BAR_PMID + 8, 4); mbar_init(BAR_OFULL, 8);
  }
  if (threadIdx.x == 96) {
    for (int i = 0; i < O_NST; i++) { mbar_init(BAR_GFULL + i * 8, 1); mbar_init(BAR_GEMPTY + i * 8, 2); }
    mbar_init(BAR_GOUT, 8);
    proxy_fence();
  }
  if (warp == 1 && threadIdx.x < 32 + 11) asm volatile("prefetch.tensormap [%0];" ::"l"(&p.x[0] + (threadIdx.x - 32)) : "memory");
  __syncthreads();
  const Sched sc = get_sched(cta);
  if (warp >= 8) {
    asm volatile("setmaxnreg.dec.sync.aligned.u32 40;");
    if (warp == 8) {
      if (elect_one()) attn_producer(p, sc);
      __syncwarp();
    } else {
      const int epoch = *(volatile int*)&g_epoch[cta];
      attn_helper(p, warp - 9, sc, epoch);
      if (warp == 11 && elect_one()) *(volatile int*)&g_epoch[cta] = epoch + 1;
    }
    if (cta < N_OCTA) {
      bar_sync(4, 128);
      if (warp == 8) {
        if (elect_one()) oproj_producer(p, cta, *(volatile int*)&g_epoch[cta]);
      } else if (warp == 9) {
        if (elect_one()) oproj_storer(p, cta);
      }
    }
  } else {
    asm volatile("setmaxnreg.inc.sync.aligned.u32 232;");
    if (warp < 4) {
      attn_consumer<0>(sc);
      if (cta < N_OCTA) oproj_consumer<0>();
    } else {
      attn_consumer<1>(sc);
      if (cta < N_OCTA) oproj_consumer<1>();
    }
  }
}

typedef CUresult (*EncodeFn)(CUtensorMap*, CUtensorMapDataType, cuuint32_t, void*, const cuuint64_t*, const cuuint64_t*, const cuuint32_t*,
                             const cuuint32_t*, CUtensorMapInterleave, CUtensorMapSwizzle, CUtensorMapL2promotion, CUtensorMapFloatOOBfill);

void make3d(EncodeFn enc, CUtensorMap* m, const void* ptr, uint64_t rows, uint64_t cols, uint32_t box_rows, uint32_t box_blocks,
            CUtensorMapL2promotion promo = CU_TENSOR_MAP_L2_PROMOTION_L2_128B) {
  cuuint64_t gd[3] = {64, rows, cols / 64};
  cuuint64_t gs[2] = {cols * 2, 128};
  cuuint32_t bd[3] = {64, box_rows, box_blocks}, es[3] = {1, 1, 1};
  enc(m, CU_TENSOR_MAP_DATA_TYPE_BFLOAT16, 3, (void*)ptr, gd, gs, bd, es, CU_TENSOR_MAP_INTERLEAVE_NONE, CU_TENSOR_MAP_SWIZZLE_128B,
      promo, CU_TENSOR_MAP_FLOAT_OOB_FILL_NONE);
}
void make2d(EncodeFn enc, CUtensorMap* m, const void* ptr, uint64_t rows, uint64_t cols, uint32_t box_rows) {
  cuuint64_t gd[2] = {cols, rows};
  cuuint64_t gs[1] = {cols * 2};
  cuuint32_t bd[2] = {64, box_rows}, es[2] = {1, 1};
  enc(m, CU_TENSOR_MAP_DATA_TYPE_BFLOAT16, 2, (void*)ptr, gd, gs, bd, es, CU_TENSOR_MAP_INTERLEAVE_NONE, CU_TENSOR_MAP_SWIZZLE_128B,
      CU_TENSOR_MAP_L2_PROMOTION_L2_128B, CU_TENSOR_MAP_FLOAT_OOB_FILL_NONE);
}

}

extern "C" void kernel_launch(void* const* d_in, const int* in_sizes, int n_in, void* d_out, int out_size) {
  static EncodeFn enc = nullptr;
  if (!enc) {
    cudaDriverEntryPointQueryResult qr;
    cudaGetDriverEntryPoint("cuTensorMapEncodeTiled", (void**)&enc, cudaEnableDefault, &qr);
    cudaFuncSetAttribute(fused_kernel, cudaFuncAttributeMaxDynamicSharedMemorySize, SMEM_BYTES);
  }
  Params p;
  for (int s = 0; s < 2; s++) {
    make2d(enc, &p.x[s], d_in[5 * s + 0], NB * SQ, DM, SQ);
    make3d(enc, &p.k[s], d_in[5 * s + 1], (uint64_t)NB * NH * SK, DH, 64, 3);
    make3d(enc, &p.v[s], d_in[5 * s + 2], (uint64_t)NB * NH * SK, DH, 64, 3);
    make3d(enc, &p.wq[s], d_in[5 * s + 3], DM, NH * DH, 64, 3);
    make3d(enc, &p.wo[s], d_in[5 * s + 4], NH * DH, DM, 64, 5);
    p.xp[s] = (const __nv_bfloat16*)d_in[5 * s + 0];
    p.wqp[s] = (const __nv_bfloat16*)d_in[5 * s + 3];
    p.kp[s] = (const __nv_bfloat16*)d_in[5 * s + 1];
    p.vp[s] = (const __nv_bfloat16*)d_in[5 * s + 2];
  }
  make2d(enc, &p.out, d_out, NB * SQ, 2 * DM, 128);
  fused_kernel<<<NCTA, 384, SMEM_BYTES>>>(p);
}
```

```cpp
#include <cuda_runtime.h>
#include <cuda_bf16.h>
#include <cuda.h>
#include <stdint.h>

#define DEBUG_TIMEOUT 0

namespace {

constexpr int SQ = 160, DM = 640, NH = 32, SK = 512, DH = 192, NB = 16;
constexpr int NITEMS = 2 * NB * NH;
constexpr int NCTA = 132, N_OCTA = 40, N_G2 = 28, N_G1 = 64, N_ATT = N_G1 + N_G2;
constexpr int ORING = 128, STAG_A0 = 15, STAG_SLOPE = 240, O_DELAY = 0, O_SLOPE = 0, G2_EXTRA = 0, DONE_J = 5, PERM_M = 41, O_PAIR = 0, DYN = 1;
constexpr int PF_N = 40, PF_WAIT = 1500, PF_GAP = 300;
constexpr int ORING_MAX = ORING;
#define W1_NG 3
constexpr int A_SLOT = 24576, B_SLOT = 20480, NSLOT = 5;
constexpr int OFF_A = 0;
constexpr int OFF_B = NSLOT * A_SLOT;
constexpr int O_STAGE = 57344, O_AB = 40960, O_NST = 4;
constexpr int OFF_L = O_NST * O_STAGE;
constexpr int OFF_BAR = OFF_L + 160 * 4;
constexpr int SMEM_BYTES = OFF_BAR + 384 + 512;
static_assert(OFF_B + NSLOT * B_SLOT <= OFF_L, "smem layout");
constexpr uint32_t SB = 1024;
constexpr uint32_t BARS = SB + OFF_BAR;
constexpr uint32_t BAR_FULLA = BARS, BAR_EMPTYA = BARS + 40, BAR_PMID = BARS + 80, BAR_EMPTYB = BARS + 120, BAR_XDONE = BARS + 160,
                   BAR_QH = BARS + 168, BAR_QM = BARS + 96, BAR_PFULL = BARS + 184, BAR_PFREE = BARS + 200, BAR_LFULL = BARS + 216,
                   BAR_OFULL = BARS + 224, BAR_GFULL = BARS + 248, BAR_GEMPTY = BARS + 280, BAR_GOUT = BARS + 312, NEXT_ITEM = BARS + 320;
constexpr int O_ITEM_BYTES = SQ * DH * 2;

struct alignas(64) Params {
  CUtensorMap x[2], wq[2], k[2], v[2], wo[2], out;
  const __nv_bfloat16 *xp[2], *wqp[2], *kp[2], *vp[2];
};

__device__ uint4 g_o[(size_t)ORING_MAX * O_ITEM_BYTES / 16];
__device__ int g_ready[NITEMS];
__device__ int g_done[2 * NH];
__device__ unsigned g_ticket;
__device__ int g_epoch[NCTA];

#define TLP(id)
#define TLG(id)
#define TL(id)
#define TL_FLUSH()
__device__ __forceinline__ uint32_t smem_u32(const void* p) { return (uint32_t)__cvta_generic_to_shared(p); }
__device__ __forceinline__ void wg_fence() { asm volatile("wgmma.fence.sync.aligned;" ::: "memory"); }
__device__ __forceinline__ void wg_commit() { asm volatile("wgmma.commit_group.sync.aligned;" ::: "memory"); }
template <int N> __device__ __forceinline__ void wg_wait() { asm volatile("wgmma.wait_group.sync.aligned %0;" ::"n"(N) : "memory"); }
template <int N> __device__ __forceinline__ void reg_fence(float (&d)[N]) {
#pragma unroll
  for (int i = 0; i < N; i++) asm volatile("" : "+f"(d[i])::"memory");
}
template <int N> __device__ __forceinline__ void zero_regs(float (&d)[N]) {
#pragma unroll
  for (int i = 0; i < N; i++) d[i] = 0.f;
}
__device__ __forceinline__ void proxy_fence() { asm volatile("fence.proxy.async.shared::cta;" ::: "memory"); }
__device__ __forceinline__ void mbar_init(uint32_t bar, int cnt) { asm volatile("mbarrier.init.shared::cta.b64 [%0], %1;" ::"r"(bar), "r"(cnt) : "memory"); }
__device__ __forceinline__ void mbar_arrive_if0(uint32_t bar, uint32_t sel) {
  asm volatile("{\n.reg .pred p;\nsetp.eq.u32 p, %1, 0;\n@p mbarrier.arrive.shared::cta.b64 _, [%0];\n}\n" ::"r"(bar), "r"(sel) : "memory");
}
__device__ __forceinline__ void mbar_arrive2_if0(uint32_t bar, uint32_t sel) {
  asm volatile("{\n.reg .pred p;\nsetp.eq.u32 p, %1, 0;\n@p mbarrier.arrive.shared::cta.b64 _, [%0], 2;\n}\n" ::"r"(bar), "r"(sel) : "memory");
}
__device__ __forceinline__ void mbar_expect(uint32_t bar, uint32_t bytes) {
  asm volatile("mbarrier.arrive.expect_tx.shared::cta.b64 _, [%0], %1;" ::"r"(bar), "r"(bytes) : "memory");
}
__device__ __forceinline__ void mbar_wait(int& bud, uint32_t bar, uint32_t parity) {
  asm volatile(
      "{\n.reg .pred p;\n"
      "LW:\n"
      "mbarrier.try_wait.parity.shared::cta.b64 p, [%0], %1;\n"
      "@!p bra LW;\n}\n" ::"r"(bar), "r"(parity) : "memory");
}
constexpr int WAIT_BUDGET = 1 << 22;
__device__ __forceinline__ bool elect_one() {
  uint32_t p;
  asm volatile("{\n.reg .pred p;\nelect.sync _|p, 0xffffffff;\nselp.u32 %0, 1, 0, p;\n}\n" : "=r"(p));
  return p;
}
__device__ __forceinline__ void tma2d(uint32_t dst, const CUtensorMap* m, uint32_t bar, int c0, int c1) {
  asm volatile("cp.async.bulk.tensor.2d.shared::cluster.global.mbarrier::complete_tx::bytes [%0], [%1, {%3, %4}], [%2];"
               ::"r"(dst), "l"(m), "r"(bar), "r"(c0), "r"(c1) : "memory");
}
__device__ __forceinline__ void tma3d(uint32_t dst, const CUtensorMap* m, uint32_t bar, int c0, int c1, int c2) {
  asm volatile("cp.async.bulk.tensor.3d.shared::cluster.global.mbarrier::complete_tx::bytes [%0], [%1, {%3, %4, %5}], [%2];"
               ::"r"(dst), "l"(m), "r"(bar), "r"(c0), "r"(c1), "r"(c2) : "memory");
}
__device__ __forceinline__ void tma3d_hint(uint32_t dst, const CUtensorMap* m, uint32_t bar, int c0, int c1, int c2, uint64_t pol) {
  asm volatile("cp.async.bulk.tensor.3d.shared::cluster.global.mbarrier::complete_tx::bytes.L2::cache_hint [%0], [%1, {%3, %4, %5}], [%2], %6;"
               ::"r"(dst), "l"(m), "r"(bar), "r"(c0), "r"(c1), "r"(c2), "l"(pol) : "memory");
}
__device__ __forceinline__ void bulk_load(uint32_t dst, const void* src, uint32_t bytes, uint32_t bar) {
  asm volatile("cp.async.bulk.shared::cluster.global.mbarrier::complete_tx::bytes [%0], [%1], %2, [%3];"
               ::"r"(dst), "l"(src), "r"(bytes), "r"(bar) : "memory");
}
__device__ __forceinline__ void tma_store2d(const CUtensorMap* m, uint32_t src, int c0, int c1) {
  asm volatile("cp.async.bulk.tensor.2d.global.shared::cta.bulk_group [%0, {%2, %3}], [%1];" ::"l"(m), "r"(src), "r"(c0), "r"(c1) : "memory");
}
__device__ __forceinline__ void bar_sync(int id, int n) { asm volatile("bar.sync %0, %1;" ::"r"(id), "r"(n) : "memory"); }
__device__ __forceinline__ void bar_arrive(int id, int n) { asm volatile("bar.arrive %0, %1;" ::"r"(id), "r"(n) : "memory"); }
__device__ __forceinline__ float ex2(float x) { float y; asm("ex2.approx.ftz.f32 %0, %1;" : "=f"(y) : "f"(x)); return y; }
__device__ __forceinline__ uint32_t pack2(float lo, float hi) { uint32_t r; asm("cvt.rn.bf16x2.f32 %0, %1, %2;" : "=r"(r) : "f"(hi), "f"(lo)); return r; }
__device__ __forceinline__ void stsm_t(uint32_t a, uint32_t r0, uint32_t r1, uint32_t r2, uint32_t r3) {
  asm volatile("stmatrix.sync.aligned.m8n8.x4.trans.shared.b16 [%0], {%1,%2,%3,%4};" ::"r"(a), "r"(r0), "r"(r1), "r"(r2), "r"(r3) : "memory");
}
__device__ __forceinline__ void flag_wait(int& bud, const int* p, int target) {
  while (true) {
    int v;
    asm volatile("ld.acquire.gpu.global.s32 %0, [%1];" : "=r"(v) : "l"(p) : "memory");
    if (v - target >= 0 || --bud <= 0) break;
    __nanosleep(64);
  }
}
__device__ __forceinline__ uint32_t lo_sw(uint32_t addr) { return (addr >> 4) | (1u << 16); }
__device__ __forceinline__ uint32_t lo_o(uint32_t addr) { return (addr >> 4) | (128u << 16); }
__device__ __forceinline__ uint32_t tid_x() { uint32_t t; asm volatile("mov.u32 %0, %tid.x;" : "=r"(t)); return t; }
__device__ __forceinline__ uint32_t opaque(uint32_t x) { uint32_t y; asm volatile("mov.u32 %0, %1;" : "=r"(y) : "r"(x)); return y; }

template <int TA, int TB, uint32_t OA, uint32_t OB>
__device__ __forceinline__ void mma160(float (&d)[80], uint32_t la, uint32_t lb) {
  asm volatile(
      "{\n.reg .pred p;\n.reg .b32 a, b;\n.reg .b64 da, db;\nsetp.eq.b32 p, 0, 0;\n"
      "add.u32 a, %80, %84;\nadd.u32 b, %81, %85;\nmov.b64 da, {a, 0x40000040};\nmov.b64 db, {b, %86};\n"
      "wgmma.mma_async.sync.aligned.m64n160k16.f32.bf16.bf16 {"
      "%0,%1,%2,%3,%4,%5,%6,%7,%8,%9,%10,%11,%12,%13,%14,%15,%16,%17,%18,%19,%20,%21,%22,%23,%24,%25,%26,%27,%28,%29,%30,%31,%32,%33,%34,%35,%36,"
      "%37,%38,%39,%40,%41,%42,%43,%44,%45,%46,%47,%48,%49,%50,%51,%52,%53,%54,%55,%56,%57,%58,%59,%60,%61,%62,%63,%64,%65,%66,%67,%68,%69,%70,%71,"
      "%72,%73,%74,%75,%76,%77,%78,%79"
      "}, da, db, p, 1, 1, %82, %83;\n}\n"
      :
      "+f"(d[0]),"+f"(d[1]),"+f"(d[2]),"+f"(d[3]),"+f"(d[4]),"+f"(d[5]),"+f"(d[6]),"+f"(d[7]),"+f"(d[8]),"+f"(d[9]),"+f"(d[10]),"+f"(d[11]),
      "+f"(d[12]),"+f"(d[13]),"+f"(d[14]),"+f"(d[15]),"+f"(d[16]),"+f"(d[17]),"+f"(d[18]),"+f"(d[19]),"+f"(d[20]),"+f"(d[21]),"+f"(d[22]),
      "+f"(d[23]),"+f"(d[24]),"+f"(d[25]),"+f"(d[26]),"+f"(d[27]),"+f"(d[28]),"+f"(d[29]),"+f"(d[30]),"+f"(d[31]),"+f"(d[32]),"+f"(d[33]),
      "+f"(d[34]),"+f"(d[35]),"+f"(d[36]),"+f"(d[37]),"+f"(d[38]),"+f"(d[39]),"+f"(d[40]),"+f"(d[41]),"+f"(d[42]),"+f"(d[43]),"+f"(d[44]),
      "+f"(d[45]),"+f"(d[46]),"+f"(d[47]),"+f"(d[48]),"+f"(d[49]),"+f"(d[50]),"+f"(d[51]),"+f"(d[52]),"+f"(d[53]),"+f"(d[54]),"+f"(d[55]),
      "+f"(d[56]),"+f"(d[57]),"+f"(d[58]),"+f"(d[59]),"+f"(d[60]),"+f"(d[61]),"+f"(d[62]),"+f"(d[63]),"+f"(d[64]),"+f"(d[65]),"+f"(d[66]),
      "+f"(d[67]),"+f"(d[68]),"+f"(d[69]),"+f"(d[70]),"+f"(d[71]),"+f"(d[72]),"+f"(d[73]),"+f"(d[74]),"+f"(d[75]),"+f"(d[76]),"+f"(d[77]),
      "+f"(d[78]),"+f"(d[79])
      : "r"(la), "r"(lb), "n"(TA), "n"(TB), "n"(OA >> 4), "n"(OB >> 4), "n"(TB ? 0xC0000010u : 0x40000040u));
}

template <int TA, int TB, uint32_t OA, uint32_t OB>
__device__ __forceinline__ void mma160z(float (&d)[80], uint32_t la, uint32_t lb) {
  asm volatile(
      "{\n.reg .pred p;\n.reg .b32 a, b;\n.reg .b64 da, db;\nsetp.ne.b32 p, 0, 0;\n"
      "add.u32 a, %80, %84;\nadd.u32 b, %81, %85;\nmov.b64 da, {a, 0x40000040};\nmov.b64 db, {b, %86};\n"
      "wgmma.mma_async.sync.aligned.m64n160k16.f32.bf16.bf16 {"
      "%0,%1,%2,%3,%4,%5,%6,%7,%8,%9,%10,%11,%12,%13,%14,%15,%16,%17,%18,%19,%20,%21,%22,%23,%24,%25,%26,%27,%28,%29,%30,%31,%32,%33,%34,%35,%36,"
      "%37,%38,%39,%40,%41,%42,%43,%44,%45,%46,%47,%48,%49,%50,%51,%52,%53,%54,%55,%56,%57,%58,%59,%60,%61,%62,%63,%64,%65,%66,%67,%68,%69,%70,%71,"
      "%72,%73,%74,%75,%76,%77,%78,%79"
      "}, da, db, p, 1, 1, %82, %83;\n}\n"
      :
      "=f"(d[0]),"=f"(d[1]),"=f"(d[2]),"=f"(d[3]),"=f"(d[4]),"=f"(d[5]),"=f"(d[6]),"=f"(d[7]),"=f"(d[8]),"=f"(d[9]),"=f"(d[10]),"=f"(d[11]),
      "=f"(d[12]),"=f"(d[13]),"=f"(d[14]),"=f"(d[15]),"=f"(d[16]),"=f"(d[17]),"=f"(d[18]),"=f"(d[19]),"=f"(d[20]),"=f"(d[21]),"=f"(d[22]),
      "=f"(d[23]),"=f"(d[24]),"=f"(d[25]),"=f"(d[26]),"=f"(d[27]),"=f"(d[28]),"=f"(d[29]),"=f"(d[30]),"=f"(d[31]),"=f"(d[32]),"=f"(d[33]),
      "=f"(d[34]),"=f"(d[35]),"=f"(d[36]),"=f"(d[37]),"=f"(d[38]),"=f"(d[39]),"=f"(d[40]),"=f"(d[41]),"=f"(d[42]),"=f"(d[43]),"=f"(d[44]),
      "=f"(d[45]),"=f"(d[46]),"=f"(d[47]),"=f"(d[48]),"=f"(d[49]),"=f"(d[50]),"=f"(d[51]),"=f"(d[52]),"=f"(d[53]),"=f"(d[54]),"=f"(d[55]),
      "=f"(d[56]),"=f"(d[57]),"=f"(d[58]),"=f"(d[59]),"=f"(d[60]),"=f"(d[61]),"=f"(d[62]),"=f"(d[63]),"=f"(d[64]),"=f"(d[65]),"=f"(d[66]),
      "=f"(d[67]),"=f"(d[68]),"=f"(d[69]),"=f"(d[70]),"=f"(d[71]),"=f"(d[72]),"=f"(d[73]),"=f"(d[74]),"=f"(d[75]),"=f"(d[76]),"=f"(d[77]),
      "=f"(d[78]),"=f"(d[79])
      : "r"(la), "r"(lb), "n"(TA), "n"(TB), "n"(OA >> 4), "n"(OB >> 4), "n"(TB ? 0xC0000010u : 0x40000040u));
}

template <int TA, int TB, uint32_t OA, uint32_t OB>
__device__ __forceinline__ void mma80(float (&d)[40], uint32_t la, uint32_t lb) {
  asm volatile(
      "{\n.reg .pred p;\n.reg .b32 a, b;\n.reg .b64 da, db;\nsetp.eq.b32 p, 0, 0;\n"
      "add.u32 a, %40, %44;\nadd.u32 b, %41, %45;\nmov.b64 da, {a, 0x40000040};\nmov.b64 db, {b, %46};\n"
      "wgmma.mma_async.sync.aligned.m64n80k16.f32.bf16.bf16 {"
      "%0,%1,%2,%3,%4,%5,%6,%7,%8,%9,%10,%11,%12,%13,%14,%15,%16,%17,%18,%19,%20,%21,%22,%23,%24,%25,%26,%27,%28,%29,%30,%31,%32,%33,%34,%35,%36,"
      "%37,%38,%39"
      "}, da, db, p, 1, 1, %42, %43;\n}\n"
      :
      "+f"(d[0]),"+f"(d[1]),"+f"(d[2]),"+f"(d[3]),"+f"(d[4]),"+f"(d[5]),"+f"(d[6]),"+f"(d[7]),"+f"(d[8]),"+f"(d[9]),"+f"(d[10]),"+f"(d[11]),
      "+f"(d[12]),"+f"(d[13]),"+f"(d[14]),"+f"(d[15]),"+f"(d[16]),"+f"(d[17]),"+f"(d[18]),"+f"(d[19]),"+f"(d[20]),"+f"(d[21]),"+f"(d[22]),
      "+f"(d[23]),"+f"(d[24]),"+f"(d[25]),"+f"(d[26]),"+f"(d[27]),"+f"(d[28]),"+f"(d[29]),"+f"(d[30]),"+f"(d[31]),"+f"(d[32]),"+f"(d[33]),
      "+f"(d[34]),"+f"(d[35]),"+f"(d[36]),"+f"(d[37]),"+f"(d[38]),"+f"(d[39])
      : "r"(la), "r"(lb), "n"(TA), "n"(TB), "n"(OA >> 4), "n"(OB >> 4), "n"(TB ? 0xC0000010u : 0x40000040u));
}

template <int TA, int TB, uint32_t OA, uint32_t OB>
__device__ __forceinline__ void mma80z(float (&d)[40], uint32_t la, uint32_t lb) {
  asm volatile(
      "{\n.reg .pred p;\n.reg .b32 a, b;\n.reg .b64 da, db;\nsetp.ne.b32 p, 0, 0;\n"
      "add.u32 a, %40, %44;\nadd.u32 b, %41, %45;\nmov.b64 da, {a, 0x40000040};\nmov.b64 db, {b, %46};\n"
      "wgmma.mma_async.sync.aligned.m64n80k16.f32.bf16.bf16 {"
      "%0,%1,%2,%3,%4,%5,%6,%7,%8,%9,%10,%11,%12,%13,%14,%15,%16,%17,%18,%19,%20,%21,%22,%23,%24,%25,%26,%27,%28,%29,%30,%31,%32,%33,%34,%35,%36,"
      "%37,%38,%39"
      "}, da, db, p, 1, 1, %42, %43;\n}\n"
      :
      "=f"(d[0]),"=f"(d[1]),"=f"(d[2]),"=f"(d[3]),"=f"(d[4]),"=f"(d[5]),"=f"(d[6]),"=f"(d[7]),"=f"(d[8]),"=f"(d[9]),"=f"(d[10]),"=f"(d[11]),
      "=f"(d[12]),"=f"(d[13]),"=f"(d[14]),"=f"(d[15]),"=f"(d[16]),"=f"(d[17]),"=f"(d[18]),"=f"(d[19]),"=f"(d[20]),"=f"(d[21]),"=f"(d[22]),
      "=f"(d[23]),"=f"(d[24]),"=f"(d[25]),"=f"(d[26]),"=f"(d[27]),"=f"(d[28]),"=f"(d[29]),"=f"(d[30]),"=f"(d[31]),"=f"(d[32]),"=f"(d[33]),
      "=f"(d[34]),"=f"(d[35]),"=f"(d[36]),"=f"(d[37]),"=f"(d[38]),"=f"(d[39])
      : "r"(la), "r"(lb), "n"(TA), "n"(TB), "n"(OA >> 4), "n"(OB >> 4), "n"(TB ? 0xC0000010u : 0x40000040u));
}

template <int TA, int TB, uint32_t OA, uint32_t OB>
__device__ __forceinline__ void mma128r(float (&d)[64], uint32_t la, uint32_t lb, int sc) {
  asm volatile(
      "{\n.reg .pred p;\n.reg .b32 a, b;\n.reg .b64 da, db;\nsetp.ne.b32 p, %71, 0;\n"
      "add.u32 a, %64, %68;\nadd.u32 b, %65, %69;\nmov.b64 da, {a, 0x40000040};\nmov.b64 db, {b, %70};\n"
      "wgmma.mma_async.sync.aligned.m64n128k16.f32.bf16.bf16 {"
      "%0,%1,%2,%3,%4,%5,%6,%7,%8,%9,%10,%11,%12,%13,%14,%15,%16,%17,%18,%19,%20,%21,%22,%23,%24,%25,%26,%27,%28,%29,%30,%31,%32,%33,%34,%35,%36,"
      "%37,%38,%39,%40,%41,%42,%43,%44,%45,%46,%47,%48,%49,%50,%51,%52,%53,%54,%55,%56,%57,%58,%59,%60,%61,%62,%63"
      "}, da, db, p, 1, 1, %66, %67;\n}\n"
      :
      "+f"(d[0]),"+f"(d[1]),"+f"(d[2]),"+f"(d[3]),"+f"(d[4]),"+f"(d[5]),"+f"(d[6]),"+f"(d[7]),"+f"(d[8]),"+f"(d[9]),"+f"(d[10]),"+f"(d[11]),
      "+f"(d[12]),"+f"(d[13]),"+f"(d[14]),"+f"(d[15]),"+f"(d[16]),"+f"(d[17]),"+f"(d[18]),"+f"(d[19]),"+f"(d[20]),"+f"(d[21]),"+f"(d[22]),
      "+f"(d[23]),"+f"(d[24]),"+f"(d[25]),"+f"(d[26]),"+f"(d[27]),"+f"(d[28]),"+f"(d[29]),"+f"(d[30]),"+f"(d[31]),"+f"(d[32]),"+f"(d[33]),
      "+f"(d[34]),"+f"(d[35]),"+f"(d[36]),"+f"(d[37]),"+f"(d[38]),"+f"(d[39]),"+f"(d[40]),"+f"(d[41]),"+f"(d[42]),"+f"(d[43]),"+f"(d[44]),
      "+f"(d[45]),"+f"(d[46]),"+f"(d[47]),"+f"(d[48]),"+f"(d[49]),"+f"(d[50]),"+f"(d[51]),"+f"(d[52]),"+f"(d[53]),"+f"(d[54]),"+f"(d[55]),
      "+f"(d[56]),"+f"(d[57]),"+f"(d[58]),"+f"(d[59]),"+f"(d[60]),"+f"(d[61]),"+f"(d[62]),"+f"(d[63])
      : "r"(la), "r"(lb), "n"(TA), "n"(TB), "n"(OA >> 4), "n"(OB >> 4), "n"(TB ? 0xC0000010u : 0x40000040u), "r"(sc));
}

template <int TA, int TB, uint32_t OA, uint32_t OB>
__device__ __forceinline__ void mma64r(float (&d)[32], uint32_t la, uint32_t lb, int sc) {
  asm volatile(
      "{\n.reg .pred p;\n.reg .b32 a, b;\n.reg .b64 da, db;\nsetp.ne.b32 p, %39, 0;\n"
      "add.u32 a, %32, %36;\nadd.u32 b, %33, %37;\nmov.b64 da, {a, 0x40000040};\nmov.b64 db, {b, %38};\n"
      "wgmma.mma_async.sync.aligned.m64n64k16.f32.bf16.bf16 {"
      "%0,%1,%2,%3,%4,%5,%6,%7,%8,%9,%10,%11,%12,%13,%14,%15,%16,%17,%18,%19,%20,%21,%22,%23,%24,%25,%26,%27,%28,%29,%30,%31"
      "}, da, db, p, 1, 1, %34, %35;\n}\n"
      :
      "+f"(d[0]),"+f"(d[1]),"+f"(d[2]),"+f"(d[3]),"+f"(d[4]),"+f"(d[5]),"+f"(d[6]),"+f"(d[7]),"+f"(d[8]),"+f"(d[9]),"+f"(d[10]),"+f"(d[11]),
      "+f"(d[12]),"+f"(d[13]),"+f"(d[14]),"+f"(d[15]),"+f"(d[16]),"+f"(d[17]),"+f"(d[18]),"+f"(d[19]),"+f"(d[20]),"+f"(d[21]),"+f"(d[22]),
      "+f"(d[23]),"+f"(d[24]),"+f"(d[25]),"+f"(d[26]),"+f"(d[27]),"+f"(d[28]),"+f"(d[29]),"+f"(d[30]),"+f"(d[31])
      : "r"(la), "r"(lb), "n"(TA), "n"(TB), "n"(OA >> 4), "n"(OB >> 4), "n"(TB ? 0xC0000010u : 0x40000040u), "r"(sc));
}

struct Ring { uint32_t s0, ph0; };
__device__ __forceinline__ void ring_pos(const Ring& r, int i, uint32_t& slot, uint32_t& ph) {
  uint32_t s = opaque(r.s0) + (i % NSLOT);
  uint32_t wrap = s >= NSLOT;
  slot = s - (wrap ? NSLOT : 0);
  ph = r.ph0 ^ ((i / NSLOT) & 1) ^ wrap;
}
__device__ __forceinline__ void ring_advance(Ring& r, int n) {
  uint32_t s, p;
  ring_pos(r, n, s, p);
  r.s0 = s; r.ph0 = p;
}
__host__ __device__ constexpr int idxK(int j) { return j == 0 ? 10 : 9 + 2 * j; }
__host__ __device__ constexpr int idxV(int j) { return j == 7 ? 25 : 12 + 2 * j; }
__host__ __device__ constexpr int xs(int c) { return c % NSLOT; }

__device__ __forceinline__ int start_delay(int cta) {
  if (cta < N_OCTA) return O_DELAY + cta * O_SLOPE;
  const int a = cta - N_OCTA;
  return max(0, (a | 1) - STAG_A0) * STAG_SLOPE + (a < N_G1 ? 0 : G2_EXTRA);
}
__device__ __forceinline__ int next_item(uint32_t a = NEXT_ITEM) {
  int v;
  asm volatile("ld.shared.s32 %0, [%1];" : "=r"(v) : "r"(a) : "memory");
  return __shfl_sync(0xffffffffu, v, 0);
}

template <int W, bool ACC>
__device__ __forceinline__ void mma_main(float (&d)[80], uint32_t aaddr, uint32_t baddr) {
  const uint32_t la = lo_sw(aaddr), lb = lo_sw(baddr);
  if (ACC) mma160<1, 0, W * 16384, 0>(d, la, lb); else mma160z<1, 0, W * 16384, 0>(d, la, lb);
  mma160<1, 0, W * 16384 + 1 * 2048, 1 * 32>(d, la, lb);
  mma160<1, 0, W * 16384 + 2 * 2048, 2 * 32>(d, la, lb);
  mma160<1, 0, W * 16384 + 3 * 2048, 3 * 32>(d, la, lb);
}
template <int W, bool ACC>
__device__ __forceinline__ void mma_mid(float (&d)[40], uint32_t aaddr, uint32_t baddr) {
  const uint32_t la = lo_sw(aaddr), lb = lo_sw(baddr);
  if (ACC) mma80<1, 0, 8192, W * 10240>(d, la, lb); else mma80z<1, 0, 8192, W * 10240>(d, la, lb);
  mma80<1, 0, 8192 + 1 * 2048, W * 10240 + 1 * 32>(d, la, lb);
  mma80<1, 0, 8192 + 2 * 2048, W * 10240 + 2 * 32>(d, la, lb);
  mma80<1, 0, 8192 + 3 * 2048, W * 10240 + 3 * 32>(d, la, lb);
}
template <int W, bool ACC>
__device__ __forceinline__ void mma_both(float (&dm)[80], float (&dh)[40], uint32_t aaddr, uint32_t baddr) {
  mma_mid<W, ACC>(dh, aaddr, baddr);
  mma_main<W, ACC>(dm, aaddr, baddr);
}
template <int KB, bool ACC>
__device__ __forceinline__ void s_mma(float (&sacc)[80], uint32_t kaddr) {
  const uint32_t la = lo_sw(kaddr), lb = lo_sw(SB + OFF_B);
  if (ACC) mma160<0, 0, KB * 8192, KB * B_SLOT>(sacc, la, lb); else mma160z<0, 0, KB * 8192, KB * B_SLOT>(sacc, la, lb);
  mma160<0, 0, KB * 8192 + 32, KB * B_SLOT + 32>(sacc, la, lb);
  mma160<0, 0, KB * 8192 + 64, KB * B_SLOT + 64>(sacc, la, lb);
  mma160<0, 0, KB * 8192 + 96, KB * B_SLOT + 96>(sacc, la, lb);
}
template <int N>
__device__ __forceinline__ void store_scaled(uint32_t addr, const float (&d)[N], float sc) {
#pragma unroll
  for (int J = 0; J < N / 8; J++)
    stsm_t(addr + J * 2048, pack2(d[8 * J] * sc, d[8 * J + 1] * sc), pack2(d[8 * J + 2] * sc, d[8 * J + 3] * sc),
           pack2(d[8 * J + 4] * sc, d[8 * J + 5] * sc), pack2(d[8 * J + 6] * sc, d[8 * J + 7] * sc));
}
__device__ __forceinline__ float4 lds_f4(uint32_t a) {
  float4 v;
  asm volatile("ld.shared.v4.f32 {%0,%1,%2,%3}, [%4];" : "=f"(v.x), "=f"(v.y), "=f"(v.z), "=f"(v.w) : "r"(a) : "memory");
  return v;
}
__device__ __forceinline__ void norm_pack(uint32_t* p, const float* d, const float4& i) {
  p[0] = pack2(d[0] * i.x, d[1] * i.y); p[1] = pack2(d[4] * i.z, d[5] * i.w);
  p[2] = pack2(d[2] * i.x, d[3] * i.y); p[3] = pack2(d[6] * i.z, d[7] * i.w);
  asm volatile("" : "+r"(p[0]), "+r"(p[1]), "+r"(p[2]), "+r"(p[3])::"memory");
}
template <int W>
__device__ __forceinline__ void pack_first(uint32_t (&pk)[60], const float (&om)[80], const float (&oh)[40], uint32_t laddr) {
  float4 n0 = lds_f4(laddr + W * 80), n1 = lds_f4(laddr + W * 80 + 16);
#pragma unroll
  for (int J = 0; J < 5; J++) {
    const float4 i = n0;
    n0 = n1;
    if (J + 2 < 5) n1 = lds_f4(laddr + W * 80 + (J + 2) * 16);
    norm_pack(&pk[20 + 4 * J], &om[8 * (5 * W + J)], i);
    norm_pack(&pk[4 * J], &oh[8 * J], i);
  }
}
template <int W, int J0, int J1>
__device__ __forceinline__ void pack_second(uint32_t (&pk)[60], const float (&om)[80], uint32_t laddr) {
  float4 n[J1 - J0];
#pragma unroll
  for (int J = J0; J < J1; J++) n[J - J0] = lds_f4(laddr + (1 - W) * 80 + J * 16);
#pragma unroll
  for (int J = J0; J < J1; J++) norm_pack(&pk[40 + 4 * J], &om[8 * (5 * (1 - W) + J)], n[J - J0]);
}
__device__ __forceinline__ char* o_ptr(int item) {
  const uint32_t t = tid_x();
  return (char*)g_o + (size_t)(item % ORING) * O_ITEM_BYTES + ((t & 96) * 16 + (t & 28) * 8 + ((((t >> 1) ^ (t >> 4)) & 1) << 4) + (t & 1) * 8);
}
template <int W, int G0, int G1>
__device__ __forceinline__ void store_groups(char* op, const uint32_t (&pk)[60], uint32_t on) {
#pragma unroll
  for (int G = G0; G < G1; G++) {
    const int off = (G < 5 ? 1 : 2 * W) * B_SLOT + (5 * (G < 10 ? W : 1 - W) + G % 5) * 2048;
    asm volatile("{\n.reg .pred p;\nsetp.ne.u32 p, %5, 0;\n@p st.global.v2.b32 [%0], {%1, %2};\n@p st.global.v2.b32 [%0+256], {%3, %4};\n}\n"
                 ::"l"(op + off), "r"(pk[4 * G]), "r"(pk[4 * G + 1]), "r"(pk[4 * G + 2]), "r"(pk[4 * G + 3]), "r"(on) : "memory");
  }
}
__device__ __forceinline__ void publish_generic(uint32_t bar, int lane) {
  __syncwarp();
  mbar_arrive_if0(bar, lane);
}
__device__ __forceinline__ void publish(uint32_t bar, int lane) {
  proxy_fence();
  __syncwarp();
  mbar_arrive_if0(bar, lane);
}

#define A_ADDR(s) (SB + OFF_A + (s) * A_SLOT)
#define B_ADDR(s) (SB + OFF_B + (s) * B_SLOT)
#define WAIT_CHUNK(c, ro, sA)                \
  uint32_t sA;                               \
  {                                          \
    uint32_t pA_;                            \
    ring_pos(ring, (ro) + (c), sA, pA_);     \
    mbar_wait(bud, BAR_FULLA + sA * 8, pA_); \
  }
#define RELEASE_CHUNK(c, sA)                                  \
  mbar_arrive_if0(BAR_EMPTYA + (sA) * 8, tid);                \
  if ((c) < NSLOT) mbar_arrive_if0(BAR_EMPTYB + xs(c) * 8, tid);

template <int W>
__device__ __forceinline__ void attn_consumer(int item) {
  int bud = WAIT_BUDGET;
  const int tid = threadIdx.x & 127, lane = tid & 31, warp = tid >> 5;
  const uint32_t st_off = ((lane & 7) + 8 * (lane >> 4)) * 128 + (((2 * warp + ((lane >> 3) & 1)) ^ (lane & 7)) << 4);
  const uint32_t laddr = SB + OFF_L + (lane & 3) * 160;
  float om[80], oh[40], sacc[80];
  uint32_t pk[60];
#pragma unroll
  for (int i = 0; i < 40; i++) pk[i] = 0;
  zero_regs(om);
  Ring ring{0u, 0u};
  uint32_t par = 0;
  int prev = 0;
  const float qscale = 0.07216878364870322f * 1.4426950408889634f;
  constexpr uint32_t pown = B_ADDR(3 + W), poth = B_ADDR(4 - W);
  TL(0); TLG(62);
  {
    WAIT_CHUNK(0, 0, s0)
    wg_fence();
    mma_both<W, false>(sacc, oh, A_ADDR(s0), B_ADDR(xs(0)));
    wg_commit();
    WAIT_CHUNK(1, 0, s1)
    wg_fence();
    mma_both<W, true>(sacc, oh, A_ADDR(s1), B_ADDR(xs(1)));
    wg_commit();
    wg_wait<1>();
    RELEASE_CHUNK(0, s0)
  }
#pragma unroll 1
  for (int it = 0;; it++) {
    char* op = o_ptr(prev);
#pragma unroll
    for (int c = 2; c < 8 - W; c++) {
      WAIT_CHUNK(c, 0, sA)
      TL(40 + c);
      wg_fence();
      mma_both<W, true>(sacc, oh, A_ADDR(sA), B_ADDR(xs(c)));
      wg_commit();
      wg_wait<1>();
      uint32_t sP, pP;
      ring_pos(ring, c - 1, sP, pP);
      RELEASE_CHUNK(c - 1, sP)
      constexpr int NG = W == 0 ? 3 : W1_NG;
      if (c == 2) { pack_second<W, 0, 1>(pk, om, laddr); store_groups<W, 0 * NG, 1 * NG>(op, pk, it); }
      if (c == 3) { pack_second<W, 1, 2>(pk, om, laddr); store_groups<W, 1 * NG, 2 * NG>(op, pk, it); }
      if (c == 4) { pack_second<W, 2, 3>(pk, om, laddr); store_groups<W, 2 * NG, 3 * NG>(op, pk, it); }
      if (c == 5) { pack_second<W, 3, 4>(pk, om, laddr); store_groups<W, 3 * NG, 4 * NG>(op, pk, it); }
      if (c == 6) {
        pack_second<W, 4, 5>(pk, om, laddr);
        if (W == 1) {
          wg_wait<0>();
          RELEASE_CHUNK(6, sA)
          mbar_arrive_if0(BAR_XDONE, tid);
        }
        store_groups<W, 4 * NG, 15>(op, pk, it);
        __syncwarp();
        mbar_arrive_if0(BAR_OFULL, lane | (it == 0));
      }
    }
    uint32_t sK0, pK0, s7, p7;
    ring_pos(ring, idxK(W), sK0, pK0);
    ring_pos(ring, 7, s7, p7);
    if (W == 1) mbar_wait(bud, BAR_FULLA + s7 * 8, p7);
    WAIT_CHUNK(8, 0, s8)
    WAIT_CHUNK(9, 0, s9)
    TL(48);
    if (W == 0) {
      wg_fence();
      mma_mid<W, true>(oh, A_ADDR(s8), B_ADDR(xs(8)));
      mma_mid<W, true>(oh, A_ADDR(s9), B_ADDR(xs(9)));
      wg_commit();
      wg_wait<1>();
      RELEASE_CHUNK(7, s7)
      wg_fence();
      mma_main<W, true>(sacc, A_ADDR(s8), B_ADDR(xs(8)));
      mma_main<W, true>(sacc, A_ADDR(s9), B_ADDR(xs(9)));
      wg_commit();
      bar_arrive(5, 256);
      TL(49);
      wg_wait<1>();
      reg_fence(oh);
      mbar_wait(bud, BAR_XDONE, par);
      store_scaled(B_ADDR(1) + st_off, oh, qscale);
    } else {
      bar_sync(5, 256);
      wg_fence();
      mma_mid<W, true>(oh, A_ADDR(s7), B_ADDR(xs(7)));
      mma_mid<W, true>(oh, A_ADDR(s8), B_ADDR(xs(8)));
      mma_mid<W, true>(oh, A_ADDR(s9), B_ADDR(xs(9)));
      wg_commit();
      mma_main<W, true>(sacc, A_ADDR(s7), B_ADDR(xs(7)));
      wg_commit();
      mma_main<W, true>(sacc, A_ADDR(s8), B_ADDR(xs(8)));
      wg_commit();
      wg_wait<2>();
      reg_fence(oh);
      store_scaled(B_ADDR(1) + 10240 + st_off, oh, qscale);
      wg_fence();
      mma_main<W, true>(sacc, A_ADDR(s9), B_ADDR(xs(9)));
      wg_commit();
      bar_arrive(8, 256);
      TL(49);
      wg_wait<2>();
      RELEASE_CHUNK(7, s7)
      publish(BAR_QH, lane);
    }
    wg_wait<0>();
    reg_fence(sacc);
    TL(1);
    RELEASE_CHUNK(8, s8)
    RELEASE_CHUNK(9, s9)
    store_scaled(B_ADDR(2 * W) + st_off, sacc, qscale);
    if (W == 1) publish(BAR_QM, lane); else proxy_fence();
    TL(2);
    uint32_t sK = sK0, sV1 = 0;
    if (W == 0) {
      zero_regs(om); zero_regs(oh);
      reg_fence(om); reg_fence(oh);
      mbar_wait(bud, BAR_FULLA + sK0 * 8, pK0);
      bar_sync(8, 256);
      wg_fence();
      s_mma<0, false>(sacc, A_ADDR(sK));
      mbar_wait(bud, BAR_QH, par);
      TL(3);
      wg_fence();
      s_mma<1, true>(sacc, A_ADDR(sK));
      mbar_wait(bud, BAR_QM, par);
      TL(5);
      wg_fence();
      s_mma<2, true>(sacc, A_ADDR(sK));
      wg_commit();
      wg_commit();
      bar_arrive(2, 256);
    } else {
      uint32_t pV1;
      ring_pos(ring, idxV(0), sV1, pV1);
      mbar_wait(bud, BAR_FULLA + sK * 8, pK0);
      bar_sync(2, 256);
      wg_fence();
      s_mma<0, false>(sacc, A_ADDR(sK));
      s_mma<1, true>(sacc, A_ADDR(sK));
      s_mma<2, true>(sacc, A_ADDR(sK));
      wg_commit();
      TL(6);
      mbar_wait(bud, BAR_FULLA + sV1 * 8, pV1);
      mbar_wait(bud, BAR_PFULL, 0);
      TL(7);
      wg_fence();
      mma_both<W, false>(om, oh, A_ADDR(sV1), poth);
      wg_commit();
      bar_arrive(1, 256);
    }
    Ring rv;
    ring_pos(ring, idxV(W), rv.s0, rv.ph0);
#pragma unroll 1
    for (int jj = 0;; jj++) {
      wg_wait<1>();
      reg_fence(sacc);
      TL(8 + jj * 7);
      mbar_arrive2_if0(BAR_EMPTYA + sK * 8, tid);
      mbar_arrive_if0(BAR_EMPTYB + tid * 8, (tid >= 3) | (jj != 3));
#pragma unroll
      for (int J = 0; J < 10; J++) {
        stsm_t(pown + st_off + J * 2048, pack2(ex2(sacc[8 * J]), ex2(sacc[8 * J + 1])), pack2(ex2(sacc[8 * J + 2]), ex2(sacc[8 * J + 3])),
               pack2(ex2(sacc[8 * J + 4]), ex2(sacc[8 * J + 5])), pack2(ex2(sacc[8 * J + 6]), ex2(sacc[8 * J + 7])));
        if (W == 1 && (J == 2 || J == 5)) publish_generic(BAR_PMID + (J / 3) * 8, lane | (jj != 3));
        if (J == 4) {
          wg_wait<0>();
          mbar_arrive_if0(BAR_EMPTYA + sV1 * 8, tid | (W == 0 && jj == 0));
        }
      }
      publish(BAR_PFULL + W * 8, lane);
      TL(10 + jj * 7);
      if (jj == 3) break;
      uint32_t pK, pV1;
      ring_pos(rv, 1, sK, pK);
      ring_pos(rv, 2, sV1, pV1);
      mbar_wait(bud, BAR_FULLA + rv.s0 * 8, rv.ph0);
      bar_sync(1 + W, 256);
      wg_fence();
      mma_both<W, true>(om, oh, A_ADDR(rv.s0), pown);
      wg_commit();
      mbar_wait(bud, BAR_FULLA + sK * 8, pK);
      TL(11 + jj * 7);
      wg_fence();
      s_mma<0, false>(sacc, A_ADDR(sK));
      s_mma<1, true>(sacc, A_ADDR(sK));
      wg_commit();
      wg_wait<1>();
      mbar_arrive_if0(BAR_EMPTYA + rv.s0 * 8, tid);
      wg_fence();
      s_mma<2, true>(sacc, A_ADDR(sK));
      wg_commit();
      TL(13 + jj * 7);
      mbar_wait(bud, BAR_FULLA + sV1 * 8, pV1);
      mbar_wait(bud, BAR_PFREE + W * 8, jj & 1);
      mbar_wait(bud, BAR_PFULL + (1 - W) * 8, (jj + W) & 1);
      TL(14 + jj * 7);
      wg_fence();
      mma_both<W, true>(om, oh, A_ADDR(sV1), poth);
      wg_commit();
      bar_arrive(2 - W, 256);
      ring_advance(rv, 4);
    }
    uint32_t sV7, pV7;
    ring_pos(ring, idxV(7), sV7, pV7);
    prev = item;
    if (W == 1 && !DEBUG_TIMEOUT) item = next_item();
    if (W == 0) {
      uint32_t sV6, pV6;
      ring_pos(ring, idxV(6), sV6, pV6);
      mbar_wait(bud, BAR_FULLA + sV6 * 8, pV6);
      bar_sync(1, 256);
      wg_fence();
      mma_both<0, true>(om, oh, A_ADDR(sV6), pown);
      wg_commit();
      mbar_wait(bud, BAR_FULLA + sV7 * 8, pV7);
      wg_wait<0>();
      mbar_arrive_if0(BAR_EMPTYA + sV6 * 8, tid);
      mbar_wait(bud, BAR_PFULL + 8, 1);
      wg_fence();
      mma_both<0, true>(om, oh, A_ADDR(sV7), poth);
      wg_commit();
      bar_arrive(6, 256);
    } else {
      mbar_wait(bud, BAR_FULLA + sV7 * 8, pV7);
      bar_sync(6, 256);
    }
    TL(32);
    if (DEBUG_TIMEOUT) item = next_item(NEXT_ITEM + 4);
    else if (W == 0) item = next_item();
    if (item >= NITEMS) {
      if (W == 1) {
        wg_fence();
        mma_both<1, true>(om, oh, A_ADDR(sV7), pown);
        wg_commit();
      }
      wg_wait<0>();
      reg_fence(om); reg_fence(oh);
      TL(33);
      mbar_wait(bud, BAR_LFULL, par);
      TL(34);
      pack_first<W>(pk, om, oh, laddr);
      op = o_ptr(prev);
      store_groups<W, 0, 10>(op, pk, 1);
      pack_second<W, 0, 5>(pk, om, laddr);
      store_groups<W, 10, 15>(op, pk, 1);
      publish_generic(BAR_OFULL, lane);
      TL(35); TLG(63);
      TL_FLUSH();
      break;
    }
    {
      if (W == 1) {
        wg_fence();
        mma_both<1, true>(om, oh, A_ADDR(sV7), pown);
        wg_commit();
      }
      WAIT_CHUNK(0, 26, s0)
      WAIT_CHUNK(1, 26, s1)
      if (W == 0) {
        wg_wait<0>();
        reg_fence(om); reg_fence(oh);
        TL(33);
        wg_fence();
        mma_main<W, false>(sacc, A_ADDR(s0), B_ADDR(xs(0)));
        wg_commit();
      } else {
        wg_fence();
        mma_main<W, false>(sacc, A_ADDR(s0), B_ADDR(xs(0)));
        mma_main<W, true>(sacc, A_ADDR(s1), B_ADDR(xs(1)));
        wg_commit();
        wg_wait<1>();
        reg_fence(om); reg_fence(oh);
        TL(33);
      }
      mbar_arrive_if0(BAR_EMPTYA + sV7 * 8, tid);
      mbar_wait(bud, BAR_LFULL, par);
      mbar_arrive_if0(BAR_EMPTYB + 24 + tid * 8, tid >= 2);
      TL(34);
      pack_first<W>(pk, om, oh, laddr);
      TL(36);
      wg_fence();
      mma_mid<W, false>(oh, A_ADDR(s0), B_ADDR(xs(0)));
      wg_commit();
      mma_mid<W, true>(oh, A_ADDR(s1), B_ADDR(xs(1)));
      if (W == 0) mma_main<W, true>(sacc, A_ADDR(s1), B_ADDR(xs(1)));
      wg_commit();
      TL(37);
      wg_wait<1>();
      RELEASE_CHUNK(0, s0)
      TL(35); TLG(63);
    }
    TL_FLUSH();
    TL(0); TLG(62);
    ring_advance(ring, 26);
    par ^= 1;
  }
}

__device__ __forceinline__ uint4 lds128(uint32_t a) {
  uint4 v;
  asm volatile("ld.shared.v4.b32 {%0,%1,%2,%3}, [%4];" : "=r"(v.x), "=r"(v.y), "=r"(v.z), "=r"(v.w) : "r"(a) : "memory");
  return v;
}
__device__ __forceinline__ void acc2(float& s, float& t, uint32_t w) {
  s += __uint_as_float(w << 16);
  t += __uint_as_float(w & 0xffff0000u);
}
__device__ __forceinline__ uint32_t badd2(uint32_t a, uint32_t b) { uint32_t r; asm("add.rn.bf16x2 %0, %1, %2;" : "=r"(r) : "r"(a), "r"(b)); return r; }
__device__ __forceinline__ void sum_unit(float& acc, uint32_t pb) {
  const uint4 v0 = lds128(pb), v1 = lds128(pb ^ 32), v2 = lds128(pb ^ 64), v3 = lds128(pb ^ 96);
  const uint32_t w0 = badd2(v0.x, v0.y), w1 = badd2(v0.z, v0.w);
  float s0 = acc + __uint_as_float(w0 << 16), t0 = __uint_as_float(w0 & 0xffff0000u);
  float s1 = __uint_as_float(w1 << 16), t1 = __uint_as_float(w1 & 0xffff0000u);
  acc2(s0, t0, badd2(v1.x, v1.y)); acc2(s1, t1, badd2(v1.z, v1.w));
  acc2(s0, t0, badd2(v2.x, v2.y)); acc2(s1, t1, badd2(v2.z, v2.w));
  acc2(s0, t0, badd2(v3.x, v3.y)); acc2(s1, t1, badd2(v3.z, v3.w));
  acc = (s0 + t0) + (s1 + t1);
}
__device__ __forceinline__ float bf_lo(uint32_t w) { return __uint_as_float(w << 16); }
__device__ __forceinline__ float bf_hi(uint32_t w) { return __uint_as_float(w & 0xffff0000u); }
__device__ __forceinline__ float bf_rn(float x) { return __bfloat162float(__float2bfloat16(x)); }
__device__ __forceinline__ void slow_item(const Params& p, int item, int hw) {
  const int blk = item >> 9, h = (item >> 4) & 31, b = item & 15;
#pragma unroll 1
  for (int n = hw; n < SQ; n += 3) {
    float q[6] = {0.f, 0.f, 0.f, 0.f, 0.f, 0.f};
    {
      const uint32_t* xr = (const uint32_t*)(p.xp[blk] + (size_t)(b * SQ + n) * DM);
      const uint32_t* wq = (const uint32_t*)(p.wqp[blk] + h * DH) + (tid_x() & 31);
#pragma unroll 2
      for (int k = 0; k < DM / 2; k++) {
        const uint32_t xv = xr[k];
#pragma unroll
        for (int i = 0; i < 3; i++) {
          const uint32_t w0 = wq[i * 32], w1 = wq[NH * DH / 2 + i * 32];
          q[2 * i] = fmaf(bf_lo(xv), bf_lo(w0), fmaf(bf_hi(xv), bf_lo(w1), q[2 * i]));
          q[2 * i + 1] = fmaf(bf_lo(xv), bf_hi(w0), fmaf(bf_hi(xv), bf_hi(w1), q[2 * i + 1]));
        }
        wq += NH * DH;
      }
    }
    const uint32_t q0 = pack2(q[0], q[1]), q1 = pack2(q[2], q[3]), q2 = pack2(q[4], q[5]);
    float o[6] = {0.f, 0.f, 0.f, 0.f, 0.f, 0.f}, m = -INFINITY, l = 0.f;
    const uint32_t* kg = (const uint32_t*)(p.kp[blk] + (size_t)(b * NH + h) * SK * DH) + (tid_x() & 31);
    const uint32_t* vg = (const uint32_t*)(p.vp[blk] + (size_t)(b * NH + h) * SK * DH) + (tid_x() & 31);
#pragma unroll 1
    for (int k = 0; k < SK; k++) {
      const uint32_t k0 = kg[0], k1 = kg[32], k2 = kg[64], v0 = vg[0], v1 = vg[32], v2 = vg[64];
      kg += DH / 2; vg += DH / 2;
      float sc = fmaf(bf_lo(q0), bf_lo(k0), bf_hi(q0) * bf_hi(k0));
      sc = fmaf(bf_lo(q1), bf_lo(k1), fmaf(bf_hi(q1), bf_hi(k1), sc));
      sc = fmaf(bf_lo(q2), bf_lo(k2), fmaf(bf_hi(q2), bf_hi(k2), sc));
#pragma unroll
      for (int d = 16; d; d >>= 1) sc += __shfl_xor_sync(0xffffffffu, sc, d);
      sc = bf_rn(bf_rn(sc) * 0.07216878364870322f);
      const float mn = fmaxf(m, sc), a = ex2((m - mn) * 1.4426950408889634f), pr = ex2((sc - mn) * 1.4426950408889634f);
      m = mn;
      l = fmaf(l, a, pr);
      o[0] = fmaf(o[0], a, pr * bf_lo(v0)); o[1] = fmaf(o[1], a, pr * bf_hi(v0));
      o[2] = fmaf(o[2], a, pr * bf_lo(v1)); o[3] = fmaf(o[3], a, pr * bf_hi(v1));
      o[4] = fmaf(o[4], a, pr * bf_lo(v2)); o[5] = fmaf(o[5], a, pr * bf_hi(v2));
    }
    float inv;
    asm("rcp.approx.ftz.f32 %0, %1;" : "=f"(inv) : "f"(l));
    const int lane = tid_x() & 31;
    const int r = n & 15, c = 4 * ((r & 7) >> 1) + 2 * (r >> 3) + (r & 1);
    char* on = (char*)g_o + (size_t)(item % ORING) * O_ITEM_BYTES + (lane >> 2) * 256 + (lane & 3) * 64 + (n >> 4) * 2048 +
               (((c >> 3) ^ ((lane >> 1) & 1)) << 4) + (c & 7) * 2;
#pragma unroll
    for (int i = 0; i < 3; i++) {
      *(__nv_bfloat16*)(on + i * B_SLOT) = __float2bfloat16(o[2 * i] * inv);
      *(__nv_bfloat16*)(on + i * B_SLOT + 32) = __float2bfloat16(o[2 * i + 1] * inv);
    }
  }
}
__device__ __forceinline__ void attn_helper(const Params& p, int hw, int item, int epoch) {
  int bud = WAIT_BUDGET;
  if (item < PF_N && hw < 2) {
    const char* g = (const char*)(hw ? p.vp[0] : p.kp[0]) + (size_t)(((item & 15) * NH + (item >> 4)) * SK) * DH * 2;
    const long long t0 = clock64();
#pragma unroll 1
    for (int i = 0; i < 32; i++) {
      while (clock64() - t0 < PF_WAIT + i * PF_GAP) __nanosleep(50);
      for (int k = 0; k < 6; k++) asm volatile("prefetch.global.L2 [%0];" ::"l"(g + i * 6144 + k * 1024 + (tid_x() & 31) * 32));
      __syncwarp();
    }
  }
#pragma unroll 1
  for (int it = 0; item < NITEMS; it++) {
    const uint32_t par = it & 1;
    int lane = tid_x() & 31;
    const int r = lane >> 1;
    const uint32_t a0 = B_ADDR(3) + (16 * hw + r) * 128 + (lane & 1) * 16 + ((r & 3) << 5);
    float acc[4] = {0.f, 0.f, 0.f, 0.f};
#pragma unroll 1
    for (int j = 0; j < 8; j++) {
      const uint32_t pb = a0 + (j & 1) * B_SLOT, bfull = BAR_PFULL + (j & 1) * 8, pfull = (j >> 1) & 1;
      mbar_wait(bud, j == 7 ? BAR_PMID : bfull, j == 7 ? par : pfull);
      sum_unit(acc[0], pb);
      if (j == 7) mbar_wait(bud, BAR_PMID + 8, par);
      sum_unit(acc[1], pb + 6144);
      if (j == 7) mbar_wait(bud, bfull, pfull);
      sum_unit(acc[2], pb + 2 * 6144);
      if (hw == 0) sum_unit(acc[3], pb + 3 * 6144);
      __syncwarp();
      mbar_arrive_if0(BAR_PFREE + (j & 1) * 8, lane);
      if (j == DONE_J && hw == 2) {
        if (lane == 0) TLP(60);
        if (item >= ORING) flag_wait(bud, &g_done[(item - ORING) >> 4], (epoch + 1) * N_OCTA);
        if (lane == 0) TLP(61);
      }
    }
    bool bad = false;
    const uint32_t la = SB + OFF_L + (((r & 7) >> 1) * 40 + 2 * (r >> 3) + (r & 1) + 4 * hw) * 4;
#pragma unroll
    for (int u = 0; u < 4; u++) {
      const float l = acc[u] + __shfl_xor_sync(0xffffffffu, acc[u], 1);
      if (u < 3 || hw == 0) {
        bad |= !(l >= 8.8817841970012523e-16f && l <= 1.125899906842624e15f);
        float inv;
        asm("rcp.approx.ftz.f32 %0, %1;" : "=f"(inv) : "f"(l));
        asm volatile("st.shared.f32 [%0], %1;" ::"r"(la + u * 48), "f"(inv) : "memory");
      }
    }
    publish_generic(BAR_LFULL, lane);
    if (lane == 0) TLP(40 + hw * 4);
    uint32_t anybad;
    asm volatile("{\n.reg .pred p, q;\nsetp.ne.u32 p, %1, 0;\nbarrier.red.or.pred q, 7, 96, p;\nselp.u32 %0, 1, 0, q;\n}\n"
                 : "=r"(anybad) : "r"((uint32_t)bad) : "memory");
    if (__any_sync(0xffffffffu, anybad)) {
      mbar_wait(bud, BAR_OFULL, par);
      slow_item(p, item, hw);
      bar_sync(7, 96);
    }
    if (hw == 1) {
      mbar_wait(bud, BAR_OFULL, par);
      if ((tid_x() & 31) == 0) {
        TLP(41 + hw * 4);
        asm volatile("red.release.gpu.global.add.s32 [%0], 1;" ::"l"(&g_ready[item]) : "memory");
        TLP(42 + hw * 4);
      }
      __syncwarp();
    }
    item = next_item();
  }
}

__device__ __forceinline__ void attn_producer(const Params& p, int item) {
  int bud = WAIT_BUDGET;
  uint32_t sa = 0, pa = 1;
  uint64_t pol;
  asm volatile("createpolicy.fractional.L2::evict_first.b64 %0, 1.0;" : "=l"(pol));
  const bool draws = item >= N_OCTA;
  {
    const int delay = start_delay(item);
    const long long t0 = clock64();
    while (clock64() - t0 < delay) __nanosleep(100);
  }
#pragma unroll 1
  for (int it = 0; item < NITEMS; it++) {
    const int blk = item >> 9, h = (item >> 4) & 31, b = item & 15;
    const int row0 = (b * NH + h) * SK;
#pragma unroll
    for (int c = 0; c < 10; c++) {
      mbar_wait(bud, BAR_EMPTYA + sa * 8, pa);
      TLP(c);
      mbar_expect(BAR_FULLA + sa * 8, A_SLOT + B_SLOT);
      tma3d(A_ADDR(sa), &p.wq[blk], BAR_FULLA + sa * 8, 0, c * 64, h * 3);
      mbar_wait(bud, BAR_EMPTYB + xs(c) * 8, c < NSLOT);
      TLP(10 + c);
      tma2d(B_ADDR(xs(c)), &p.x[blk], BAR_FULLA + sa * 8, c * 64, b * SQ);
      if (++sa == NSLOT) { sa = 0; pa ^= 1; }
    }
#pragma unroll
    for (int i = 0; i < 16; i++) {
      const bool isK = (i == 0) || ((i & 1) && i < 15);
      const int j = i == 0 ? 0 : (i == 15 ? 7 : (isK ? (i + 1) >> 1 : (i - 2) >> 1));
      mbar_wait(bud, BAR_EMPTYA + sa * 8, pa);
      TLP(20 + i);
      if (i == 11) item = !draws ? NITEMS : DYN ? NCTA + (int)atomicInc(&g_ticket, NITEMS - NCTA + N_ATT - 1) : item + N_ATT;
      if (i == 13) asm volatile("st.shared.s32 [%0], %1;" ::"r"(NEXT_ITEM), "r"(item) : "memory");
      mbar_expect(BAR_FULLA + sa * 8, A_SLOT);
      tma3d_hint(A_ADDR(sa), isK ? &p.k[blk] : &p.v[blk], BAR_FULLA + sa * 8, 0, row0 + j * 64, 0, pol);
      if (++sa == NSLOT) { sa = 0; pa ^= 1; }
    }
  }
}

template <int W>
__device__ __forceinline__ void oproj_consumer() {
  int bud = WAIT_BUDGET;
  const int tid = threadIdx.x & 127, lane = tid & 31, warp = tid >> 5;
  const int qrow = 8 * ((lane >> 1) & 1) + 4 * (lane >> 4) + 2 * ((lane >> 2) & 1) + (lane & 1);
  const uint32_t st_off = qrow * 128 + (((2 * warp + ((lane >> 3) & 1)) ^ (qrow & 7)) << 4);
  float a0[64], a1[64], ah[32];
  zero_regs(a0); zero_regs(a1); zero_regs(ah);
#pragma unroll 1
  for (int blk = 0; blk < 2; blk++) {
    int c3 = 0, step = blk * NH;
#pragma unroll 1
    for (int c = 0; c < 96; c++) {
      const uint32_t st = c & 3;
      mbar_wait(bud, BAR_GFULL + st * 8, (c >> 2) & 1);
      wg_fence();
      const uint32_t la = lo_sw(SB + st * O_STAGE), lb = lo_o(SB + st * O_STAGE + O_AB);
#define O_STEP(ks, sc)                                                   \
  mma64r<1, 1, 2 * 8192 + ks * 2048, W * 8192 + ks * 512>(ah, la, lb, sc);    \
  mma128r<1, 1, (W * 3) * 8192 + ks * 2048, ks * 512>(a0, la, lb, sc);        \
  mma128r<1, 1, (W * 3 + 1) * 8192 + ks * 2048, ks * 512>(a1, la, lb, sc);
      O_STEP(0, c != 0) O_STEP(1, 1) O_STEP(2, 1) O_STEP(3, 1)
#undef O_STEP
      wg_commit();
      if (++c3 == 3) {
        c3 = 0;
        if (W == 0)
          asm volatile("{\n.reg .pred p;\nsetp.eq.u32 p, %1, 0;\n@p red.relaxed.gpu.global.add.s32 [%0], 1;\n}\n" ::"l"(&g_done[step]), "r"(tid) : "memory");
        TL(step);
        step++;
      }
      wg_wait<1>();
      mbar_arrive_if0(BAR_GEMPTY + ((c - 1) & 3) * 8, tid | (c == 0) | (c == 95));
    }
    wg_wait<0>();
    reg_fence(a0); reg_fence(a1); reg_fence(ah);
    bar_sync(3, 256);
    const uint32_t sg = SB + 2 * O_STAGE + st_off;
    store_scaled(sg + 2 * 16384 + W * 8192, ah, 1.0f);
    store_scaled(sg + (W * 3) * 16384, a0, 1.0f);
    store_scaled(sg + (W * 3 + 1) * 16384, a1, 1.0f);
    publish(BAR_GOUT, lane);
  }
  TL_FLUSH();
}

__device__ __forceinline__ void oproj_producer(const Params& p, int cta, int target) {
  int bud = WAIT_BUDGET;
  const int half = O_PAIR ? (cta >> 1) & 1 : cta & 1, r0 = (O_PAIR ? (cta >> 2) * 2 + (cta & 1) : cta >> 1) * 128;
  const int b0 = r0 / SQ, off0 = r0 - b0 * SQ, n0 = min(128, SQ - off0), n1 = 128 - n0;
#pragma unroll 1
  for (int step = 0; step < 2 * NH; step++) {
    const int blk = step >> 5, item0 = step * 16 + b0;
    const char* o0 = (const char*)g_o + (size_t)(item0 % ORING) * O_ITEM_BYTES + off0 * 128;
    const char* o1 = (const char*)g_o + (size_t)((item0 + 1) % ORING) * O_ITEM_BYTES;
#pragma unroll 1
    for (int kb = 0; kb < 3; kb++) {
      const int c = step * 3 + kb;
      const uint32_t st = c & 3, dst = SB + st * O_STAGE, bar = BAR_GFULL + st * 8;
      mbar_wait(bud, BAR_GEMPTY + st * 8, ((c >> 2) & 1) ^ 1);
      mbar_expect(bar, O_STAGE);
      tma3d(dst, &p.wo[blk], bar, 0, ((step & 31) * 3 + kb) * 64, half * 5);
      if (kb == 0) {
        flag_wait(bud, &g_ready[item0], target);
        if (n1) flag_wait(bud, &g_ready[item0 + 1], target);
        asm volatile("fence.proxy.async.global;" ::: "memory");
      }
      bulk_load(dst + O_AB, o0 + kb * B_SLOT, n0 * 128, bar);
      if (n1) bulk_load(dst + O_AB + n0 * 128, o1 + kb * B_SLOT, n1 * 128, bar);
    }
  }
}

__device__ __forceinline__ void oproj_storer(const Params& p, int cta) {
  int bud = WAIT_BUDGET;
  const int half = O_PAIR ? (cta >> 1) & 1 : cta & 1, r0 = (O_PAIR ? (cta >> 2) * 2 + (cta & 1) : cta >> 1) * 128;
#pragma unroll 1
  for (int blk = 0; blk < 2; blk++) {
    mbar_wait(bud, BAR_GOUT, blk);
    for (int k = 0; k < 5; k++) tma_store2d(&p.out, SB + 2 * O_STAGE + k * 16384, blk * DM + half * 320 + k * 64, r0);
    asm volatile("cp.async.bulk.commit_group;" ::: "memory");
    asm volatile("cp.async.bulk.wait_group.read 0;" ::: "memory");
    mbar_arrive2_if0(BAR_GEMPTY + 16, 0);
    mbar_arrive2_if0(BAR_GEMPTY + 24, 0);
  }
  asm volatile("cp.async.bulk.wait_group 0;" ::: "memory");
}

__global__ void __launch_bounds__(384, 1) fused_kernel(const __grid_constant__ Params p) {
  extern __shared__ __align__(1024) char smem_raw[];
  if ((smem_u32(smem_raw) & 0xFFFFFFu) != SB) return;
  const int cta = (((blockIdx.x >> 1) * PERM_M) % (NCTA / 2)) * 2 + (blockIdx.x & 1);
  const int warp = __shfl_sync(0xffffffffu, threadIdx.x >> 5, 0);
  if (threadIdx.x == 0) {
    for (int i = 0; i < NSLOT; i++) { mbar_init(BAR_FULLA + i * 8, 1); mbar_init(BAR_EMPTYA + i * 8, 2); mbar_init(BAR_EMPTYB + i * 8, 2); }
    proxy_fence();
  }
  if (threadIdx.x == 64) {
    mbar_init(BAR_XDONE, 1); mbar_init(BAR_QH, 4); mbar_init(BAR_QM, 4);
    mbar_init(BAR_PFULL, 4); mbar_init(BAR_PFULL + 8, 4); mbar_init(BAR_PFREE, 3); mbar_init(BAR_PFREE + 8, 3);
    mbar_init(BAR_LFULL, 3); mbar_init(BAR_PMID, 4); mbar_init(BAR_PMID + 8, 4); mbar_init(BAR_OFULL, 8);
  }
  if (threadIdx.x == 96) {
    for (int i = 0; i < O_NST; i++) { mbar_init(BAR_GFULL + i * 8, 1); mbar_init(BAR_GEMPTY + i * 8, 2); }
    mbar_init(BAR_GOUT, 8);
    proxy_fence();
  }
  if (warp == 1 && threadIdx.x < 32 + 11) asm volatile("prefetch.tensormap [%0];" ::"l"(&p.x[0] + (threadIdx.x - 32)) : "memory");
  __syncthreads();
  if (warp >= 8) {
    asm volatile("setmaxnreg.dec.sync.aligned.u32 40;");
    if (warp == 8) {
      if (elect_one()) attn_producer(p, cta);
      __syncwarp();
    } else {
      const int epoch = *(volatile int*)&g_epoch[cta];
      attn_helper(p, warp - 9, cta, epoch);
      if (warp == 11 && elect_one()) *(volatile int*)&g_epoch[cta] = epoch + 1;
    }
    if (cta < N_OCTA) {
      bar_sync(4, 128);
      if (warp == 8) {
        if (elect_one()) oproj_producer(p, cta, *(volatile int*)&g_epoch[cta]);
      } else if (warp == 9) {
        if (elect_one()) oproj_storer(p, cta);
      }
    }
  } else {
    asm volatile("setmaxnreg.inc.sync.aligned.u32 232;");
    if (warp < 4) {
      attn_consumer<0>(cta);
      if (cta < N_OCTA) oproj_consumer<0>();
    } else {
      attn_consumer<1>(cta);
      if (cta < N_OCTA) oproj_consumer<1>();
    }
  }
}

typedef CUresult (*EncodeFn)(CUtensorMap*, CUtensorMapDataType, cuuint32_t, void*, const cuuint64_t*, const cuuint64_t*, const cuuint32_t*,
                             const cuuint32_t*, CUtensorMapInterleave, CUtensorMapSwizzle, CUtensorMapL2promotion, CUtensorMapFloatOOBfill);

void make3d(EncodeFn enc, CUtensorMap* m, const void* ptr, uint64_t rows, uint64_t cols, uint32_t box_rows, uint32_t box_blocks,
            CUtensorMapL2promotion promo = CU_TENSOR_MAP_L2_PROMOTION_L2_128B) {
  cuuint64_t gd[3] = {64, rows, cols / 64};
  cuuint64_t gs[2] = {cols * 2, 128};
  cuuint32_t bd[3] = {64, box_rows, box_blocks}, es[3] = {1, 1, 1};
  enc(m, CU_TENSOR_MAP_DATA_TYPE_BFLOAT16, 3, (void*)ptr, gd, gs, bd, es, CU_TENSOR_MAP_INTERLEAVE_NONE, CU_TENSOR_MAP_SWIZZLE_128B,
      promo, CU_TENSOR_MAP_FLOAT_OOB_FILL_NONE);
}
void make2d(EncodeFn enc, CUtensorMap* m, const void* ptr, uint64_t rows, uint64_t cols, uint32_t box_rows) {
  cuuint64_t gd[2] = {cols, rows};
  cuuint64_t gs[1] = {cols * 2};
  cuuint32_t bd[2] = {64, box_rows}, es[2] = {1, 1};
  enc(m, CU_TENSOR_MAP_DATA_TYPE_BFLOAT16, 2, (void*)ptr, gd, gs, bd, es, CU_TENSOR_MAP_INTERLEAVE_NONE, CU_TENSOR_MAP_SWIZZLE_128B,
      CU_TENSOR_MAP_L2_PROMOTION_L2_128B, CU_TENSOR_MAP_FLOAT_OOB_FILL_NONE);
}

}

extern "C" void kernel_launch(void* const* d_in, const int* in_sizes, int n_in, void* d_out, int out_size) {
  static EncodeFn enc = nullptr;
  if (!enc) {
    cudaDriverEntryPointQueryResult qr;
    cudaGetDriverEntryPoint("cuTensorMapEncodeTiled", (void**)&enc, cudaEnableDefault, &qr);
    cudaFuncSetAttribute(fused_kernel, cudaFuncAttributeMaxDynamicSharedMemorySize, SMEM_BYTES);
  }
  Params p;
  for (int s = 0; s < 2; s++) {
    make2d(enc, &p.x[s], d_in[5 * s + 0], NB * SQ, DM, SQ);
    make3d(enc, &p.k[s], d_in[5 * s + 1], (uint64_t)NB * NH * SK, DH, 64, 3);
    make3d(enc, &p.v[s], d_in[5 * s + 2], (uint64_t)NB * NH * SK, DH, 64, 3);
    make3d(enc, &p.wq[s], d_in[5 * s + 3], DM, NH * DH, 64, 3);
    make3d(enc, &p.wo[s], d_in[5 * s + 4], NH * DH, DM, 64, 5);
    p.xp[s] = (const __nv_bfloat16*)d_in[5 * s + 0];
    p.wqp[s] = (const __nv_bfloat16*)d_in[5 * s + 3];
    p.kp[s] = (const __nv_bfloat16*)d_in[5 * s + 1];
    p.vp[s] = (const __nv_bfloat16*)d_in[5 * s + 2];
  }
  make2d(enc, &p.out, d_out, NB * SQ, 2 * DM, 128);
  fused_kernel<<<NCTA, 384, SMEM_BYTES>>>(p);
}
```

```cpp
#include <cuda_runtime.h>
#include <cuda_bf16.h>
#include <cuda.h>
#include <stdint.h>

#define DEBUG_TIMEOUT 0

namespace {

constexpr int SQ = 160, DM = 640, NH = 32, SK = 512, DH = 192, NB = 16;
constexpr int NITEMS = 2 * NB * NH;
constexpr int NCTA = 132, N_OCTA = 32, N_ATT = NCTA - N_OCTA;
constexpr int ORING = 192, OFRESH = 800, STEP1 = 52, STEP2 = 57, STEP3 = 61;
constexpr int STAG_A0 = 15, STAG_SLOPE = 180, PERM_M = 41, PF_N = 32, PF_WAIT = 1500, PF_GAP = 300;
constexpr int OSLOTS = ORING + NITEMS - OFRESH;
#define W1_NG 3
constexpr int A_SLOT = 24576, B_SLOT = 20480, NSLOT = 5;
constexpr int OFF_A = 0;
constexpr int OFF_B = NSLOT * A_SLOT;
constexpr int O_STAGE = 61440, O_AB = 40960, O_NST = 3;
constexpr int OFF_L = OFF_B + NSLOT * B_SLOT;
constexpr int OFF_BAR = OFF_L + 160 * 4;
constexpr int SMEM_BYTES = OFF_BAR + 384 + 512;
static_assert(O_NST * O_STAGE <= OFF_L, "smem layout");
constexpr uint32_t SB = 1024;
constexpr uint32_t BARS = SB + OFF_BAR;
constexpr uint32_t BAR_FULLA = BARS, BAR_EMPTYA = BARS + 40, BAR_PMID = BARS + 80, BAR_EMPTYB = BARS + 120, BAR_XDONE = BARS + 160,
                   BAR_QH = BARS + 168, BAR_QM = BARS + 96, BAR_PFULL = BARS + 184, BAR_PFREE = BARS + 200, BAR_LFULL = BARS + 216,
                   BAR_OFULL = BARS + 224, BAR_GFULL = BARS + 248, BAR_GEMPTY = BARS + 280, BAR_GOUT = BARS + 312, BAR_GRED = BARS + 232, NEXT_ITEM = BARS + 320;
constexpr int O_ITEM_BYTES = SQ * DH * 2;

struct alignas(64) Params {
  CUtensorMap x[2], wq[2], k[2], v[2], wo[2], out, part;
  __nv_bfloat16* outp;
  const __nv_bfloat16 *xp[2], *wqp[2], *kp[2], *vp[2];
};

__device__ uint4 g_o[(size_t)OSLOTS * O_ITEM_BYTES / 16];
__device__ uint4 g_part[4 * NB * SQ * DM / 8];
__device__ int g_pcnt[N_OCTA];
__device__ int g_ready[NITEMS];
__device__ int g_done[NITEMS];
__device__ unsigned g_ticket;
__device__ int g_epoch[NCTA];

#define TLP(id)
#define TLG(id)
#define TL(id)
#define TL_FLUSH()
__device__ __forceinline__ uint32_t smem_u32(const void* p) { return (uint32_t)__cvta_generic_to_shared(p); }
__device__ __forceinline__ void wg_fence() { asm volatile("wgmma.fence.sync.aligned;" ::: "memory"); }
__device__ __forceinline__ void wg_commit() { asm volatile("wgmma.commit_group.sync.aligned;" ::: "memory"); }
template <int N> __device__ __forceinline__ void wg_wait() { asm volatile("wgmma.wait_group.sync.aligned %0;" ::"n"(N) : "memory"); }
template <int N> __device__ __forceinline__ void reg_fence(float (&d)[N]) {
#pragma unroll
  for (int i = 0; i < N; i++) asm volatile("" : "+f"(d[i])::"memory");
}
template <int N> __device__ __forceinline__ void zero_regs(float (&d)[N]) {
#pragma unroll
  for (int i = 0; i < N; i++) d[i] = 0.f;
}
__device__ __forceinline__ void proxy_fence() { asm volatile("fence.proxy.async.shared::cta;" ::: "memory"); }
__device__ __forceinline__ void mbar_init(uint32_t bar, int cnt) { asm volatile("mbarrier.init.shared::cta.b64 [%0], %1;" ::"r"(bar), "r"(cnt) : "memory"); }
__device__ __forceinline__ void mbar_arrive_if0(uint32_t bar, uint32_t sel) {
  asm volatile("{\n.reg .pred p;\nsetp.eq.u32 p, %1, 0;\n@p mbarrier.arrive.shared::cta.b64 _, [%0];\n}\n" ::"r"(bar), "r"(sel) : "memory");
}
__device__ __forceinline__ void mbar_arrive2_if0(uint32_t bar, uint32_t sel) {
  asm volatile("{\n.reg .pred p;\nsetp.eq.u32 p, %1, 0;\n@p mbarrier.arrive.shared::cta.b64 _, [%0], 2;\n}\n" ::"r"(bar), "r"(sel) : "memory");
}
__device__ __forceinline__ void mbar_expect(uint32_t bar, uint32_t bytes) {
  asm volatile("mbarrier.arrive.expect_tx.shared::cta.b64 _, [%0], %1;" ::"r"(bar), "r"(bytes) : "memory");
}
__device__ __forceinline__ void mbar_wait(int& bud, uint32_t bar, uint32_t parity) {
  asm volatile(
      "{\n.reg .pred p;\n"
      "LW:\n"
      "mbarrier.try_wait.parity.shared::cta.b64 p, [%0], %1;\n"
      "@!p bra LW;\n}\n" ::"r"(bar), "r"(parity) : "memory");
}
constexpr int WAIT_BUDGET = 1 << 22;
__device__ __forceinline__ bool elect_one() {
  uint32_t p;
  asm volatile("{\n.reg .pred p;\nelect.sync _|p, 0xffffffff;\nselp.u32 %0, 1, 0, p;\n}\n" : "=r"(p));
  return p;
}
__device__ __forceinline__ void tma2d(uint32_t dst, const CUtensorMap* m, uint32_t bar, int c0, int c1) {
  asm volatile("cp.async.bulk.tensor.2d.shared::cluster.global.mbarrier::complete_tx::bytes [%0], [%1, {%3, %4}], [%2];"
               ::"r"(dst), "l"(m), "r"(bar), "r"(c0), "r"(c1) : "memory");
}
__device__ __forceinline__ void tma3d(uint32_t dst, const CUtensorMap* m, uint32_t bar, int c0, int c1, int c2) {
  asm volatile("cp.async.bulk.tensor.3d.shared::cluster.global.mbarrier::complete_tx::bytes [%0], [%1, {%3, %4, %5}], [%2];"
               ::"r"(dst), "l"(m), "r"(bar), "r"(c0), "r"(c1), "r"(c2) : "memory");
}
__device__ __forceinline__ void tma3d_hint(uint32_t dst, const CUtensorMap* m, uint32_t bar, int c0, int c1, int c2, uint64_t pol) {
  asm volatile("cp.async.bulk.tensor.3d.shared::cluster.global.mbarrier::complete_tx::bytes.L2::cache_hint [%0], [%1, {%3, %4, %5}], [%2], %6;"
               ::"r"(dst), "l"(m), "r"(bar), "r"(c0), "r"(c1), "r"(c2), "l"(pol) : "memory");
}
__device__ __forceinline__ void bulk_load(uint32_t dst, const void* src, uint32_t bytes, uint32_t bar) {
  asm volatile("cp.async.bulk.shared::cluster.global.mbarrier::complete_tx::bytes [%0], [%1], %2, [%3];"
               ::"r"(dst), "l"(src), "r"(bytes), "r"(bar) : "memory");
}
__device__ __forceinline__ void tma_store2d(const CUtensorMap* m, uint32_t src, int c0, int c1) {
  asm volatile("cp.async.bulk.tensor.2d.global.shared::cta.bulk_group [%0, {%2, %3}], [%1];" ::"l"(m), "r"(src), "r"(c0), "r"(c1) : "memory");
}
__device__ __forceinline__ void bar_sync(int id, int n) { asm volatile("bar.sync %0, %1;" ::"r"(id), "r"(n) : "memory"); }
__device__ __forceinline__ void bar_arrive(int id, int n) { asm volatile("bar.arrive %0, %1;" ::"r"(id), "r"(n) : "memory"); }
__device__ __forceinline__ float ex2(float x) { float y; asm("ex2.approx.ftz.f32 %0, %1;" : "=f"(y) : "f"(x)); return y; }
__device__ __forceinline__ uint32_t pack2(float lo, float hi) { uint32_t r; asm("cvt.rn.bf16x2.f32 %0, %1, %2;" : "=r"(r) : "f"(hi), "f"(lo)); return r; }
__device__ __forceinline__ void stsm_t(uint32_t a, uint32_t r0, uint32_t r1, uint32_t r2, uint32_t r3) {
  asm volatile("stmatrix.sync.aligned.m8n8.x4.trans.shared.b16 [%0], {%1,%2,%3,%4};" ::"r"(a), "r"(r0), "r"(r1), "r"(r2), "r"(r3) : "memory");
}
__device__ __forceinline__ void flag_wait(int& bud, const int* p, int target) {
  while (true) {
    int v;
    asm volatile("ld.acquire.gpu.global.s32 %0, [%1];" : "=r"(v) : "l"(p) : "memory");
    if (v - target >= 0 || --bud <= 0) break;
    __nanosleep(64);
  }
}
__device__ __forceinline__ uint32_t lo_sw(uint32_t addr) { return (addr >> 4) | (1u << 16); }
__device__ __forceinline__ uint32_t lo_o(uint32_t addr) { return (addr >> 4) | (128u << 16); }
__device__ __forceinline__ uint32_t tid_x() { uint32_t t; asm volatile("mov.u32 %0, %tid.x;" : "=r"(t)); return t; }
__device__ __forceinline__ uint32_t opaque(uint32_t x) { uint32_t y; asm volatile("mov.u32 %0, %1;" : "=r"(y) : "r"(x)); return y; }

template <int TA, int TB, uint32_t OA, uint32_t OB>
__device__ __forceinline__ void mma160(float (&d)[80], uint32_t la, uint32_t lb) {
  asm volatile(
      "{\n.reg .pred p;\n.reg .b32 a, b;\n.reg .b64 da, db;\nsetp.eq.b32 p, 0, 0;\n"
      "add.u32 a, %80, %84;\nadd.u32 b, %81, %85;\nmov.b64 da, {a, 0x40000040};\nmov.b64 db, {b, %86};\n"
      "wgmma.mma_async.sync.aligned.m64n160k16.f32.bf16.bf16 {"
      "%0,%1,%2,%3,%4,%5,%6,%7,%8,%9,%10,%11,%12,%13,%14,%15,%16,%17,%18,%19,%20,%21,%22,%23,%24,%25,%26,%27,%28,%29,%30,%31,%32,%33,%34,%35,%36,"
      "%37,%38,%39,%40,%41,%42,%43,%44,%45,%46,%47,%48,%49,%50,%51,%52,%53,%54,%55,%56,%57,%58,%59,%60,%61,%62,%63,%64,%65,%66,%67,%68,%69,%70,%71,"
      "%72,%73,%74,%75,%76,%77,%78,%79"
      "}, da, db, p, 1, 1, %82, %83;\n}\n"
      :
      "+f"(d[0]),"+f"(d[1]),"+f"(d[2]),"+f"(d[3]),"+f"(d[4]),"+f"(d[5]),"+f"(d[6]),"+f"(d[7]),"+f"(d[8]),"+f"(d[9]),"+f"(d[10]),"+f"(d[11]),
      "+f"(d[12]),"+f"(d[13]),"+f"(d[14]),"+f"(d[15]),"+f"(d[16]),"+f"(d[17]),"+f"(d[18]),"+f"(d[19]),"+f"(d[20]),"+f"(d[21]),"+f"(d[22]),
      "+f"(d[23]),"+f"(d[24]),"+f"(d[25]),"+f"(d[26]),"+f"(d[27]),"+f"(d[28]),"+f"(d[29]),"+f"(d[30]),"+f"(d[31]),"+f"(d[32]),"+f"(d[33]),
      "+f"(d[34]),"+f"(d[35]),"+f"(d[36]),"+f"(d[37]),"+f"(d[38]),"+f"(d[39]),"+f"(d[40]),"+f"(d[41]),"+f"(d[42]),"+f"(d[43]),"+f"(d[44]),
      "+f"(d[45]),"+f"(d[46]),"+f"(d[47]),"+f"(d[48]),"+f"(d[49]),"+f"(d[50]),"+f"(d[51]),"+f"(d[52]),"+f"(d[53]),"+f"(d[54]),"+f"(d[55]),
      "+f"(d[56]),"+f"(d[57]),"+f"(d[58]),"+f"(d[59]),"+f"(d[60]),"+f"(d[61]),"+f"(d[62]),"+f"(d[63]),"+f"(d[64]),"+f"(d[65]),"+f"(d[66]),
      "+f"(d[67]),"+f"(d[68]),"+f"(d[69]),"+f"(d[70]),"+f"(d[71]),"+f"(d[72]),"+f"(d[73]),"+f"(d[74]),"+f"(d[75]),"+f"(d[76]),"+f"(d[77]),
      "+f"(d[78]),"+f"(d[79])
      : "r"(la), "r"(lb), "n"(TA), "n"(TB), "n"(OA >> 4), "n"(OB >> 4), "n"(TB ? 0xC0000010u : 0x40000040u));
}

template <int TA, int TB, uint32_t OA, uint32_t OB>
__device__ __forceinline__ void mma160z(float (&d)[80], uint32_t la, uint32_t lb) {
  asm volatile(
      "{\n.reg .pred p;\n.reg .b32 a, b;\n.reg .b64 da, db;\nsetp.ne.b32 p, 0, 0;\n"
      "add.u32 a, %80, %84;\nadd.u32 b, %81, %85;\nmov.b64 da, {a, 0x40000040};\nmov.b64 db, {b, %86};\n"
      "wgmma.mma_async.sync.aligned.m64n160k16.f32.bf16.bf16 {"
      "%0,%1,%2,%3,%4,%5,%6,%7,%8,%9,%10,%11,%12,%13,%14,%15,%16,%17,%18,%19,%20,%21,%22,%23,%24,%25,%26,%27,%28,%29,%30,%31,%32,%33,%34,%35,%36,"
      "%37,%38,%39,%40,%41,%42,%43,%44,%45,%46,%47,%48,%49,%50,%51,%52,%53,%54,%55,%56,%57,%58,%59,%60,%61,%62,%63,%64,%65,%66,%67,%68,%69,%70,%71,"
      "%72,%73,%74,%75,%76,%77,%78,%79"
      "}, da, db, p, 1, 1, %82, %83;\n}\n"
      :
      "=f"(d[0]),"=f"(d[1]),"=f"(d[2]),"=f"(d[3]),"=f"(d[4]),"=f"(d[5]),"=f"(d[6]),"=f"(d[7]),"=f"(d[8]),"=f"(d[9]),"=f"(d[10]),"=f"(d[11]),
      "=f"(d[12]),"=f"(d[13]),"=f"(d[14]),"=f"(d[15]),"=f"(d[16]),"=f"(d[17]),"=f"(d[18]),"=f"(d[19]),"=f"(d[20]),"=f"(d[21]),"=f"(d[22]),
      "=f"(d[23]),"=f"(d[24]),"=f"(d[25]),"=f"(d[26]),"=f"(d[27]),"=f"(d[28]),"=f"(d[29]),"=f"(d[30]),"=f"(d[31]),"=f"(d[32]),"=f"(d[33]),
      "=f"(d[34]),"=f"(d[35]),"=f"(d[36]),"=f"(d[37]),"=f"(d[38]),"=f"(d[39]),"=f"(d[40]),"=f"(d[41]),"=f"(d[42]),"=f"(d[43]),"=f"(d[44]),
      "=f"(d[45]),"=f"(d[46]),"=f"(d[47]),"=f"(d[48]),"=f"(d[49]),"=f"(d[50]),"=f"(d[51]),"=f"(d[52]),"=f"(d[53]),"=f"(d[54]),"=f"(d[55]),
      "=f"(d[56]),"=f"(d[57]),"=f"(d[58]),"=f"(d[59]),"=f"(d[60]),"=f"(d[61]),"=f"(d[62]),"=f"(d[63]),"=f"(d[64]),"=f"(d[65]),"=f"(d[66]),
      "=f"(d[67]),"=f"(d[68]),"=f"(d[69]),"=f"(d[70]),"=f"(d[71]),"=f"(d[72]),"=f"(d[73]),"=f"(d[74]),"=f"(d[75]),"=f"(d[76]),"=f"(d[77]),
      "=f"(d[78]),"=f"(d[79])
      : "r"(la), "r"(lb), "n"(TA), "n"(TB), "n"(OA >> 4), "n"(OB >> 4), "n"(TB ? 0xC0000010u : 0x40000040u));
}

template <int TA, int TB, uint32_t OA, uint32_t OB>
__device__ __forceinline__ void mma80(float (&d)[40], uint32_t la, uint32_t lb) {
  asm volatile(
      "{\n.reg .pred p;\n.reg .b32 a, b;\n.reg .b64 da, db;\nsetp.eq.b32 p, 0, 0;\n"
      "add.u32 a, %40, %44;\nadd.u32 b, %41, %45;\nmov.b64 da, {a, 0x40000040};\nmov.b64 db, {b, %46};\n"
      "wgmma.mma_async.sync.aligned.m64n80k16.f32.bf16.bf16 {"
      "%0,%1,%2,%3,%4,%5,%6,%7,%8,%9,%10,%11,%12,%13,%14,%15,%16,%17,%18,%19,%20,%21,%22,%23,%24,%25,%26,%27,%28,%29,%30,%31,%32,%33,%34,%35,%36,"
      "%37,%38,%39"
      "}, da, db, p, 1, 1, %42, %43;\n}\n"
      :
      "+f"(d[0]),"+f"(d[1]),"+f"(d[2]),"+f"(d[3]),"+f"(d[4]),"+f"(d[5]),"+f"(d[6]),"+f"(d[7]),"+f"(d[8]),"+f"(d[9]),"+f"(d[10]),"+f"(d[11]),
      "+f"(d[12]),"+f"(d[13]),"+f"(d[14]),"+f"(d[15]),"+f"(d[16]),"+f"(d[17]),"+f"(d[18]),"+f"(d[19]),"+f"(d[20]),"+f"(d[21]),"+f"(d[22]),
      "+f"(d[23]),"+f"(d[24]),"+f"(d[25]),"+f"(d[26]),"+f"(d[27]),"+f"(d[28]),"+f"(d[29]),"+f"(d[30]),"+f"(d[31]),"+f"(d[32]),"+f"(d[33]),
      "+f"(d[34]),"+f"(d[35]),"+f"(d[36]),"+f"(d[37]),"+f"(d[38]),"+f"(d[39])
      : "r"(la), "r"(lb), "n"(TA), "n"(TB), "n"(OA >> 4), "n"(OB >> 4), "n"(TB ? 0xC0000010u : 0x40000040u));
}

template <int TA, int TB, uint32_t OA, uint32_t OB>
__device__ __forceinline__ void mma80z(float (&d)[40], uint32_t la, uint32_t lb) {
  asm volatile(
      "{\n.reg .pred p;\n.reg .b32 a, b;\n.reg .b64 da, db;\nsetp.ne.b32 p, 0, 0;\n"
      "add.u32 a, %40, %44;\nadd.u32 b, %41, %45;\nmov.b64 da, {a, 0x40000040};\nmov.b64 db, {b, %46};\n"
      "wgmma.mma_async.sync.aligned.m64n80k16.f32.bf16.bf16 {"
      "%0,%1,%2,%3,%4,%5,%6,%7,%8,%9,%10,%11,%12,%13,%14,%15,%16,%17,%18,%19,%20,%21,%22,%23,%24,%25,%26,%27,%28,%29,%30,%31,%32,%33,%34,%35,%36,"
      "%37,%38,%39"
      "}, da, db, p, 1, 1, %42, %43;\n}\n"
      :
      "=f"(d[0]),"=f"(d[1]),"=f"(d[2]),"=f"(d[3]),"=f"(d[4]),"=f"(d[5]),"=f"(d[6]),"=f"(d[7]),"=f"(d[8]),"=f"(d[9]),"=f"(d[10]),"=f"(d[11]),
      "=f"(d[12]),"=f"(d[13]),"=f"(d[14]),"=f"(d[15]),"=f"(d[16]),"=f"(d[17]),"=f"(d[18]),"=f"(d[19]),"=f"(d[20]),"=f"(d[21]),"=f"(d[22]),
      "=f"(d[23]),"=f"(d[24]),"=f"(d[25]),"=f"(d[26]),"=f"(d[27]),"=f"(d[28]),"=f"(d[29]),"=f"(d[30]),"=f"(d[31]),"=f"(d[32]),"=f"(d[33]),
      "=f"(d[34]),"=f"(d[35]),"=f"(d[36]),"=f"(d[37]),"=f"(d[38]),"=f"(d[39])
      : "r"(la), "r"(lb), "n"(TA), "n"(TB), "n"(OA >> 4), "n"(OB >> 4), "n"(TB ? 0xC0000010u : 0x40000040u));
}

template <int TA, int TB, uint32_t OA, uint32_t OB>
__device__ __forceinline__ void mma160r(float (&d)[80], uint32_t la, uint32_t lb, int sc) {
  asm volatile(
      "{\n.reg .pred p;\n.reg .b32 a, b;\n.reg .b64 da, db;\nsetp.ne.b32 p, %87, 0;\n"
      "add.u32 a, %80, %84;\nadd.u32 b, %81, %85;\nmov.b64 da, {a, 0x40000040};\nmov.b64 db, {b, %86};\n"
      "wgmma.mma_async.sync.aligned.m64n160k16.f32.bf16.bf16 {"
      "%0,%1,%2,%3,%4,%5,%6,%7,%8,%9,%10,%11,%12,%13,%14,%15,%16,%17,%18,%19,%20,%21,%22,%23,%24,%25,%26,%27,%28,%29,%30,%31,%32,%33,%34,%35,%36,"
      "%37,%38,%39,%40,%41,%42,%43,%44,%45,%46,%47,%48,%49,%50,%51,%52,%53,%54,%55,%56,%57,%58,%59,%60,%61,%62,%63,%64,%65,%66,%67,%68,%69,%70,%71,"
      "%72,%73,%74,%75,%76,%77,%78,%79"
      "}, da, db, p, 1, 1, %82, %83;\n}\n"
      :
      "+f"(d[0]),"+f"(d[1]),"+f"(d[2]),"+f"(d[3]),"+f"(d[4]),"+f"(d[5]),"+f"(d[6]),"+f"(d[7]),"+f"(d[8]),"+f"(d[9]),"+f"(d[10]),"+f"(d[11]),
      "+f"(d[12]),"+f"(d[13]),"+f"(d[14]),"+f"(d[15]),"+f"(d[16]),"+f"(d[17]),"+f"(d[18]),"+f"(d[19]),"+f"(d[20]),"+f"(d[21]),"+f"(d[22]),
      "+f"(d[23]),"+f"(d[24]),"+f"(d[25]),"+f"(d[26]),"+f"(d[27]),"+f"(d[28]),"+f"(d[29]),"+f"(d[30]),"+f"(d[31]),"+f"(d[32]),"+f"(d[33]),
      "+f"(d[34]),"+f"(d[35]),"+f"(d[36]),"+f"(d[37]),"+f"(d[38]),"+f"(d[39]),"+f"(d[40]),"+f"(d[41]),"+f"(d[42]),"+f"(d[43]),"+f"(d[44]),
      "+f"(d[45]),"+f"(d[46]),"+f"(d[47]),"+f"(d[48]),"+f"(d[49]),"+f"(d[50]),"+f"(d[51]),"+f"(d[52]),"+f"(d[53]),"+f"(d[54]),"+f"(d[55]),
      "+f"(d[56]),"+f"(d[57]),"+f"(d[58]),"+f"(d[59]),"+f"(d[60]),"+f"(d[61]),"+f"(d[62]),"+f"(d[63]),"+f"(d[64]),"+f"(d[65]),"+f"(d[66]),
      "+f"(d[67]),"+f"(d[68]),"+f"(d[69]),"+f"(d[70]),"+f"(d[71]),"+f"(d[72]),"+f"(d[73]),"+f"(d[74]),"+f"(d[75]),"+f"(d[76]),"+f"(d[77]),
      "+f"(d[78]),"+f"(d[79])
      : "r"(la), "r"(lb), "n"(TA), "n"(TB), "n"(OA >> 4), "n"(OB >> 4), "n"(TB ? 0xC0000010u : 0x40000040u), "r"(sc));
}

template <int TA, int TB, uint32_t OA, uint32_t OB>
__device__ __forceinline__ void mma80r(float (&d)[40], uint32_t la, uint32_t lb, int sc) {
  asm volatile(
      "{\n.reg .pred p;\n.reg .b32 a, b;\n.reg .b64 da, db;\nsetp.ne.b32 p, %47, 0;\n"
      "add.u32 a, %40, %44;\nadd.u32 b, %41, %45;\nmov.b64 da, {a, 0x40000040};\nmov.b64 db, {b, %46};\n"
      "wgmma.mma_async.sync.aligned.m64n80k16.f32.bf16.bf16 {"
      "%0,%1,%2,%3,%4,%5,%6,%7,%8,%9,%10,%11,%12,%13,%14,%15,%16,%17,%18,%19,%20,%21,%22,%23,%24,%25,%26,%27,%28,%29,%30,%31,%32,%33,%34,%35,%36,"
      "%37,%38,%39"
      "}, da, db, p, 1, 1, %42, %43;\n}\n"
      :
      "+f"(d[0]),"+f"(d[1]),"+f"(d[2]),"+f"(d[3]),"+f"(d[4]),"+f"(d[5]),"+f"(d[6]),"+f"(d[7]),"+f"(d[8]),"+f"(d[9]),"+f"(d[10]),"+f"(d[11]),
      "+f"(d[12]),"+f"(d[13]),"+f"(d[14]),"+f"(d[15]),"+f"(d[16]),"+f"(d[17]),"+f"(d[18]),"+f"(d[19]),"+f"(d[20]),"+f"(d[21]),"+f"(d[22]),
      "+f"(d[23]),"+f"(d[24]),"+f"(d[25]),"+f"(d[26]),"+f"(d[27]),"+f"(d[28]),"+f"(d[29]),"+f"(d[30]),"+f"(d[31]),"+f"(d[32]),"+f"(d[33]),
      "+f"(d[34]),"+f"(d[35]),"+f"(d[36]),"+f"(d[37]),"+f"(d[38]),"+f"(d[39])
      : "r"(la), "r"(lb), "n"(TA), "n"(TB), "n"(OA >> 4), "n"(OB >> 4), "n"(TB ? 0xC0000010u : 0x40000040u), "r"(sc));
}

struct Ring { uint32_t s0, ph0; };
__device__ __forceinline__ void ring_pos(const Ring& r, int i, uint32_t& slot, uint32_t& ph) {
  uint32_t s = opaque(r.s0) + (i % NSLOT);
  uint32_t wrap = s >= NSLOT;
  slot = s - (wrap ? NSLOT : 0);
  ph = r.ph0 ^ ((i / NSLOT) & 1) ^ wrap;
}
__device__ __forceinline__ void ring_advance(Ring& r, int n) {
  uint32_t s, p;
  ring_pos(r, n, s, p);
  r.s0 = s; r.ph0 = p;
}
__host__ __device__ constexpr int idxK(int j) { return j == 0 ? 10 : 9 + 2 * j; }
__host__ __device__ constexpr int idxV(int j) { return j == 7 ? 25 : 12 + 2 * j; }
__host__ __device__ constexpr int xs(int c) { return c % NSLOT; }

__device__ __forceinline__ int start_delay(int cta) {
  return max(0, ((cta - N_OCTA) | 1) - STAG_A0) * STAG_SLOPE;
}
__device__ __forceinline__ char* o_slot(int item) {
  return (char*)g_o + (size_t)(item < OFRESH ? item % ORING : item - OFRESH + ORING) * O_ITEM_BYTES;
}
__device__ __forceinline__ int next_item(uint32_t a = NEXT_ITEM) {
  int v;
  asm volatile("ld.shared.s32 %0, [%1];" : "=r"(v) : "r"(a) : "memory");
  return __shfl_sync(0xffffffffu, v, 0);
}

template <int W, bool ACC>
__device__ __forceinline__ void mma_main(float (&d)[80], uint32_t aaddr, uint32_t baddr) {
  const uint32_t la = lo_sw(aaddr), lb = lo_sw(baddr);
  if (ACC) mma160<1, 0, W * 16384, 0>(d, la, lb); else mma160z<1, 0, W * 16384, 0>(d, la, lb);
  mma160<1, 0, W * 16384 + 1 * 2048, 1 * 32>(d, la, lb);
  mma160<1, 0, W * 16384 + 2 * 2048, 2 * 32>(d, la, lb);
  mma160<1, 0, W * 16384 + 3 * 2048, 3 * 32>(d, la, lb);
}
template <int W, bool ACC>
__device__ __forceinline__ void mma_mid(float (&d)[40], uint32_t aaddr, uint32_t baddr) {
  const uint32_t la = lo_sw(aaddr), lb = lo_sw(baddr);
  if (ACC) mma80<1, 0, 8192, W * 10240>(d, la, lb); else mma80z<1, 0, 8192, W * 10240>(d, la, lb);
  mma80<1, 0, 8192 + 1 * 2048, W * 10240 + 1 * 32>(d, la, lb);
  mma80<1, 0, 8192 + 2 * 2048, W * 10240 + 2 * 32>(d, la, lb);
  mma80<1, 0, 8192 + 3 * 2048, W * 10240 + 3 * 32>(d, la, lb);
}
template <int W, bool ACC>
__device__ __forceinline__ void mma_both(float (&dm)[80], float (&dh)[40], uint32_t aaddr, uint32_t baddr) {
  mma_mid<W, ACC>(dh, aaddr, baddr);
  mma_main<W, ACC>(dm, aaddr, baddr);
}
template <int KB, bool ACC>
__device__ __forceinline__ void s_mma(float (&sacc)[80], uint32_t kaddr) {
  const uint32_t la = lo_sw(kaddr), lb = lo_sw(SB + OFF_B);
  if (ACC) mma160<0, 0, KB * 8192, KB * B_SLOT>(sacc, la, lb); else mma160z<0, 0, KB * 8192, KB * B_SLOT>(sacc, la, lb);
  mma160<0, 0, KB * 8192 + 32, KB * B_SLOT + 32>(sacc, la, lb);
  mma160<0, 0, KB * 8192 + 64, KB * B_SLOT + 64>(sacc, la, lb);
  mma160<0, 0, KB * 8192 + 96, KB * B_SLOT + 96>(sacc, la, lb);
}
template <int N>
__device__ __forceinline__ void store_scaled(uint32_t addr, const float (&d)[N], float sc) {
#pragma unroll
  for (int J = 0; J < N / 8; J++)
    stsm_t(addr + J * 2048, pack2(d[8 * J] * sc, d[8 * J + 1] * sc), pack2(d[8 * J + 2] * sc, d[8 * J + 3] * sc),
           pack2(d[8 * J + 4] * sc, d[8 * J + 5] * sc), pack2(d[8 * J + 6] * sc, d[8 * J + 7] * sc));
}
__device__ __forceinline__ float4 lds_f4(uint32_t a) {
  float4 v;
  asm volatile("ld.shared.v4.f32 {%0,%1,%2,%3}, [%4];" : "=f"(v.x), "=f"(v.y), "=f"(v.z), "=f"(v.w) : "r"(a) : "memory");
  return v;
}
__device__ __forceinline__ void norm_pack(uint32_t* p, const float* d, const float4& i) {
  p[0] = pack2(d[0] * i.x, d[1] * i.y); p[1] = pack2(d[4] * i.z, d[5] * i.w);
  p[2] = pack2(d[2] * i.x, d[3] * i.y); p[3] = pack2(d[6] * i.z, d[7] * i.w);
  asm volatile("" : "+r"(p[0]), "+r"(p[1]), "+r"(p[2]), "+r"(p[3])::"memory");
}
template <int W>
__device__ __forceinline__ void pack_first(uint32_t (&pk)[60], const float (&om)[80], const float (&oh)[40], uint32_t laddr) {
  float4 n0 = lds_f4(laddr + W * 80), n1 = lds_f4(laddr + W * 80 + 16);
#pragma unroll
  for (int J = 0; J < 5; J++) {
    const float4 i = n0;
    n0 = n1;
    if (J + 2 < 5) n1 = lds_f4(laddr + W * 80 + (J + 2) * 16);
    norm_pack(&pk[20 + 4 * J], &om[8 * (5 * W + J)], i);
    norm_pack(&pk[4 * J], &oh[8 * J], i);
  }
}
template <int W, int J0, int J1>
__device__ __forceinline__ void pack_second(uint32_t (&pk)[60], const float (&om)[80], uint32_t laddr) {
  float4 n[J1 - J0];
#pragma unroll
  for (int J = J0; J < J1; J++) n[J - J0] = lds_f4(laddr + (1 - W) * 80 + J * 16);
#pragma unroll
  for (int J = J0; J < J1; J++) norm_pack(&pk[40 + 4 * J], &om[8 * (5 * (1 - W) + J)], n[J - J0]);
}
__device__ __forceinline__ char* o_ptr(int item) {
  const uint32_t t = tid_x();
  return o_slot(item) + ((t & 96) * 16 + (t & 28) * 8 + ((((t >> 1) ^ (t >> 4)) & 1) << 4) + (t & 1) * 8);
}
template <int W, int G0, int G1>
__device__ __forceinline__ void store_groups(char* op, const uint32_t (&pk)[60], uint32_t on) {
#pragma unroll
  for (int G = G0; G < G1; G++) {
    const int off = (G < 5 ? 1 : 2 * W) * B_SLOT + (5 * (G < 10 ? W : 1 - W) + G % 5) * 2048;
    asm volatile("{\n.reg .pred p;\nsetp.ne.u32 p, %5, 0;\n@p st.global.v2.b32 [%0], {%1, %2};\n@p st.global.v2.b32 [%0+256], {%3, %4};\n}\n"
                 ::"l"(op + off), "r"(pk[4 * G]), "r"(pk[4 * G + 1]), "r"(pk[4 * G + 2]), "r"(pk[4 * G + 3]), "r"(on) : "memory");
  }
}
__device__ __forceinline__ void publish_generic(uint32_t bar, int lane) {
  __syncwarp();
  mbar_arrive_if0(bar, lane);
}
__device__ __forceinline__ void publish(uint32_t bar, int lane) {
  proxy_fence();
  __syncwarp();
  mbar_arrive_if0(bar, lane);
}

#define A_ADDR(s) (SB + OFF_A + (s) * A_SLOT)
#define B_ADDR(s) (SB + OFF_B + (s) * B_SLOT)
#define WAIT_CHUNK(c, ro, sA)                \
  uint32_t sA;                               \
  {                                          \
    uint32_t pA_;                            \
    ring_pos(ring, (ro) + (c), sA, pA_);     \
    mbar_wait(bud, BAR_FULLA + sA * 8, pA_); \
  }
#define RELEASE_CHUNK(c, sA)                                  \
  mbar_arrive_if0(BAR_EMPTYA + (sA) * 8, tid);                \
  if ((c) < NSLOT) mbar_arrive_if0(BAR_EMPTYB + xs(c) * 8, tid);

template <int W>
__device__ __forceinline__ int attn_consumer(int item) {
  int bud = WAIT_BUDGET;
  const int tid = threadIdx.x & 127, lane = tid & 31, warp = tid >> 5;
  const uint32_t st_off = ((lane & 7) + 8 * (lane >> 4)) * 128 + (((2 * warp + ((lane >> 3) & 1)) ^ (lane & 7)) << 4);
  const uint32_t laddr = SB + OFF_L + (lane & 3) * 160;
  float om[80], oh[40], sacc[80];
  uint32_t pk[60];
#pragma unroll
  for (int i = 0; i < 40; i++) pk[i] = 0;
  zero_regs(om);
  Ring ring{0u, 0u};
  uint32_t par = 0;
  int prev = 0;
  const float qscale = 0.07216878364870322f * 1.4426950408889634f;
  constexpr uint32_t pown = B_ADDR(3 + W), poth = B_ADDR(4 - W);
  TL(0); TLG(62);
  {
    WAIT_CHUNK(0, 0, s0)
    wg_fence();
    mma_both<W, false>(sacc, oh, A_ADDR(s0), B_ADDR(xs(0)));
    wg_commit();
    WAIT_CHUNK(1, 0, s1)
    wg_fence();
    mma_both<W, true>(sacc, oh, A_ADDR(s1), B_ADDR(xs(1)));
    wg_commit();
    wg_wait<1>();
    RELEASE_CHUNK(0, s0)
  }
#pragma unroll 1
  for (int it = 0;; it++) {
    char* op = o_ptr(prev);
#pragma unroll
    for (int c = 2; c < 8 - W; c++) {
      WAIT_CHUNK(c, 0, sA)
      TL(40 + c);
      wg_fence();
      mma_both<W, true>(sacc, oh, A_ADDR(sA), B_ADDR(xs(c)));
      wg_commit();
      wg_wait<1>();
      uint32_t sP, pP;
      ring_pos(ring, c - 1, sP, pP);
      RELEASE_CHUNK(c - 1, sP)
      constexpr int NG = W == 0 ? 3 : W1_NG;
      if (c == 2) { pack_second<W, 0, 1>(pk, om, laddr); store_groups<W, 0 * NG, 1 * NG>(op, pk, it); }
      if (c == 3) { pack_second<W, 1, 2>(pk, om, laddr); store_groups<W, 1 * NG, 2 * NG>(op, pk, it); }
      if (c == 4) { pack_second<W, 2, 3>(pk, om, laddr); store_groups<W, 2 * NG, 3 * NG>(op, pk, it); }
      if (c == 5) { pack_second<W, 3, 4>(pk, om, laddr); store_groups<W, 3 * NG, 4 * NG>(op, pk, it); }
      if (c == 6) {
        pack_second<W, 4, 5>(pk, om, laddr);
        if (W == 1) {
          wg_wait<0>();
          RELEASE_CHUNK(6, sA)
          mbar_arrive_if0(BAR_XDONE, tid);
        }
        store_groups<W, 4 * NG, 15>(op, pk, it);
        __syncwarp();
        mbar_arrive_if0(BAR_OFULL, lane | (it == 0));
      }
    }
    uint32_t sK0, pK0, s7, p7;
    ring_pos(ring, idxK(W), sK0, pK0);
    ring_pos(ring, 7, s7, p7);
    if (W == 1) mbar_wait(bud, BAR_FULLA + s7 * 8, p7);
    WAIT_CHUNK(8, 0, s8)
    WAIT_CHUNK(9, 0, s9)
    TL(48);
    if (W == 0) {
      wg_fence();
      mma_mid<W, true>(oh, A_ADDR(s8), B_ADDR(xs(8)));
      mma_mid<W, true>(oh, A_ADDR(s9), B_ADDR(xs(9)));
      wg_commit();
      wg_wait<1>();
      RELEASE_CHUNK(7, s7)
      wg_fence();
      mma_main<W, true>(sacc, A_ADDR(s8), B_ADDR(xs(8)));
      mma_main<W, true>(sacc, A_ADDR(s9), B_ADDR(xs(9)));
      wg_commit();
      bar_arrive(5, 256);
      TL(49);
      wg_wait<1>();
      reg_fence(oh);
      mbar_wait(bud, BAR_XDONE, par);
      store_scaled(B_ADDR(1) + st_off, oh, qscale);
    } else {
      bar_sync(5, 256);
      wg_fence();
      mma_mid<W, true>(oh, A_ADDR(s7), B_ADDR(xs(7)));
      mma_mid<W, true>(oh, A_ADDR(s8), B_ADDR(xs(8)));
      mma_mid<W, true>(oh, A_ADDR(s9), B_ADDR(xs(9)));
      wg_commit();
      mma_main<W, true>(sacc, A_ADDR(s7), B_ADDR(xs(7)));
      wg_commit();
      mma_main<W, true>(sacc, A_ADDR(s8), B_ADDR(xs(8)));
      wg_commit();
      wg_wait<2>();
      reg_fence(oh);
      store_scaled(B_ADDR(1) + 10240 + st_off, oh, qscale);
      wg_fence();
      mma_main<W, true>(sacc, A_ADDR(s9), B_ADDR(xs(9)));
      wg_commit();
      bar_arrive(8, 256);
      TL(49);
      wg_wait<2>();
      RELEASE_CHUNK(7, s7)
      publish(BAR_QH, lane);
    }
    wg_wait<0>();
    reg_fence(sacc);
    TL(1);
    RELEASE_CHUNK(8, s8)
    RELEASE_CHUNK(9, s9)
    store_scaled(B_ADDR(2 * W) + st_off, sacc, qscale);
    if (W == 1) publish(BAR_QM, lane); else proxy_fence();
    TL(2);
    uint32_t sK = sK0, sV1 = 0;
    if (W == 0) {
      zero_regs(om); zero_regs(oh);
      reg_fence(om); reg_fence(oh);
      mbar_wait(bud, BAR_FULLA + sK0 * 8, pK0);
      bar_sync(8, 256);
      wg_fence();
      s_mma<0, false>(sacc, A_ADDR(sK));
      mbar_wait(bud, BAR_QH, par);
      TL(3);
      wg_fence();
      s_mma<1, true>(sacc, A_ADDR(sK));
      mbar_wait(bud, BAR_QM, par);
      TL(5);
      wg_fence();
      s_mma<2, true>(sacc, A_ADDR(sK));
      wg_commit();
      wg_commit();
      bar_arrive(2, 256);
    } else {
      uint32_t pV1;
      ring_pos(ring, idxV(0), sV1, pV1);
      mbar_wait(bud, BAR_FULLA + sK * 8, pK0);
      bar_sync(2, 256);
      wg_fence();
      s_mma<0, false>(sacc, A_ADDR(sK));
      s_mma<1, true>(sacc, A_ADDR(sK));
      s_mma<2, true>(sacc, A_ADDR(sK));
      wg_commit();
      TL(6);
      mbar_wait(bud, BAR_FULLA + sV1 * 8, pV1);
      mbar_wait(bud, BAR_PFULL, 0);
      TL(7);
      wg_fence();
      mma_both<W, false>(om, oh, A_ADDR(sV1), poth);
      wg_commit();
      bar_arrive(1, 256);
    }
    Ring rv;
    ring_pos(ring, idxV(W), rv.s0, rv.ph0);
#pragma unroll 1
    for (int jj = 0;; jj++) {
      wg_wait<1>();
      reg_fence(sacc);
      TL(8 + jj * 7);
      mbar_arrive2_if0(BAR_EMPTYA + sK * 8, tid);
      mbar_arrive_if0(BAR_EMPTYB + tid * 8, (tid >= 3) | (jj != 3));
#pragma unroll
      for (int J = 0; J < 10; J++) {
        stsm_t(pown + st_off + J * 2048, pack2(ex2(sacc[8 * J]), ex2(sacc[8 * J + 1])), pack2(ex2(sacc[8 * J + 2]), ex2(sacc[8 * J + 3])),
               pack2(ex2(sacc[8 * J + 4]), ex2(sacc[8 * J + 5])), pack2(ex2(sacc[8 * J + 6]), ex2(sacc[8 * J + 7])));
        if (W == 1 && (J == 2 || J == 5)) publish_generic(BAR_PMID + (J / 3) * 8, lane | (jj != 3));
        if (J == 4) {
          wg_wait<0>();
          mbar_arrive_if0(BAR_EMPTYA + sV1 * 8, tid | (W == 0 && jj == 0));
        }
      }
      publish(BAR_PFULL + W * 8, lane);
      TL(10 + jj * 7);
      if (jj == 3) break;
      uint32_t pK, pV1;
      ring_pos(rv, 1, sK, pK);
      ring_pos(rv, 2, sV1, pV1);
      mbar_wait(bud, BAR_FULLA + rv.s0 * 8, rv.ph0);
      bar_sync(1 + W, 256);
      wg_fence();
      mma_both<W, true>(om, oh, A_ADDR(rv.s0), pown);
      wg_commit();
      mbar_wait(bud, BAR_FULLA + sK * 8, pK);
      TL(11 + jj * 7);
      wg_fence();
      s_mma<0, false>(sacc, A_ADDR(sK));
      s_mma<1, true>(sacc, A_ADDR(sK));
      wg_commit();
      wg_wait<1>();
      mbar_arrive_if0(BAR_EMPTYA + rv.s0 * 8, tid);
      wg_fence();
      s_mma<2, true>(sacc, A_ADDR(sK));
      wg_commit();
      TL(13 + jj * 7);
      mbar_wait(bud, BAR_FULLA + sV1 * 8, pV1);
      mbar_wait(bud, BAR_PFREE + W * 8, jj & 1);
      mbar_wait(bud, BAR_PFULL + (1 - W) * 8, (jj + W) & 1);
      TL(14 + jj * 7);
      wg_fence();
      mma_both<W, true>(om, oh, A_ADDR(sV1), poth);
      wg_commit();
      bar_arrive(2 - W, 256);
      ring_advance(rv, 4);
    }
    uint32_t sV7, pV7;
    ring_pos(ring, idxV(7), sV7, pV7);
    prev = item;
    if (W == 1 && !DEBUG_TIMEOUT) item = next_item();
    if (W == 0) {
      uint32_t sV6, pV6;
      ring_pos(ring, idxV(6), sV6, pV6);
      mbar_wait(bud, BAR_FULLA + sV6 * 8, pV6);
      bar_sync(1, 256);
      wg_fence();
      mma_both<0, true>(om, oh, A_ADDR(sV6), pown);
      wg_commit();
      mbar_wait(bud, BAR_FULLA + sV7 * 8, pV7);
      wg_wait<0>();
      mbar_arrive_if0(BAR_EMPTYA + sV6 * 8, tid);
      mbar_wait(bud, BAR_PFULL + 8, 1);
      wg_fence();
      mma_both<0, true>(om, oh, A_ADDR(sV7), poth);
      wg_commit();
      bar_arrive(6, 256);
    } else {
      mbar_wait(bud, BAR_FULLA + sV7 * 8, pV7);
      bar_sync(6, 256);
    }
    TL(32);
    if (DEBUG_TIMEOUT) item = next_item(NEXT_ITEM + 4);
    else if (W == 0) item = next_item();
    if (item >= NITEMS) {
      if (W == 1) {
        wg_fence();
        mma_both<1, true>(om, oh, A_ADDR(sV7), pown);
        wg_commit();
      }
      wg_wait<0>();
      reg_fence(om); reg_fence(oh);
      TL(33);
      mbar_wait(bud, BAR_LFULL, par);
      TL(34);
      pack_first<W>(pk, om, oh, laddr);
      op = o_ptr(prev);
      store_groups<W, 0, 10>(op, pk, 1);
      pack_second<W, 0, 5>(pk, om, laddr);
      store_groups<W, 10, 15>(op, pk, 1);
      publish_generic(BAR_OFULL, lane);
      TL(35); TLG(63);
      TL_FLUSH();
      return item;
    }
    {
      if (W == 1) {
        wg_fence();
        mma_both<1, true>(om, oh, A_ADDR(sV7), pown);
        wg_commit();
      }
      WAIT_CHUNK(0, 26, s0)
      WAIT_CHUNK(1, 26, s1)
      if (W == 0) {
        wg_wait<0>();
        reg_fence(om); reg_fence(oh);
        TL(33);
        wg_fence();
        mma_main<W, false>(sacc, A_ADDR(s0), B_ADDR(xs(0)));
        wg_commit();
      } else {
        wg_fence();
        mma_main<W, false>(sacc, A_ADDR(s0), B_ADDR(xs(0)));
        mma_main<W, true>(sacc, A_ADDR(s1), B_ADDR(xs(1)));
        wg_commit();
        wg_wait<1>();
        reg_fence(om); reg_fence(oh);
        TL(33);
      }
      mbar_arrive_if0(BAR_EMPTYA + sV7 * 8, tid);
      mbar_wait(bud, BAR_LFULL, par);
      mbar_arrive_if0(BAR_EMPTYB + 24 + tid * 8, tid >= 2);
      TL(34);
      pack_first<W>(pk, om, oh, laddr);
      TL(36);
      wg_fence();
      mma_mid<W, false>(oh, A_ADDR(s0), B_ADDR(xs(0)));
      wg_commit();
      mma_mid<W, true>(oh, A_ADDR(s1), B_ADDR(xs(1)));
      if (W == 0) mma_main<W, true>(sacc, A_ADDR(s1), B_ADDR(xs(1)));
      wg_commit();
      TL(37);
      wg_wait<1>();
      RELEASE_CHUNK(0, s0)
      TL(35); TLG(63);
    }
    TL_FLUSH();
    TL(0); TLG(62);
    ring_advance(ring, 26);
    par ^= 1;
  }
}

__device__ __forceinline__ uint4 lds128(uint32_t a) {
  uint4 v;
  asm volatile("ld.shared.v4.b32 {%0,%1,%2,%3}, [%4];" : "=r"(v.x), "=r"(v.y), "=r"(v.z), "=r"(v.w) : "r"(a) : "memory");
  return v;
}
__device__ __forceinline__ void acc2(float& s, float& t, uint32_t w) {
  s += __uint_as_float(w << 16);
  t += __uint_as_float(w & 0xffff0000u);
}
__device__ __forceinline__ uint32_t badd2(uint32_t a, uint32_t b) { uint32_t r; asm("add.rn.bf16x2 %0, %1, %2;" : "=r"(r) : "r"(a), "r"(b)); return r; }
__device__ __forceinline__ void sum_unit(float& acc, uint32_t pb) {
  const uint4 v0 = lds128(pb), v1 = lds128(pb ^ 32), v2 = lds128(pb ^ 64), v3 = lds128(pb ^ 96);
  const uint32_t w0 = badd2(v0.x, v0.y), w1 = badd2(v0.z, v0.w);
  float s0 = acc + __uint_as_float(w0 << 16), t0 = __uint_as_float(w0 & 0xffff0000u);
  float s1 = __uint_as_float(w1 << 16), t1 = __uint_as_float(w1 & 0xffff0000u);
  acc2(s0, t0, badd2(v1.x, v1.y)); acc2(s1, t1, badd2(v1.z, v1.w));
  acc2(s0, t0, badd2(v2.x, v2.y)); acc2(s1, t1, badd2(v2.z, v2.w));
  acc2(s0, t0, badd2(v3.x, v3.y)); acc2(s1, t1, badd2(v3.z, v3.w));
  acc = (s0 + t0) + (s1 + t1);
}
__device__ __forceinline__ float bf_lo(uint32_t w) { return __uint_as_float(w << 16); }
__device__ __forceinline__ float bf_hi(uint32_t w) { return __uint_as_float(w & 0xffff0000u); }
__device__ __forceinline__ float bf_rn(float x) { return __bfloat162float(__float2bfloat16(x)); }
__device__ __forceinline__ void slow_item(const Params& p, int item, int hw) {
  const int blk = item >> 9, h = (item >> 4) & 31, b = item & 15;
#pragma unroll 1
  for (int n = hw; n < SQ; n += 3) {
    float q[6] = {0.f, 0.f, 0.f, 0.f, 0.f, 0.f};
    {
      const uint32_t* xr = (const uint32_t*)(p.xp[blk] + (size_t)(b * SQ + n) * DM);
      const uint32_t* wq = (const uint32_t*)(p.wqp[blk] + h * DH) + (tid_x() & 31);
#pragma unroll 2
      for (int k = 0; k < DM / 2; k++) {
        const uint32_t xv = xr[k];
#pragma unroll
        for (int i = 0; i < 3; i++) {
          const uint32_t w0 = wq[i * 32], w1 = wq[NH * DH / 2 + i * 32];
          q[2 * i] = fmaf(bf_lo(xv), bf_lo(w0), fmaf(bf_hi(xv), bf_lo(w1), q[2 * i]));
          q[2 * i + 1] = fmaf(bf_lo(xv), bf_hi(w0), fmaf(bf_hi(xv), bf_hi(w1), q[2 * i + 1]));
        }
        wq += NH * DH;
      }
    }
    const uint32_t q0 = pack2(q[0], q[1]), q1 = pack2(q[2], q[3]), q2 = pack2(q[4], q[5]);
    float o[6] = {0.f, 0.f, 0.f, 0.f, 0.f, 0.f}, m = -INFINITY, l = 0.f;
    const uint32_t* kg = (const uint32_t*)(p.kp[blk] + (size_t)(b * NH + h) * SK * DH) + (tid_x() & 31);
    const uint32_t* vg = (const uint32_t*)(p.vp[blk] + (size_t)(b * NH + h) * SK * DH) + (tid_x() & 31);
#pragma unroll 1
    for (int k = 0; k < SK; k++) {
      const uint32_t k0 = kg[0], k1 = kg[32], k2 = kg[64], v0 = vg[0], v1 = vg[32], v2 = vg[64];
      kg += DH / 2; vg += DH / 2;
      float sc = fmaf(bf_lo(q0), bf_lo(k0), bf_hi(q0) * bf_hi(k0));
      sc = fmaf(bf_lo(q1), bf_lo(k1), fmaf(bf_hi(q1), bf_hi(k1), sc));
      sc = fmaf(bf_lo(q2), bf_lo(k2), fmaf(bf_hi(q2), bf_hi(k2), sc));
#pragma unroll
      for (int d = 16; d; d >>= 1) sc += __shfl_xor_sync(0xffffffffu, sc, d);
      sc = bf_rn(bf_rn(sc) * 0.07216878364870322f);
      const float mn = fmaxf(m, sc), a = ex2((m - mn) * 1.4426950408889634f), pr = ex2((sc - mn) * 1.4426950408889634f);
      m = mn;
      l = fmaf(l, a, pr);
      o[0] = fmaf(o[0], a, pr * bf_lo(v0)); o[1] = fmaf(o[1], a, pr * bf_hi(v0));
      o[2] = fmaf(o[2], a, pr * bf_lo(v1)); o[3] = fmaf(o[3], a, pr * bf_hi(v1));
      o[4] = fmaf(o[4], a, pr * bf_lo(v2)); o[5] = fmaf(o[5], a, pr * bf_hi(v2));
    }
    float inv;
    asm("rcp.approx.ftz.f32 %0, %1;" : "=f"(inv) : "f"(l));
    const int lane = tid_x() & 31;
    const int r = n & 15, c = 4 * ((r & 7) >> 1) + 2 * (r >> 3) + (r & 1);
    char* on = o_slot(item) + (lane >> 2) * 256 + (lane & 3) * 64 + (n >> 4) * 2048 +
               (((c >> 3) ^ ((lane >> 1) & 1)) << 4) + (c & 7) * 2;
#pragma unroll
    for (int i = 0; i < 3; i++) {
      *(__nv_bfloat16*)(on + i * B_SLOT) = __float2bfloat16(o[2 * i] * inv);
      *(__nv_bfloat16*)(on + i * B_SLOT + 32) = __float2bfloat16(o[2 * i + 1] * inv);
    }
  }
}
__device__ __forceinline__ void attn_helper(const Params& p, int hw, int item, int epoch) {
  int bud = WAIT_BUDGET;
  if (item < PF_N && hw < 2) {
    const char* g = (const char*)(hw ? p.vp[0] : p.kp[0]) + (size_t)(((item & 15) * NH + (item >> 4)) * SK) * DH * 2;
    const long long t0 = clock64();
#pragma unroll 1
    for (int i = 0; i < 32; i++) {
      while (clock64() - t0 < PF_WAIT + i * PF_GAP) __nanosleep(50);
      for (int k = 0; k < 6; k++) asm volatile("prefetch.global.L2 [%0];" ::"l"(g + i * 6144 + k * 1024 + (tid_x() & 31) * 32));
      __syncwarp();
    }
  }
#pragma unroll 1
  for (int it = 0; item < NITEMS; it++) {
    const uint32_t par = it & 1;
    int lane = tid_x() & 31;
    const int r = lane >> 1;
    const uint32_t a0 = B_ADDR(3) + (16 * hw + r) * 128 + (lane & 1) * 16 + ((r & 3) << 5);
    float acc[4] = {0.f, 0.f, 0.f, 0.f};
#pragma unroll 1
    for (int j = 0; j < 8; j++) {
      const uint32_t pb = a0 + (j & 1) * B_SLOT, bfull = BAR_PFULL + (j & 1) * 8, pfull = (j >> 1) & 1;
      mbar_wait(bud, j == 7 ? BAR_PMID : bfull, j == 7 ? par : pfull);
      sum_unit(acc[0], pb);
      if (j == 7) mbar_wait(bud, BAR_PMID + 8, par);
      sum_unit(acc[1], pb + 6144);
      if (j == 7) mbar_wait(bud, bfull, pfull);
      sum_unit(acc[2], pb + 2 * 6144);
      if (hw == 0) sum_unit(acc[3], pb + 3 * 6144);
      __syncwarp();
      mbar_arrive_if0(BAR_PFREE + (j & 1) * 8, lane);
      if (j == 5 && hw == 2) {
        if (lane == 0) TLP(60);
        if (item >= ORING && item < OFRESH) flag_wait(bud, &g_done[item - ORING], (epoch + 1) * 2);
        if (lane == 0) TLP(61);
      }
    }
    bool bad = false;
    const uint32_t la = SB + OFF_L + (((r & 7) >> 1) * 40 + 2 * (r >> 3) + (r & 1) + 4 * hw) * 4;
#pragma unroll
    for (int u = 0; u < 4; u++) {
      const float l = acc[u] + __shfl_xor_sync(0xffffffffu, acc[u], 1);
      if (u < 3 || hw == 0) {
        bad |= !(l >= 8.8817841970012523e-16f && l <= 1.125899906842624e15f);
        float inv;
        asm("rcp.approx.ftz.f32 %0, %1;" : "=f"(inv) : "f"(l));
        asm volatile("st.shared.f32 [%0], %1;" ::"r"(la + u * 48), "f"(inv) : "memory");
      }
    }
    publish_generic(BAR_LFULL, lane);
    if (lane == 0) TLP(40 + hw * 4);
    uint32_t anybad;
    asm volatile("{\n.reg .pred p, q;\nsetp.ne.u32 p, %1, 0;\nbarrier.red.or.pred q, 7, 96, p;\nselp.u32 %0, 1, 0, q;\n}\n"
                 : "=r"(anybad) : "r"((uint32_t)bad) : "memory");
    if (__any_sync(0xffffffffu, anybad)) {
      mbar_wait(bud, BAR_OFULL, par);
      slow_item(p, item, hw);
      bar_sync(7, 96);
    }
    if (hw == 1) {
      mbar_wait(bud, BAR_OFULL, par);
      if ((tid_x() & 31) == 0) {
        TLP(41 + hw * 4);
        asm volatile("red.release.gpu.global.add.s32 [%0], 1;" ::"l"(&g_ready[item]) : "memory");
        TLP(42 + hw * 4);
      }
      __syncwarp();
    }
    item = next_item();
  }
}

__device__ __forceinline__ void attn_producer(const Params& p, int item) {
  int bud = WAIT_BUDGET;
  uint32_t sa = 0, pa = 1;
  uint64_t pol;
  asm volatile("createpolicy.fractional.L2::evict_first.b64 %0, 1.0;" : "=l"(pol));
  const bool draws = item >= N_OCTA;
  {
    const int delay = start_delay(item);
    const long long t0 = clock64();
    while (clock64() - t0 < delay) __nanosleep(100);
  }
#pragma unroll 1
  for (int it = 0; item < NITEMS; it++) {
    const int blk = item >> 9, h = (item >> 4) & 31, b = item & 15;
    const int row0 = (b * NH + h) * SK;
#pragma unroll
    for (int c = 0; c < 10; c++) {
      mbar_wait(bud, BAR_EMPTYA + sa * 8, pa);
      TLP(c);
      mbar_expect(BAR_FULLA + sa * 8, A_SLOT + B_SLOT);
      tma3d(A_ADDR(sa), &p.wq[blk], BAR_FULLA + sa * 8, 0, c * 64, h * 3);
      mbar_wait(bud, BAR_EMPTYB + xs(c) * 8, c < NSLOT);
      TLP(10 + c);
      tma2d(B_ADDR(xs(c)), &p.x[blk], BAR_FULLA + sa * 8, c * 64, b * SQ);
      if (++sa == NSLOT) { sa = 0; pa ^= 1; }
    }
#pragma unroll
    for (int i = 0; i < 16; i++) {
      const bool isK = (i == 0) || ((i & 1) && i < 15);
      const int j = i == 0 ? 0 : (i == 15 ? 7 : (isK ? (i + 1) >> 1 : (i - 2) >> 1));
      mbar_wait(bud, BAR_EMPTYA + sa * 8, pa);
      TLP(20 + i);
      if (i == 11) item = draws ? NCTA + (int)atomicInc(&g_ticket, NITEMS - NCTA + N_ATT - 1) : NITEMS;
      if (i == 13) asm volatile("st.shared.s32 [%0], %1;" ::"r"(NEXT_ITEM), "r"(item) : "memory");
      mbar_expect(BAR_FULLA + sa * 8, A_SLOT);
      tma3d_hint(A_ADDR(sa), isK ? &p.k[blk] : &p.v[blk], BAR_FULLA + sa * 8, 0, row0 + j * 64, 0, pol);
      if (++sa == NSLOT) { sa = 0; pa ^= 1; }
    }
  }
}

struct OJob { int tile, part, s0, s1; };
__device__ __forceinline__ OJob get_ojob(int cta, int last) {
  if (cta < N_OCTA) return OJob{cta, 0, 0, STEP1};
  const int u = last - NITEMS, part = 1 + (u >> 5);
  return OJob{u & 31, part, part == 1 ? STEP1 : part == 2 ? STEP2 : STEP3, part == 1 ? STEP2 : part == 2 ? STEP3 : part == 3 ? 2 * NH : 0};
}

template <int W>
__device__ __forceinline__ void oproj_consumer(const Params& p, const OJob job) {
  int bud = WAIT_BUDGET;
  const int tid = threadIdx.x & 127, lane = tid & 31, warp = tid >> 5;
  const int qrow = 8 * ((lane >> 1) & 1) + 4 * (lane >> 4) + 2 * ((lane >> 2) & 1) + (lane & 1);
  const uint32_t st_off = qrow * 128 + (((2 * warp + ((lane >> 3) & 1)) ^ (qrow & 7)) << 4);
  float a0[80], a1[80], ah[40];
  zero_regs(a0); zero_regs(a1); zero_regs(ah);
  int step = job.s0;
#pragma unroll 1
  while (step < job.s1) {
    const int nc = 3 * ((step < NH ? NH : job.s1) - step);
    uint32_t st = 0;
#pragma unroll 1
    for (int c = 0; c < nc; c++) {
      mbar_wait(bud, BAR_GFULL + st * 8, (step - job.s0) & 1);
      wg_fence();
      const uint32_t la = lo_sw(SB + st * O_STAGE), lb = lo_o(SB + st * O_STAGE + O_AB);
#define O_STEP(ks, sc)                                                        \
  mma80r<1, 1, 2 * 8192 + ks * 2048, W * 10240 + ks * 512>(ah, la, lb, sc);   \
  mma160r<1, 1, (W * 3) * 8192 + ks * 2048, ks * 512>(a0, la, lb, sc);        \
  mma160r<1, 1, (W * 3 + 1) * 8192 + ks * 2048, ks * 512>(a1, la, lb, sc);
      O_STEP(0, c != 0) O_STEP(1, 1)
      wg_commit();
      wg_wait<1>();
      mbar_arrive_if0(BAR_GEMPTY + (st == 0 ? 2 : st - 1) * 8, tid | (c == 0) | (c == nc - 1));
      wg_fence();
      O_STEP(2, 1) O_STEP(3, 1)
#undef O_STEP
      wg_commit();
      if (++st == 3) {
        st = 0;
        if (W == 0)
          asm volatile("{\n.reg .pred p;\nsetp.eq.u32 p, %1, 0;\n@p red.relaxed.gpu.global.add.s32 [%0], 1;\n}\n"
                       ::"l"(&g_done[step * 16 + (job.tile >> 1)]), "r"(tid) : "memory");
        TLG(step);
        step++;
      }
    }
    wg_wait<0>();
    reg_fence(a0); reg_fence(a1); reg_fence(ah);
    bar_sync(3, 256);
    const uint32_t sg = SB + O_STAGE + st_off;
    store_scaled(sg + 2 * B_SLOT + W * 10240, ah, 1.0f);
    store_scaled(sg + (W * 3) * B_SLOT, a0, 1.0f);
    store_scaled(sg + (W * 3 + 1) * B_SLOT, a1, 1.0f);
    publish(BAR_GOUT, lane);
  }
  TL_FLUSH();
  TLG(0);
  mbar_wait(bud, BAR_GRED, 0);
  TLG(1);
  const int row0 = (job.tile >> 1) * SQ + job.part * 40, col0 = (job.tile & 1) * 40;
#pragma unroll
  for (int i = 0; i < 7; i++) {
    const int e = i * 256 + W * 128 + tid;
    if (e < 1600) {
      const int r = row0 + e / 40, cc = col0 + e % 40;
      float acc[8] = {0.f, 0.f, 0.f, 0.f, 0.f, 0.f, 0.f, 0.f};
#pragma unroll
      for (int q = 0; q < 4; q++) {
        const uint4 v = __ldcg(&g_part[(q * NB * SQ + r) * (DM / 8) + cc]);
        acc[0] += bf_lo(v.x); acc[1] += bf_hi(v.x); acc[2] += bf_lo(v.y); acc[3] += bf_hi(v.y);
        acc[4] += bf_lo(v.z); acc[5] += bf_hi(v.z); acc[6] += bf_lo(v.w); acc[7] += bf_hi(v.w);
      }
      ((uint4*)p.outp)[r * (2 * DM / 8) + DM / 8 + cc] =
          make_uint4(pack2(acc[0], acc[1]), pack2(acc[2], acc[3]), pack2(acc[4], acc[5]), pack2(acc[6], acc[7]));
    }
  }
  TLG(2);
  TL_FLUSH();
}

__device__ __forceinline__ void oproj_producer(const Params& p, const OJob job, int target) {
  int bud = WAIT_BUDGET;
#pragma unroll 1
  for (int step = job.s0; step < job.s1; step++) {
    const int item = step * 16 + (job.tile >> 1);
    const char* og = o_slot(item);
    flag_wait(bud, &g_ready[item], target);
    asm volatile("fence.proxy.async.global;" ::: "memory");
#pragma unroll
    for (int kb = 0; kb < 3; kb++) {
      const uint32_t dst = SB + kb * O_STAGE, bar = BAR_GFULL + kb * 8;
      mbar_wait(bud, BAR_GEMPTY + kb * 8, ((step - job.s0) & 1) ^ 1);
      mbar_expect(bar, O_STAGE);
      tma3d(dst, &p.wo[step >> 5], bar, 0, ((step & 31) * 3 + kb) * 64, (job.tile & 1) * 5);
      bulk_load(dst + O_AB, og + kb * B_SLOT, B_SLOT, bar);
    }
  }
}

__device__ __forceinline__ void oproj_storer(const Params& p, const OJob job, int target) {
  int bud = WAIT_BUDGET;
  const int col = (job.tile & 1) * 320, row = (job.tile >> 1) * SQ;
  if (job.part == 0) {
    mbar_wait(bud, BAR_GOUT, 0);
    for (int k = 0; k < 5; k++) tma_store2d(&p.out, SB + O_STAGE + k * B_SLOT, col + k * 64, row);
    asm volatile("cp.async.bulk.commit_group;" ::: "memory");
    asm volatile("cp.async.bulk.wait_group.read 0;" ::: "memory");
    mbar_arrive2_if0(BAR_GEMPTY + 8, 0);
    mbar_arrive2_if0(BAR_GEMPTY + 16, 0);
  }
  mbar_wait(bud, BAR_GOUT, job.part == 0);
  for (int k = 0; k < 5; k++) tma_store2d(&p.part, SB + O_STAGE + k * B_SLOT, col + k * 64, job.part * NB * SQ + row);
  asm volatile("cp.async.bulk.commit_group;" ::: "memory");
  asm volatile("cp.async.bulk.wait_group 0;" ::: "memory");
  asm volatile("fence.proxy.async.global;" ::: "memory");
  asm volatile("red.release.gpu.global.add.s32 [%0], 1;" ::"l"(&g_pcnt[job.tile]) : "memory");
  flag_wait(bud, &g_pcnt[job.tile], 4 * target);
  mbar_arrive_if0(BAR_GRED, 0);
}

__global__ void __launch_bounds__(384, 1) fused_kernel(const __grid_constant__ Params p) {
  extern __shared__ __align__(1024) char smem_raw[];
  if ((smem_u32(smem_raw) & 0xFFFFFFu) != SB) return;
  const int cta = (((blockIdx.x >> 1) * PERM_M) % (NCTA / 2)) * 2 + (blockIdx.x & 1);
  const int warp = __shfl_sync(0xffffffffu, threadIdx.x >> 5, 0);
  if (threadIdx.x == 0) {
    for (int i = 0; i < NSLOT; i++) { mbar_init(BAR_FULLA + i * 8, 1); mbar_init(BAR_EMPTYA + i * 8, 2); mbar_init(BAR_EMPTYB + i * 8, 2); }
    proxy_fence();
  }
  if (threadIdx.x == 64) {
    mbar_init(BAR_XDONE, 1); mbar_init(BAR_QH, 4); mbar_init(BAR_QM, 4);
    mbar_init(BAR_PFULL, 4); mbar_init(BAR_PFULL + 8, 4); mbar_init(BAR_PFREE, 3); mbar_init(BAR_PFREE + 8, 3);
    mbar_init(BAR_LFULL, 3); mbar_init(BAR_PMID, 4); mbar_init(BAR_PMID + 8, 4); mbar_init(BAR_OFULL, 8);
  }
  if (threadIdx.x == 96) {
    for (int i = 0; i < O_NST; i++) { mbar_init(BAR_GFULL + i * 8, 1); mbar_init(BAR_GEMPTY + i * 8, 2); }
    mbar_init(BAR_GOUT, 8); mbar_init(BAR_GRED, 1);
    proxy_fence();
  }
  if (warp == 1 && threadIdx.x < 32 + 12) asm volatile("prefetch.tensormap [%0];" ::"l"(&p.x[0] + (threadIdx.x - 32)) : "memory");
  __syncthreads();
  if (warp >= 8) {
    asm volatile("setmaxnreg.dec.sync.aligned.u32 40;");
    if (warp == 8) {
      if (elect_one()) attn_producer(p, cta);
      __syncwarp();
    } else {
      const int epoch = *(volatile int*)&g_epoch[cta];
      attn_helper(p, warp - 9, cta, epoch);
      if (warp == 11 && elect_one()) *(volatile int*)&g_epoch[cta] = epoch + 1;
    }
    bar_sync(4, 128);
    const OJob job = get_ojob(cta, next_item());
    if (job.s0 < job.s1) {
      if (warp == 8) {
        if (elect_one()) oproj_producer(p, job, *(volatile int*)&g_epoch[cta]);
      } else if (warp == 9) {
        if (elect_one()) oproj_storer(p, job, *(volatile int*)&g_epoch[cta]);
      }
    }
  } else {
    asm volatile("setmaxnreg.inc.sync.aligned.u32 232;");
    if (warp < 4) {
      const OJob job = get_ojob(cta, attn_consumer<0>(cta));
      if (job.s0 < job.s1) oproj_consumer<0>(p, job);
    } else {
      const OJob job = get_ojob(cta, attn_consumer<1>(cta));
      if (job.s0 < job.s1) oproj_consumer<1>(p, job);
    }
  }
}

typedef CUresult (*EncodeFn)(CUtensorMap*, CUtensorMapDataType, cuuint32_t, void*, const cuuint64_t*, const cuuint64_t*, const cuuint32_t*,
                             const cuuint32_t*, CUtensorMapInterleave, CUtensorMapSwizzle, CUtensorMapL2promotion, CUtensorMapFloatOOBfill);

void make3d(EncodeFn enc, CUtensorMap* m, const void* ptr, uint64_t rows, uint64_t cols, uint32_t box_rows, uint32_t box_blocks,
            CUtensorMapL2promotion promo = CU_TENSOR_MAP_L2_PROMOTION_L2_128B) {
  cuuint64_t gd[3] = {64, rows, cols / 64};
  cuuint64_t gs[2] = {cols * 2, 128};
  cuuint32_t bd[3] = {64, box_rows, box_blocks}, es[3] = {1, 1, 1};
  enc(m, CU_TENSOR_MAP_DATA_TYPE_BFLOAT16, 3, (void*)ptr, gd, gs, bd, es, CU_TENSOR_MAP_INTERLEAVE_NONE, CU_TENSOR_MAP_SWIZZLE_128B,
      promo, CU_TENSOR_MAP_FLOAT_OOB_FILL_NONE);
}
void make2d(EncodeFn enc, CUtensorMap* m, const void* ptr, uint64_t rows, uint64_t cols, uint32_t box_rows) {
  cuuint64_t gd[2] = {cols, rows};
  cuuint64_t gs[1] = {cols * 2};
  cuuint32_t bd[2] = {64, box_rows}, es[2] = {1, 1};
  enc(m, CU_TENSOR_MAP_DATA_TYPE_BFLOAT16, 2, (void*)ptr, gd, gs, bd, es, CU_TENSOR_MAP_INTERLEAVE_NONE, CU_TENSOR_MAP_SWIZZLE_128B,
      CU_TENSOR_MAP_L2_PROMOTION_L2_128B, CU_TENSOR_MAP_FLOAT_OOB_FILL_NONE);
}

}

extern "C" void kernel_launch(void* const* d_in, const int* in_sizes, int n_in, void* d_out, int out_size) {
  static EncodeFn enc = nullptr;
  static void* part = nullptr;
  if (!enc) {
    cudaGetSymbolAddress(&part, g_part);
    cudaDriverEntryPointQueryResult qr;
    cudaGetDriverEntryPoint("cuTensorMapEncodeTiled", (void**)&enc, cudaEnableDefault, &qr);
    cudaFuncSetAttribute(fused_kernel, cudaFuncAttributeMaxDynamicSharedMemorySize, SMEM_BYTES);
  }
  Params p;
  for (int s = 0; s < 2; s++) {
    make2d(enc, &p.x[s], d_in[5 * s + 0], NB * SQ, DM, SQ);
    make3d(enc, &p.k[s], d_in[5 * s + 1], (uint64_t)NB * NH * SK, DH, 64, 3);
    make3d(enc, &p.v[s], d_in[5 * s + 2], (uint64_t)NB * NH * SK, DH, 64, 3);
    make3d(enc, &p.wq[s], d_in[5 * s + 3], DM, NH * DH, 64, 3);
    make3d(enc, &p.wo[s], d_in[5 * s + 4], NH * DH, DM, 64, 5);
    p.xp[s] = (const __nv_bfloat16*)d_in[5 * s + 0];
    p.wqp[s] = (const __nv_bfloat16*)d_in[5 * s + 3];
    p.kp[s] = (const __nv_bfloat16*)d_in[5 * s + 1];
    p.vp[s] = (const __nv_bfloat16*)d_in[5 * s + 2];
  }
  make2d(enc, &p.out, d_out, NB * SQ, 2 * DM, SQ);
  make2d(enc, &p.part, part, 4 * NB * SQ, DM, SQ);
  p.outp = (__nv_bfloat16*)d_out;
  fused_kernel<<<NCTA, 384, SMEM_BYTES>>>(p);
}
```

```cpp
#include <cuda_runtime.h>
#include <cuda_bf16.h>
#include <cuda.h>
#include <stdint.h>

#define DEBUG_TIMEOUT 0

namespace {

constexpr int SQ = 160, DM = 640, NH = 32, SK = 512, DH = 192, NB = 16;
constexpr int NITEMS = 2 * NB * NH;
constexpr int NCTA = 132, N_OCTA = 32, N_ATT = NCTA - N_OCTA;
constexpr int ORING = 192, OFRESH = 800, STEP1 = 53, STEP2 = 58, STEP3 = 62;
constexpr int WO_PF = 2, STAG_A0 = 15, STAG_SLOPE = 262, PERM_M = 41, PF_N = 32, PF_WAIT = 1500, PF_GAP = 300;
constexpr int OSLOTS = ORING + NITEMS - OFRESH;
#define W1_NG 3
constexpr int A_SLOT = 24576, B_SLOT = 20480, NSLOT = 5;
constexpr int OFF_A = 0;
constexpr int OFF_B = NSLOT * A_SLOT;
constexpr int O_STAGE = 61440, O_AB = 40960, O_NST = 3;
constexpr int OFF_L = OFF_B + NSLOT * B_SLOT;
constexpr int OFF_BAR = OFF_L + 160 * 4;
constexpr int SMEM_BYTES = OFF_BAR + 384 + 512;
constexpr int O_OUT = 2 * O_STAGE;
static_assert(O_OUT + 5 * B_SLOT <= OFF_L, "smem layout");
constexpr uint32_t SB = 1024;
constexpr uint32_t BARS = SB + OFF_BAR;
constexpr uint32_t BAR_FULLA = BARS, BAR_EMPTYA = BARS + 40, BAR_PMID = BARS + 80, BAR_EMPTYB = BARS + 120, BAR_XDONE = BARS + 160,
                   BAR_QH = BARS + 168, BAR_QM = BARS + 96, BAR_PFULL = BARS + 184, BAR_PFREE = BARS + 200, BAR_LFULL = BARS + 216,
                   BAR_OFULL = BARS + 224, BAR_GFULL = BARS + 248, BAR_GEMPTY = BARS + 280, BAR_GOUT = BARS + 328, BAR_GRED = BARS + 232,
                   BAR_FREE = BARS + 240, NEXT_ITEM = BARS + 320;
constexpr int O_ITEM_BYTES = SQ * DH * 2;

struct alignas(64) Params {
  CUtensorMap x[2], wq[2], k[2], v[2], wo[2], out, part;
  __nv_bfloat16* outp;
  const __nv_bfloat16 *xp[2], *wqp[2], *kp[2], *vp[2], *wop[2];
};

__device__ uint4 g_o[(size_t)OSLOTS * O_ITEM_BYTES / 16];
__device__ uint4 g_part[4 * NB * SQ * DM / 8];
__device__ int g_pcnt[N_OCTA];
__device__ int g_ready[NITEMS];
__device__ int g_done[NITEMS];
__device__ unsigned g_ticket;
__device__ int g_epoch[NCTA];

#define TLP(id)
#define TLG(id)
#define TL(id)
#define TL_FLUSH()
__device__ __forceinline__ uint32_t smem_u32(const void* p) { return (uint32_t)__cvta_generic_to_shared(p); }
__device__ __forceinline__ void wg_fence() { asm volatile("wgmma.fence.sync.aligned;" ::: "memory"); }
__device__ __forceinline__ void wg_commit() { asm volatile("wgmma.commit_group.sync.aligned;" ::: "memory"); }
template <int N> __device__ __forceinline__ void wg_wait() { asm volatile("wgmma.wait_group.sync.aligned %0;" ::"n"(N) : "memory"); }
template <int N> __device__ __forceinline__ void reg_fence(float (&d)[N]) {
#pragma unroll
  for (int i = 0; i < N; i++) asm volatile("" : "+f"(d[i])::"memory");
}
template <int N> __device__ __forceinline__ void zero_regs(float (&d)[N]) {
#pragma unroll
  for (int i = 0; i < N; i++) d[i] = 0.f;
}
__device__ __forceinline__ void proxy_fence() { asm volatile("fence.proxy.async.shared::cta;" ::: "memory"); }
__device__ __forceinline__ void mbar_init(uint32_t bar, int cnt) { asm volatile("mbarrier.init.shared::cta.b64 [%0], %1;" ::"r"(bar), "r"(cnt) : "memory"); }
__device__ __forceinline__ void mbar_arrive_if0(uint32_t bar, uint32_t sel) {
  asm volatile("{\n.reg .pred p;\nsetp.eq.u32 p, %1, 0;\n@p mbarrier.arrive.shared::cta.b64 _, [%0];\n}\n" ::"r"(bar), "r"(sel) : "memory");
}
__device__ __forceinline__ void mbar_arrive2_if0(uint32_t bar, uint32_t sel) {
  asm volatile("{\n.reg .pred p;\nsetp.eq.u32 p, %1, 0;\n@p mbarrier.arrive.shared::cta.b64 _, [%0], 2;\n}\n" ::"r"(bar), "r"(sel) : "memory");
}
__device__ __forceinline__ void mbar_expect(uint32_t bar, uint32_t bytes) {
  asm volatile("mbarrier.arrive.expect_tx.shared::cta.b64 _, [%0], %1;" ::"r"(bar), "r"(bytes) : "memory");
}
__device__ __forceinline__ void mbar_wait(int& bud, uint32_t bar, uint32_t parity) {
  asm volatile(
      "{\n.reg .pred p;\n"
      "LW:\n"
      "mbarrier.try_wait.parity.shared::cta.b64 p, [%0], %1;\n"
      "@!p bra LW;\n}\n" ::"r"(bar), "r"(parity) : "memory");
}
constexpr int WAIT_BUDGET = 1 << 22;
__device__ __forceinline__ bool elect_one() {
  uint32_t p;
  asm volatile("{\n.reg .pred p;\nelect.sync _|p, 0xffffffff;\nselp.u32 %0, 1, 0, p;\n}\n" : "=r"(p));
  return p;
}
__device__ __forceinline__ void tma2d(uint32_t dst, const CUtensorMap* m, uint32_t bar, int c0, int c1) {
  asm volatile("cp.async.bulk.tensor.2d.shared::cluster.global.mbarrier::complete_tx::bytes [%0], [%1, {%3, %4}], [%2];"
               ::"r"(dst), "l"(m), "r"(bar), "r"(c0), "r"(c1) : "memory");
}
__device__ __forceinline__ void tma3d(uint32_t dst, const CUtensorMap* m, uint32_t bar, int c0, int c1, int c2) {
  asm volatile("cp.async.bulk.tensor.3d.shared::cluster.global.mbarrier::complete_tx::bytes [%0], [%1, {%3, %4, %5}], [%2];"
               ::"r"(dst), "l"(m), "r"(bar), "r"(c0), "r"(c1), "r"(c2) : "memory");
}
__device__ __forceinline__ void tma3d_hint(uint32_t dst, const CUtensorMap* m, uint32_t bar, int c0, int c1, int c2, uint64_t pol) {
  asm volatile("cp.async.bulk.tensor.3d.shared::cluster.global.mbarrier::complete_tx::bytes.L2::cache_hint [%0], [%1, {%3, %4, %5}], [%2], %6;"
               ::"r"(dst), "l"(m), "r"(bar), "r"(c0), "r"(c1), "r"(c2), "l"(pol) : "memory");
}
__device__ __forceinline__ void bulk_load(uint32_t dst, const void* src, uint32_t bytes, uint32_t bar) {
  asm volatile("cp.async.bulk.shared::cluster.global.mbarrier::complete_tx::bytes [%0], [%1], %2, [%3];"
               ::"r"(dst), "l"(src), "r"(bytes), "r"(bar) : "memory");
}
__device__ __forceinline__ void tma_store2d(const CUtensorMap* m, uint32_t src, int c0, int c1) {
  asm volatile("cp.async.bulk.tensor.2d.global.shared::cta.bulk_group [%0, {%2, %3}], [%1];" ::"l"(m), "r"(src), "r"(c0), "r"(c1) : "memory");
}
__device__ __forceinline__ void bar_sync(int id, int n) { asm volatile("bar.sync %0, %1;" ::"r"(id), "r"(n) : "memory"); }
__device__ __forceinline__ void bar_arrive(int id, int n) { asm volatile("bar.arrive %0, %1;" ::"r"(id), "r"(n) : "memory"); }
__device__ __forceinline__ float ex2(float x) { float y; asm("ex2.approx.ftz.f32 %0, %1;" : "=f"(y) : "f"(x)); return y; }
__device__ __forceinline__ uint32_t pack2(float lo, float hi) { uint32_t r; asm("cvt.rn.bf16x2.f32 %0, %1, %2;" : "=r"(r) : "f"(hi), "f"(lo)); return r; }
__device__ __forceinline__ void stsm_t(uint32_t a, uint32_t r0, uint32_t r1, uint32_t r2, uint32_t r3) {
  asm volatile("stmatrix.sync.aligned.m8n8.x4.trans.shared.b16 [%0], {%1,%2,%3,%4};" ::"r"(a), "r"(r0), "r"(r1), "r"(r2), "r"(r3) : "memory");
}
__device__ __forceinline__ void flag_wait(int& bud, const int* p, int target) {
  while (true) {
    int v;
    asm volatile("ld.acquire.gpu.global.s32 %0, [%1];" : "=r"(v) : "l"(p) : "memory");
    if (v - target >= 0 || --bud <= 0) break;
    __nanosleep(64);
  }
}
__device__ __forceinline__ uint32_t lo_sw(uint32_t addr) { return (addr >> 4) | (1u << 16); }
__device__ __forceinline__ uint32_t lo_o(uint32_t addr) { return (addr >> 4) | (128u << 16); }
__device__ __forceinline__ uint32_t tid_x() { uint32_t t; asm volatile("mov.u32 %0, %tid.x;" : "=r"(t)); return t; }
__device__ __forceinline__ uint32_t opaque(uint32_t x) { uint32_t y; asm volatile("mov.u32 %0, %1;" : "=r"(y) : "r"(x)); return y; }

template <int TA, int TB, uint32_t OA, uint32_t OB>
__device__ __forceinline__ void mma160(float (&d)[80], uint32_t la, uint32_t lb) {
  asm volatile(
      "{\n.reg .pred p;\n.reg .b32 a, b;\n.reg .b64 da, db;\nsetp.eq.b32 p, 0, 0;\n"
      "add.u32 a, %80, %84;\nadd.u32 b, %81, %85;\nmov.b64 da, {a, 0x40000040};\nmov.b64 db, {b, %86};\n"
      "wgmma.mma_async.sync.aligned.m64n160k16.f32.bf16.bf16 {"
      "%0,%1,%2,%3,%4,%5,%6,%7,%8,%9,%10,%11,%12,%13,%14,%15,%16,%17,%18,%19,%20,%21,%22,%23,%24,%25,%26,%27,%28,%29,%30,%31,%32,%33,%34,%35,%36,"
      "%37,%38,%39,%40,%41,%42,%43,%44,%45,%46,%47,%48,%49,%50,%51,%52,%53,%54,%55,%56,%57,%58,%59,%60,%61,%62,%63,%64,%65,%66,%67,%68,%69,%70,%71,"
      "%72,%73,%74,%75,%76,%77,%78,%79"
      "}, da, db, p, 1, 1, %82, %83;\n}\n"
      :
      "+f"(d[0]),"+f"(d[1]),"+f"(d[2]),"+f"(d[3]),"+f"(d[4]),"+f"(d[5]),"+f"(d[6]),"+f"(d[7]),"+f"(d[8]),"+f"(d[9]),"+f"(d[10]),"+f"(d[11]),
      "+f"(d[12]),"+f"(d[13]),"+f"(d[14]),"+f"(d[15]),"+f"(d[16]),"+f"(d[17]),"+f"(d[18]),"+f"(d[19]),"+f"(d[20]),"+f"(d[21]),"+f"(d[22]),
      "+f"(d[23]),"+f"(d[24]),"+f"(d[25]),"+f"(d[26]),"+f"(d[27]),"+f"(d[28]),"+f"(d[29]),"+f"(d[30]),"+f"(d[31]),"+f"(d[32]),"+f"(d[33]),
      "+f"(d[34]),"+f"(d[35]),"+f"(d[36]),"+f"(d[37]),"+f"(d[38]),"+f"(d[39]),"+f"(d[40]),"+f"(d[41]),"+f"(d[42]),"+f"(d[43]),"+f"(d[44]),
      "+f"(d[45]),"+f"(d[46]),"+f"(d[47]),"+f"(d[48]),"+f"(d[49]),"+f"(d[50]),"+f"(d[51]),"+f"(d[52]),"+f"(d[53]),"+f"(d[54]),"+f"(d[55]),
      "+f"(d[56]),"+f"(d[57]),"+f"(d[58]),"+f"(d[59]),"+f"(d[60]),"+f"(d[61]),"+f"(d[62]),"+f"(d[63]),"+f"(d[64]),"+f"(d[65]),"+f"(d[66]),
      "+f"(d[67]),"+f"(d[68]),"+f"(d[69]),"+f"(d[70]),"+f"(d[71]),"+f"(d[72]),"+f"(d[73]),"+f"(d[74]),"+f"(d[75]),"+f"(d[76]),"+f"(d[77]),
      "+f"(d[78]),"+f"(d[79])
      : "r"(la), "r"(lb), "n"(TA), "n"(TB), "n"(OA >> 4), "n"(OB >> 4), "n"(TB ? 0xC0000010u : 0x40000040u));
}

template <int TA, int TB, uint32_t OA, uint32_t OB>
__device__ __forceinline__ void mma160z(float (&d)[80], uint32_t la, uint32_t lb) {
  asm volatile(
      "{\n.reg .pred p;\n.reg .b32 a, b;\n.reg .b64 da, db;\nsetp.ne.b32 p, 0, 0;\n"
      "add.u32 a, %80, %84;\nadd.u32 b, %81, %85;\nmov.b64 da, {a, 0x40000040};\nmov.b64 db, {b, %86};\n"
      "wgmma.mma_async.sync.aligned.m64n160k16.f32.bf16.bf16 {"
      "%0,%1,%2,%3,%4,%5,%6,%7,%8,%9,%10,%11,%12,%13,%14,%15,%16,%17,%18,%19,%20,%21,%22,%23,%24,%25,%26,%27,%28,%29,%30,%31,%32,%33,%34,%35,%36,"
      "%37,%38,%39,%40,%41,%42,%43,%44,%45,%46,%47,%48,%49,%50,%51,%52,%53,%54,%55,%56,%57,%58,%59,%60,%61,%62,%63,%64,%65,%66,%67,%68,%69,%70,%71,"
      "%72,%73,%74,%75,%76,%77,%78,%79"
      "}, da, db, p, 1, 1, %82, %83;\n}\n"
      :
      "=f"(d[0]),"=f"(d[1]),"=f"(d[2]),"=f"(d[3]),"=f"(d[4]),"=f"(d[5]),"=f"(d[6]),"=f"(d[7]),"=f"(d[8]),"=f"(d[9]),"=f"(d[10]),"=f"(d[11]),
      "=f"(d[12]),"=f"(d[13]),"=f"(d[14]),"=f"(d[15]),"=f"(d[16]),"=f"(d[17]),"=f"(d[18]),"=f"(d[19]),"=f"(d[20]),"=f"(d[21]),"=f"(d[22]),
      "=f"(d[23]),"=f"(d[24]),"=f"(d[25]),"=f"(d[26]),"=f"(d[27]),"=f"(d[28]),"=f"(d[29]),"=f"(d[30]),"=f"(d[31]),"=f"(d[32]),"=f"(d[33]),
      "=f"(d[34]),"=f"(d[35]),"=f"(d[36]),"=f"(d[37]),"=f"(d[38]),"=f"(d[39]),"=f"(d[40]),"=f"(d[41]),"=f"(d[42]),"=f"(d[43]),"=f"(d[44]),
      "=f"(d[45]),"=f"(d[46]),"=f"(d[47]),"=f"(d[48]),"=f"(d[49]),"=f"(d[50]),"=f"(d[51]),"=f"(d[52]),"=f"(d[53]),"=f"(d[54]),"=f"(d[55]),
      "=f"(d[56]),"=f"(d[57]),"=f"(d[58]),"=f"(d[59]),"=f"(d[60]),"=f"(d[61]),"=f"(d[62]),"=f"(d[63]),"=f"(d[64]),"=f"(d[65]),"=f"(d[66]),
      "=f"(d[67]),"=f"(d[68]),"=f"(d[69]),"=f"(d[70]),"=f"(d[71]),"=f"(d[72]),"=f"(d[73]),"=f"(d[74]),"=f"(d[75]),"=f"(d[76]),"=f"(d[77]),
      "=f"(d[78]),"=f"(d[79])
      : "r"(la), "r"(lb), "n"(TA), "n"(TB), "n"(OA >> 4), "n"(OB >> 4), "n"(TB ? 0xC0000010u : 0x40000040u));
}

template <int TA, int TB, uint32_t OA, uint32_t OB>
__device__ __forceinline__ void mma80(float (&d)[40], uint32_t la, uint32_t lb) {
  asm volatile(
      "{\n.reg .pred p;\n.reg .b32 a, b;\n.reg .b64 da, db;\nsetp.eq.b32 p, 0, 0;\n"
      "add.u32 a, %40, %44;\nadd.u32 b, %41, %45;\nmov.b64 da, {a, 0x40000040};\nmov.b64 db, {b, %46};\n"
      "wgmma.mma_async.sync.aligned.m64n80k16.f32.bf16.bf16 {"
      "%0,%1,%2,%3,%4,%5,%6,%7,%8,%9,%10,%11,%12,%13,%14,%15,%16,%17,%18,%19,%20,%21,%22,%23,%24,%25,%26,%27,%28,%29,%30,%31,%32,%33,%34,%35,%36,"
      "%37,%38,%39"
      "}, da, db, p, 1, 1, %42, %43;\n}\n"
      :
      "+f"(d[0]),"+f"(d[1]),"+f"(d[2]),"+f"(d[3]),"+f"(d[4]),"+f"(d[5]),"+f"(d[6]),"+f"(d[7]),"+f"(d[8]),"+f"(d[9]),"+f"(d[10]),"+f"(d[11]),
      "+f"(d[12]),"+f"(d[13]),"+f"(d[14]),"+f"(d[15]),"+f"(d[16]),"+f"(d[17]),"+f"(d[18]),"+f"(d[19]),"+f"(d[20]),"+f"(d[21]),"+f"(d[22]),
      "+f"(d[23]),"+f"(d[24]),"+f"(d[25]),"+f"(d[26]),"+f"(d[27]),"+f"(d[28]),"+f"(d[29]),"+f"(d[30]),"+f"(d[31]),"+f"(d[32]),"+f"(d[33]),
      "+f"(d[34]),"+f"(d[35]),"+f"(d[36]),"+f"(d[37]),"+f"(d[38]),"+f"(d[39])
      : "r"(la), "r"(lb), "n"(TA), "n"(TB), "n"(OA >> 4), "n"(OB >> 4), "n"(TB ? 0xC0000010u : 0x40000040u));
}

template <int TA, int TB, uint32_t OA, uint32_t OB>
__device__ __forceinline__ void mma80z(float (&d)[40], uint32_t la, uint32_t lb) {
  asm volatile(
      "{\n.reg .pred p;\n.reg .b32 a, b;\n.reg .b64 da, db;\nsetp.ne.b32 p, 0, 0;\n"
      "add.u32 a, %40, %44;\nadd.u32 b, %41, %45;\nmov.b64 da, {a, 0x40000040};\nmov.b64 db, {b, %46};\n"
      "wgmma.mma_async.sync.aligned.m64n80k16.f32.bf16.bf16 {"
      "%0,%1,%2,%3,%4,%5,%6,%7,%8,%9,%10,%11,%12,%13,%14,%15,%16,%17,%18,%19,%20,%21,%22,%23,%24,%25,%26,%27,%28,%29,%30,%31,%32,%33,%34,%35,%36,"
      "%37,%38,%39"
      "}, da, db, p, 1, 1, %42, %43;\n}\n"
      :
      "=f"(d[0]),"=f"(d[1]),"=f"(d[2]),"=f"(d[3]),"=f"(d[4]),"=f"(d[5]),"=f"(d[6]),"=f"(d[7]),"=f"(d[8]),"=f"(d[9]),"=f"(d[10]),"=f"(d[11]),
      "=f"(d[12]),"=f"(d[13]),"=f"(d[14]),"=f"(d[15]),"=f"(d[16]),"=f"(d[17]),"=f"(d[18]),"=f"(d[19]),"=f"(d[20]),"=f"(d[21]),"=f"(d[22]),
      "=f"(d[23]),"=f"(d[24]),"=f"(d[25]),"=f"(d[26]),"=f"(d[27]),"=f"(d[28]),"=f"(d[29]),"=f"(d[30]),"=f"(d[31]),"=f"(d[32]),"=f"(d[33]),
      "=f"(d[34]),"=f"(d[35]),"=f"(d[36]),"=f"(d[37]),"=f"(d[38]),"=f"(d[39])
      : "r"(la), "r"(lb), "n"(TA), "n"(TB), "n"(OA >> 4), "n"(OB >> 4), "n"(TB ? 0xC0000010u : 0x40000040u));
}

template <int TA, int TB, uint32_t OA, uint32_t OB>
__device__ __forceinline__ void mma160r(float (&d)[80], uint32_t la, uint32_t lb, int sc) {
  asm volatile(
      "{\n.reg .pred p;\n.reg .b32 a, b;\n.reg .b64 da, db;\nsetp.ne.b32 p, %87, 0;\n"
      "add.u32 a, %80, %84;\nadd.u32 b, %81, %85;\nmov.b64 da, {a, 0x40000040};\nmov.b64 db, {b, %86};\n"
      "wgmma.mma_async.sync.aligned.m64n160k16.f32.bf16.bf16 {"
      "%0,%1,%2,%3,%4,%5,%6,%7,%8,%9,%10,%11,%12,%13,%14,%15,%16,%17,%18,%19,%20,%21,%22,%23,%24,%25,%26,%27,%28,%29,%30,%31,%32,%33,%34,%35,%36,"
      "%37,%38,%39,%40,%41,%42,%43,%44,%45,%46,%47,%48,%49,%50,%51,%52,%53,%54,%55,%56,%57,%58,%59,%60,%61,%62,%63,%64,%65,%66,%67,%68,%69,%70,%71,"
      "%72,%73,%74,%75,%76,%77,%78,%79"
      "}, da, db, p, 1, 1, %82, %83;\n}\n"
      :
      "+f"(d[0]),"+f"(d[1]),"+f"(d[2]),"+f"(d[3]),"+f"(d[4]),"+f"(d[5]),"+f"(d[6]),"+f"(d[7]),"+f"(d[8]),"+f"(d[9]),"+f"(d[10]),"+f"(d[11]),
      "+f"(d[12]),"+f"(d[13]),"+f"(d[14]),"+f"(d[15]),"+f"(d[16]),"+f"(d[17]),"+f"(d[18]),"+f"(d[19]),"+f"(d[20]),"+f"(d[21]),"+f"(d[22]),
      "+f"(d[23]),"+f"(d[24]),"+f"(d[25]),"+f"(d[26]),"+f"(d[27]),"+f"(d[28]),"+f"(d[29]),"+f"(d[30]),"+f"(d[31]),"+f"(d[32]),"+f"(d[33]),
      "+f"(d[34]),"+f"(d[35]),"+f"(d[36]),"+f"(d[37]),"+f"(d[38]),"+f"(d[39]),"+f"(d[40]),"+f"(d[41]),"+f"(d[42]),"+f"(d[43]),"+f"(d[44]),
      "+f"(d[45]),"+f"(d[46]),"+f"(d[47]),"+f"(d[48]),"+f"(d[49]),"+f"(d[50]),"+f"(d[51]),"+f"(d[52]),"+f"(d[53]),"+f"(d[54]),"+f"(d[55]),
      "+f"(d[56]),"+f"(d[57]),"+f"(d[58]),"+f"(d[59]),"+f"(d[60]),"+f"(d[61]),"+f"(d[62]),"+f"(d[63]),"+f"(d[64]),"+f"(d[65]),"+f"(d[66]),
      "+f"(d[67]),"+f"(d[68]),"+f"(d[69]),"+f"(d[70]),"+f"(d[71]),"+f"(d[72]),"+f"(d[73]),"+f"(d[74]),"+f"(d[75]),"+f"(d[76]),"+f"(d[77]),
      "+f"(d[78]),"+f"(d[79])
      : "r"(la), "r"(lb), "n"(TA), "n"(TB), "n"(OA >> 4), "n"(OB >> 4), "n"(TB ? 0xC0000010u : 0x40000040u), "r"(sc));
}

template <int TA, int TB, uint32_t OA, uint32_t OB>
__device__ __forceinline__ void mma80r(float (&d)[40], uint32_t la, uint32_t lb, int sc) {
  asm volatile(
      "{\n.reg .pred p;\n.reg .b32 a, b;\n.reg .b64 da, db;\nsetp.ne.b32 p, %47, 0;\n"
      "add.u32 a, %40, %44;\nadd.u32 b, %41, %45;\nmov.b64 da, {a, 0x40000040};\nmov.b64 db, {b, %46};\n"
      "wgmma.mma_async.sync.aligned.m64n80k16.f32.bf16.bf16 {"
      "%0,%1,%2,%3,%4,%5,%6,%7,%8,%9,%10,%11,%12,%13,%14,%15,%16,%17,%18,%19,%20,%21,%22,%23,%24,%25,%26,%27,%28,%29,%30,%31,%32,%33,%34,%35,%36,"
      "%37,%38,%39"
      "}, da, db, p, 1, 1, %42, %43;\n}\n"
      :
      "+f"(d[0]),"+f"(d[1]),"+f"(d[2]),"+f"(d[3]),"+f"(d[4]),"+f"(d[5]),"+f"(d[6]),"+f"(d[7]),"+f"(d[8]),"+f"(d[9]),"+f"(d[10]),"+f"(d[11]),
      "+f"(d[12]),"+f"(d[13]),"+f"(d[14]),"+f"(d[15]),"+f"(d[16]),"+f"(d[17]),"+f"(d[18]),"+f"(d[19]),"+f"(d[20]),"+f"(d[21]),"+f"(d[22]),
      "+f"(d[23]),"+f"(d[24]),"+f"(d[25]),"+f"(d[26]),"+f"(d[27]),"+f"(d[28]),"+f"(d[29]),"+f"(d[30]),"+f"(d[31]),"+f"(d[32]),"+f"(d[33]),
      "+f"(d[34]),"+f"(d[35]),"+f"(d[36]),"+f"(d[37]),"+f"(d[38]),"+f"(d[39])
      : "r"(la), "r"(lb), "n"(TA), "n"(TB), "n"(OA >> 4), "n"(OB >> 4), "n"(TB ? 0xC0000010u : 0x40000040u), "r"(sc));
}

struct Ring { uint32_t s0, ph0; };
__device__ __forceinline__ void ring_pos(const Ring& r, int i, uint32_t& slot, uint32_t& ph) {
  uint32_t s = opaque(r.s0) + (i % NSLOT);
  uint32_t wrap = s >= NSLOT;
  slot = s - (wrap ? NSLOT : 0);
  ph = r.ph0 ^ ((i / NSLOT) & 1) ^ wrap;
}
__device__ __forceinline__ void ring_advance(Ring& r, int n) {
  uint32_t s, p;
  ring_pos(r, n, s, p);
  r.s0 = s; r.ph0 = p;
}
__host__ __device__ constexpr int idxK(int j) { return j == 0 ? 10 : 9 + 2 * j; }
__host__ __device__ constexpr int idxV(int j) { return j == 7 ? 25 : 12 + 2 * j; }
__host__ __device__ constexpr int xs(int c) { return c % NSLOT; }

__device__ __forceinline__ int start_delay(int cta) {
  return max(0, ((cta - N_OCTA) | 1) - STAG_A0) * STAG_SLOPE;
}
__device__ __forceinline__ char* o_slot(int item) {
  return (char*)g_o + (size_t)(item < OFRESH ? item % ORING : item - OFRESH + ORING) * O_ITEM_BYTES;
}
__device__ __forceinline__ int next_item(uint32_t a = NEXT_ITEM) {
  int v;
  asm volatile("ld.shared.s32 %0, [%1];" : "=r"(v) : "r"(a) : "memory");
  return __shfl_sync(0xffffffffu, v, 0);
}

template <int W, bool ACC>
__device__ __forceinline__ void mma_main(float (&d)[80], uint32_t aaddr, uint32_t baddr) {
  const uint32_t la = lo_sw(aaddr), lb = lo_sw(baddr);
  if (ACC) mma160<1, 0, W * 16384, 0>(d, la, lb); else mma160z<1, 0, W * 16384, 0>(d, la, lb);
  mma160<1, 0, W * 16384 + 1 * 2048, 1 * 32>(d, la, lb);
  mma160<1, 0, W * 16384 + 2 * 2048, 2 * 32>(d, la, lb);
  mma160<1, 0, W * 16384 + 3 * 2048, 3 * 32>(d, la, lb);
}
template <int W, bool ACC>
__device__ __forceinline__ void mma_mid(float (&d)[40], uint32_t aaddr, uint32_t baddr) {
  const uint32_t la = lo_sw(aaddr), lb = lo_sw(baddr);
  if (ACC) mma80<1, 0, 8192, W * 10240>(d, la, lb); else mma80z<1, 0, 8192, W * 10240>(d, la, lb);
  mma80<1, 0, 8192 + 1 * 2048, W * 10240 + 1 * 32>(d, la, lb);
  mma80<1, 0, 8192 + 2 * 2048, W * 10240 + 2 * 32>(d, la, lb);
  mma80<1, 0, 8192 + 3 * 2048, W * 10240 + 3 * 32>(d, la, lb);
}
template <int W, bool ACC>
__device__ __forceinline__ void mma_both(float (&dm)[80], float (&dh)[40], uint32_t aaddr, uint32_t baddr) {
  mma_mid<W, ACC>(dh, aaddr, baddr);
  mma_main<W, ACC>(dm, aaddr, baddr);
}
template <int KB, bool ACC>
__device__ __forceinline__ void s_mma(float (&sacc)[80], uint32_t kaddr) {
  const uint32_t la = lo_sw(kaddr), lb = lo_sw(SB + OFF_B);
  if (ACC) mma160<0, 0, KB * 8192, KB * B_SLOT>(sacc, la, lb); else mma160z<0, 0, KB * 8192, KB * B_SLOT>(sacc, la, lb);
  mma160<0, 0, KB * 8192 + 32, KB * B_SLOT + 32>(sacc, la, lb);
  mma160<0, 0, KB * 8192 + 64, KB * B_SLOT + 64>(sacc, la, lb);
  mma160<0, 0, KB * 8192 + 96, KB * B_SLOT + 96>(sacc, la, lb);
}
template <int N>
__device__ __forceinline__ void store_scaled(uint32_t addr, const float (&d)[N], float sc) {
#pragma unroll
  for (int J = 0; J < N / 8; J++)
    stsm_t(addr + J * 2048, pack2(d[8 * J] * sc, d[8 * J + 1] * sc), pack2(d[8 * J + 2] * sc, d[8 * J + 3] * sc),
           pack2(d[8 * J + 4] * sc, d[8 * J + 5] * sc), pack2(d[8 * J + 6] * sc, d[8 * J + 7] * sc));
}
__device__ __forceinline__ float4 lds_f4(uint32_t a) {
  float4 v;
  asm volatile("ld.shared.v4.f32 {%0,%1,%2,%3}, [%4];" : "=f"(v.x), "=f"(v.y), "=f"(v.z), "=f"(v.w) : "r"(a) : "memory");
  return v;
}
__device__ __forceinline__ void norm_pack(uint32_t* p, const float* d, const float4& i) {
  p[0] = pack2(d[0] * i.x, d[1] * i.y); p[1] = pack2(d[4] * i.z, d[5] * i.w);
  p[2] = pack2(d[2] * i.x, d[3] * i.y); p[3] = pack2(d[6] * i.z, d[7] * i.w);
  asm volatile("" : "+r"(p[0]), "+r"(p[1]), "+r"(p[2]), "+r"(p[3])::"memory");
}
template <int W>
__device__ __forceinline__ void pack_first(uint32_t (&pk)[60], const float (&om)[80], const float (&oh)[40], uint32_t laddr) {
  float4 n0 = lds_f4(laddr + W * 80), n1 = lds_f4(laddr + W * 80 + 16);
#pragma unroll
  for (int J = 0; J < 5; J++) {
    const float4 i = n0;
    n0 = n1;
    if (J + 2 < 5) n1 = lds_f4(laddr + W * 80 + (J + 2) * 16);
    norm_pack(&pk[20 + 4 * J], &om[8 * (5 * W + J)], i);
    norm_pack(&pk[4 * J], &oh[8 * J], i);
  }
}
template <int W, int J0, int J1>
__device__ __forceinline__ void pack_second(uint32_t (&pk)[60], const float (&om)[80], uint32_t laddr) {
  float4 n[J1 - J0];
#pragma unroll
  for (int J = J0; J < J1; J++) n[J - J0] = lds_f4(laddr + (1 - W) * 80 + J * 16);
#pragma unroll
  for (int J = J0; J < J1; J++) norm_pack(&pk[40 + 4 * J], &om[8 * (5 * (1 - W) + J)], n[J - J0]);
}
__device__ __forceinline__ char* o_ptr(int item) {
  const uint32_t t = tid_x();
  return o_slot(item) + ((t & 96) * 16 + (t & 28) * 8 + ((((t >> 1) ^ (t >> 4)) & 1) << 4) + (t & 1) * 8);
}
template <int W, int G0, int G1>
__device__ __forceinline__ void store_groups(char* op, const uint32_t (&pk)[60], uint32_t on) {
#pragma unroll
  for (int G = G0; G < G1; G++) {
    const int off = (G < 5 ? 1 : 2 * W) * B_SLOT + (5 * (G < 10 ? W : 1 - W) + G % 5) * 2048;
    asm volatile("{\n.reg .pred p;\nsetp.ne.u32 p, %5, 0;\n@p st.global.v2.b32 [%0], {%1, %2};\n@p st.global.v2.b32 [%0+256], {%3, %4};\n}\n"
                 ::"l"(op + off), "r"(pk[4 * G]), "r"(pk[4 * G + 1]), "r"(pk[4 * G + 2]), "r"(pk[4 * G + 3]), "r"(on) : "memory");
  }
}
__device__ __forceinline__ void publish_generic(uint32_t bar, int lane) {
  __syncwarp();
  mbar_arrive_if0(bar, lane);
}
__device__ __forceinline__ void publish(uint32_t bar, int lane) {
  proxy_fence();
  __syncwarp();
  mbar_arrive_if0(bar, lane);
}

#define A_ADDR(s) (SB + OFF_A + (s) * A_SLOT)
#define B_ADDR(s) (SB + OFF_B + (s) * B_SLOT)
#define WAIT_CHUNK(c, ro, sA)                \
  uint32_t sA;                               \
  {                                          \
    uint32_t pA_;                            \
    ring_pos(ring, (ro) + (c), sA, pA_);     \
    mbar_wait(bud, BAR_FULLA + sA * 8, pA_); \
  }
#define RELEASE_CHUNK(c, sA)                                  \
  mbar_arrive_if0(BAR_EMPTYA + (sA) * 8, tid);                \
  if ((c) < NSLOT) mbar_arrive_if0(BAR_EMPTYB + xs(c) * 8, tid);

template <int W>
__device__ __forceinline__ int attn_consumer(int item) {
  int bud = WAIT_BUDGET;
  const int tid = threadIdx.x & 127, lane = tid & 31, warp = tid >> 5;
  const uint32_t st_off = ((lane & 7) + 8 * (lane >> 4)) * 128 + (((2 * warp + ((lane >> 3) & 1)) ^ (lane & 7)) << 4);
  const uint32_t laddr = SB + OFF_L + (lane & 3) * 160;
  float om[80], oh[40], sacc[80];
  uint32_t pk[60];
#pragma unroll
  for (int i = 0; i < 40; i++) pk[i] = 0;
  zero_regs(om);
  Ring ring{0u, 0u};
  uint32_t par = 0;
  int prev = 0;
  const float qscale = 0.07216878364870322f * 1.4426950408889634f;
  constexpr uint32_t pown = B_ADDR(3 + W), poth = B_ADDR(4 - W);
  TL(0); TLG(62);
  {
    WAIT_CHUNK(0, 0, s0)
    wg_fence();
    mma_both<W, false>(sacc, oh, A_ADDR(s0), B_ADDR(xs(0)));
    wg_commit();
    WAIT_CHUNK(1, 0, s1)
    wg_fence();
    mma_both<W, true>(sacc, oh, A_ADDR(s1), B_ADDR(xs(1)));
    wg_commit();
    wg_wait<1>();
    RELEASE_CHUNK(0, s0)
  }
#pragma unroll 1
  for (int it = 0;; it++) {
    char* op = o_ptr(prev);
#pragma unroll
    for (int c = 2; c < 8 - W; c++) {
      WAIT_CHUNK(c, 0, sA)
      TL(40 + c);
      wg_fence();
      mma_both<W, true>(sacc, oh, A_ADDR(sA), B_ADDR(xs(c)));
      wg_commit();
      wg_wait<1>();
      uint32_t sP, pP;
      ring_pos(ring, c - 1, sP, pP);
      RELEASE_CHUNK(c - 1, sP)
      constexpr int NG = W == 0 ? 3 : W1_NG;
      if (c == 2) { pack_second<W, 0, 1>(pk, om, laddr); store_groups<W, 0 * NG, 1 * NG>(op, pk, it); }
      if (c == 3) { pack_second<W, 1, 2>(pk, om, laddr); store_groups<W, 1 * NG, 2 * NG>(op, pk, it); }
      if (c == 4) { pack_second<W, 2, 3>(pk, om, laddr); store_groups<W, 2 * NG, 3 * NG>(op, pk, it); }
      if (c == 5) { pack_second<W, 3, 4>(pk, om, laddr); store_groups<W, 3 * NG, 4 * NG>(op, pk, it); }
      if (c == 6) {
        pack_second<W, 4, 5>(pk, om, laddr);
        if (W == 1) {
          wg_wait<0>();
          RELEASE_CHUNK(6, sA)
          mbar_arrive_if0(BAR_XDONE, tid);
        }
        store_groups<W, 4 * NG, 15>(op, pk, it);
        __syncwarp();
        mbar_arrive_if0(BAR_OFULL, lane | (it == 0));
      }
    }
    uint32_t sK0, pK0, s7, p7;
    ring_pos(ring, idxK(W), sK0, pK0);
    ring_pos(ring, 7, s7, p7);
    if (W == 1) mbar_wait(bud, BAR_FULLA + s7 * 8, p7);
    WAIT_CHUNK(8, 0, s8)
    WAIT_CHUNK(9, 0, s9)
    TL(48);
    if (W == 0) {
      wg_fence();
      mma_mid<W, true>(oh, A_ADDR(s8), B_ADDR(xs(8)));
      mma_mid<W, true>(oh, A_ADDR(s9), B_ADDR(xs(9)));
      wg_commit();
      wg_wait<1>();
      RELEASE_CHUNK(7, s7)
      wg_fence();
      mma_main<W, true>(sacc, A_ADDR(s8), B_ADDR(xs(8)));
      mma_main<W, true>(sacc, A_ADDR(s9), B_ADDR(xs(9)));
      wg_commit();
      bar_arrive(5, 256);
      TL(49);
      wg_wait<1>();
      reg_fence(oh);
      mbar_wait(bud, BAR_XDONE, par);
      store_scaled(B_ADDR(1) + st_off, oh, qscale);
    } else {
      bar_sync(5, 256);
      wg_fence();
      mma_mid<W, true>(oh, A_ADDR(s7), B_ADDR(xs(7)));
      mma_mid<W, true>(oh, A_ADDR(s8), B_ADDR(xs(8)));
      mma_mid<W, true>(oh, A_ADDR(s9), B_ADDR(xs(9)));
      wg_commit();
      mma_main<W, true>(sacc, A_ADDR(s7), B_ADDR(xs(7)));
      wg_commit();
      mma_main<W, true>(sacc, A_ADDR(s8), B_ADDR(xs(8)));
      wg_commit();
      wg_wait<2>();
      reg_fence(oh);
      store_scaled(B_ADDR(1) + 10240 + st_off, oh, qscale);
      wg_fence();
      mma_main<W, true>(sacc, A_ADDR(s9), B_ADDR(xs(9)));
      wg_commit();
      bar_arrive(8, 256);
      TL(49);
      wg_wait<2>();
      RELEASE_CHUNK(7, s7)
      publish(BAR_QH, lane);
    }
    wg_wait<0>();
    reg_fence(sacc);
    TL(1);
    RELEASE_CHUNK(8, s8)
    RELEASE_CHUNK(9, s9)
    store_scaled(B_ADDR(2 * W) + st_off, sacc, qscale);
    if (W == 1) publish(BAR_QM, lane); else proxy_fence();
    TL(2);
    uint32_t sK = sK0, sV1 = 0;
    if (W == 0) {
      zero_regs(om); zero_regs(oh);
      reg_fence(om); reg_fence(oh);
      mbar_wait(bud, BAR_FULLA + sK0 * 8, pK0);
      bar_sync(8, 256);
      wg_fence();
      s_mma<0, false>(sacc, A_ADDR(sK));
      mbar_wait(bud, BAR_QH, par);
      TL(3);
      wg_fence();
      s_mma<1, true>(sacc, A_ADDR(sK));
      mbar_wait(bud, BAR_QM, par);
      TL(5);
      wg_fence();
      s_mma<2, true>(sacc, A_ADDR(sK));
      wg_commit();
      wg_commit();
      bar_arrive(2, 256);
    } else {
      uint32_t pV1;
      ring_pos(ring, idxV(0), sV1, pV1);
      mbar_wait(bud, BAR_FULLA + sK * 8, pK0);
      bar_sync(2, 256);
      wg_fence();
      s_mma<0, false>(sacc, A_ADDR(sK));
      s_mma<1, true>(sacc, A_ADDR(sK));
      s_mma<2, true>(sacc, A_ADDR(sK));
      wg_commit();
      TL(6);
      mbar_wait(bud, BAR_FULLA + sV1 * 8, pV1);
      mbar_wait(bud, BAR_PFULL, 0);
      TL(7);
      wg_fence();
      mma_both<W, false>(om, oh, A_ADDR(sV1), poth);
      wg_commit();
      bar_arrive(1, 256);
    }
    Ring rv;
    ring_pos(ring, idxV(W), rv.s0, rv.ph0);
#pragma unroll 1
    for (int jj = 0;; jj++) {
      wg_wait<1>();
      reg_fence(sacc);
      TL(8 + jj * 7);
      mbar_arrive2_if0(BAR_EMPTYA + sK * 8, tid);
      mbar_arrive_if0(BAR_EMPTYB + tid * 8, (tid >= 3) | (jj != 3));
#pragma unroll
      for (int J = 0; J < 10; J++) {
        stsm_t(pown + st_off + J * 2048, pack2(ex2(sacc[8 * J]), ex2(sacc[8 * J + 1])), pack2(ex2(sacc[8 * J + 2]), ex2(sacc[8 * J + 3])),
               pack2(ex2(sacc[8 * J + 4]), ex2(sacc[8 * J + 5])), pack2(ex2(sacc[8 * J + 6]), ex2(sacc[8 * J + 7])));
        if (W == 1 && (J == 2 || J == 5)) publish_generic(BAR_PMID + (J / 3) * 8, lane | (jj != 3));
        if (J == 4) {
          wg_wait<0>();
          mbar_arrive_if0(BAR_EMPTYA + sV1 * 8, tid | (W == 0 && jj == 0));
        }
      }
      publish(BAR_PFULL + W * 8, lane);
      TL(10 + jj * 7);
      if (jj == 3) break;
      uint32_t pK, pV1;
      ring_pos(rv, 1, sK, pK);
      ring_pos(rv, 2, sV1, pV1);
      mbar_wait(bud, BAR_FULLA + rv.s0 * 8, rv.ph0);
      bar_sync(1 + W, 256);
      wg_fence();
      mma_both<W, true>(om, oh, A_ADDR(rv.s0), pown);
      wg_commit();
      mbar_wait(bud, BAR_FULLA + sK * 8, pK);
      TL(11 + jj * 7);
      wg_fence();
      s_mma<0, false>(sacc, A_ADDR(sK));
      s_mma<1, true>(sacc, A_ADDR(sK));
      wg_commit();
      wg_wait<1>();
      mbar_arrive_if0(BAR_EMPTYA + rv.s0 * 8, tid);
      wg_fence();
      s_mma<2, true>(sacc, A_ADDR(sK));
      wg_commit();
      TL(13 + jj * 7);
      mbar_wait(bud, BAR_FULLA + sV1 * 8, pV1);
      mbar_wait(bud, BAR_PFREE + W * 8, jj & 1);
      mbar_wait(bud, BAR_PFULL + (1 - W) * 8, (jj + W) & 1);
      TL(14 + jj * 7);
      wg_fence();
      mma_both<W, true>(om, oh, A_ADDR(sV1), poth);
      wg_commit();
      bar_arrive(2 - W, 256);
      ring_advance(rv, 4);
    }
    uint32_t sV7, pV7;
    ring_pos(ring, idxV(7), sV7, pV7);
    prev = item;
    if (W == 1 && !DEBUG_TIMEOUT) item = next_item();
    if (W == 0) {
      uint32_t sV6, pV6;
      ring_pos(ring, idxV(6), sV6, pV6);
      mbar_wait(bud, BAR_FULLA + sV6 * 8, pV6);
      bar_sync(1, 256);
      wg_fence();
      mma_both<0, true>(om, oh, A_ADDR(sV6), pown);
      wg_commit();
      mbar_wait(bud, BAR_FULLA + sV7 * 8, pV7);
      wg_wait<0>();
      mbar_arrive_if0(BAR_EMPTYA + sV6 * 8, tid);
      mbar_wait(bud, BAR_PFULL + 8, 1);
      wg_fence();
      mma_both<0, true>(om, oh, A_ADDR(sV7), poth);
      wg_commit();
      bar_arrive(6, 256);
    } else {
      mbar_wait(bud, BAR_FULLA + sV7 * 8, pV7);
      bar_sync(6, 256);
    }
    TL(32);
    if (DEBUG_TIMEOUT) item = next_item(NEXT_ITEM + 4);
    else if (W == 0) item = next_item();
    if (item >= NITEMS) {
      if (W == 1) {
        wg_fence();
        mma_both<1, true>(om, oh, A_ADDR(sV7), pown);
        wg_commit();
      }
      wg_wait<0>();
      reg_fence(om); reg_fence(oh);
      TL(33);
      mbar_wait(bud, BAR_LFULL, par);
      mbar_arrive_if0(BAR_FREE, tid);
      TL(34);
      pack_first<W>(pk, om, oh, laddr);
      op = o_ptr(prev);
      store_groups<W, 0, 10>(op, pk, 1);
      pack_second<W, 0, 5>(pk, om, laddr);
      store_groups<W, 10, 15>(op, pk, 1);
      publish_generic(BAR_OFULL, lane);
      TL(35); TLG(63);
      TL_FLUSH();
      return item;
    }
    {
      if (W == 1) {
        wg_fence();
        mma_both<1, true>(om, oh, A_ADDR(sV7), pown);
        wg_commit();
      }
      WAIT_CHUNK(0, 26, s0)
      WAIT_CHUNK(1, 26, s1)
      if (W == 0) {
        wg_wait<0>();
        reg_fence(om); reg_fence(oh);
        TL(33);
        wg_fence();
        mma_main<W, false>(sacc, A_ADDR(s0), B_ADDR(xs(0)));
        wg_commit();
      } else {
        wg_fence();
        mma_main<W, false>(sacc, A_ADDR(s0), B_ADDR(xs(0)));
        mma_main<W, true>(sacc, A_ADDR(s1), B_ADDR(xs(1)));
        wg_commit();
        wg_wait<1>();
        reg_fence(om); reg_fence(oh);
        TL(33);
      }
      mbar_arrive_if0(BAR_EMPTYA + sV7 * 8, tid);
      mbar_wait(bud, BAR_LFULL, par);
      mbar_arrive_if0(BAR_EMPTYB + 24 + tid * 8, tid >= 2);
      TL(34);
      pack_first<W>(pk, om, oh, laddr);
      TL(36);
      wg_fence();
      mma_mid<W, false>(oh, A_ADDR(s0), B_ADDR(xs(0)));
      wg_commit();
      mma_mid<W, true>(oh, A_ADDR(s1), B_ADDR(xs(1)));
      if (W == 0) mma_main<W, true>(sacc, A_ADDR(s1), B_ADDR(xs(1)));
      wg_commit();
      TL(37);
      wg_wait<1>();
      RELEASE_CHUNK(0, s0)
      TL(35); TLG(63);
    }
    TL_FLUSH();
    TL(0); TLG(62);
    ring_advance(ring, 26);
    par ^= 1;
  }
}

__device__ __forceinline__ uint4 lds128(uint32_t a) {
  uint4 v;
  asm volatile("ld.shared.v4.b32 {%0,%1,%2,%3}, [%4];" : "=r"(v.x), "=r"(v.y), "=r"(v.z), "=r"(v.w) : "r"(a) : "memory");
  return v;
}
__device__ __forceinline__ void acc2(float& s, float& t, uint32_t w) {
  s += __uint_as_float(w << 16);
  t += __uint_as_float(w & 0xffff0000u);
}
__device__ __forceinline__ uint32_t badd2(uint32_t a, uint32_t b) { uint32_t r; asm("add.rn.bf16x2 %0, %1, %2;" : "=r"(r) : "r"(a), "r"(b)); return r; }
__device__ __forceinline__ void sum_unit(float& acc, uint32_t pb) {
  const uint4 v0 = lds128(pb), v1 = lds128(pb ^ 32), v2 = lds128(pb ^ 64), v3 = lds128(pb ^ 96);
  const uint32_t w0 = badd2(v0.x, v0.y), w1 = badd2(v0.z, v0.w);
  float s0 = acc + __uint_as_float(w0 << 16), t0 = __uint_as_float(w0 & 0xffff0000u);
  float s1 = __uint_as_float(w1 << 16), t1 = __uint_as_float(w1 & 0xffff0000u);
  acc2(s0, t0, badd2(v1.x, v1.y)); acc2(s1, t1, badd2(v1.z, v1.w));
  acc2(s0, t0, badd2(v2.x, v2.y)); acc2(s1, t1, badd2(v2.z, v2.w));
  acc2(s0, t0, badd2(v3.x, v3.y)); acc2(s1, t1, badd2(v3.z, v3.w));
  acc = (s0 + t0) + (s1 + t1);
}
__device__ __forceinline__ float bf_lo(uint32_t w) { return __uint_as_float(w << 16); }
__device__ __forceinline__ float bf_hi(uint32_t w) { return __uint_as_float(w & 0xffff0000u); }
__device__ __forceinline__ float bf_rn(float x) { return __bfloat162float(__float2bfloat16(x)); }
__device__ __forceinline__ void slow_item(const Params& p, int item, int hw) {
  const int blk = item >> 9, h = (item >> 4) & 31, b = item & 15;
#pragma unroll 1
  for (int n = hw; n < SQ; n += 3) {
    float q[6] = {0.f, 0.f, 0.f, 0.f, 0.f, 0.f};
    {
      const uint32_t* xr = (const uint32_t*)(p.xp[blk] + (size_t)(b * SQ + n) * DM);
      const uint32_t* wq = (const uint32_t*)(p.wqp[blk] + h * DH) + (tid_x() & 31);
#pragma unroll 2
      for (int k = 0; k < DM / 2; k++) {
        const uint32_t xv = xr[k];
#pragma unroll
        for (int i = 0; i < 3; i++) {
          const uint32_t w0 = wq[i * 32], w1 = wq[NH * DH / 2 + i * 32];
          q[2 * i] = fmaf(bf_lo(xv), bf_lo(w0), fmaf(bf_hi(xv), bf_lo(w1), q[2 * i]));
          q[2 * i + 1] = fmaf(bf_lo(xv), bf_hi(w0), fmaf(bf_hi(xv), bf_hi(w1), q[2 * i + 1]));
        }
        wq += NH * DH;
      }
    }
    const uint32_t q0 = pack2(q[0], q[1]), q1 = pack2(q[2], q[3]), q2 = pack2(q[4], q[5]);
    float o[6] = {0.f, 0.f, 0.f, 0.f, 0.f, 0.f}, m = -INFINITY, l = 0.f;
    const uint32_t* kg = (const uint32_t*)(p.kp[blk] + (size_t)(b * NH + h) * SK * DH) + (tid_x() & 31);
    const uint32_t* vg = (const uint32_t*)(p.vp[blk] + (size_t)(b * NH + h) * SK * DH) + (tid_x() & 31);
#pragma unroll 1
    for (int k = 0; k < SK; k++) {
      const uint32_t k0 = kg[0], k1 = kg[32], k2 = kg[64], v0 = vg[0], v1 = vg[32], v2 = vg[64];
      kg += DH / 2; vg += DH / 2;
      float sc = fmaf(bf_lo(q0), bf_lo(k0), bf_hi(q0) * bf_hi(k0));
      sc = fmaf(bf_lo(q1), bf_lo(k1), fmaf(bf_hi(q1), bf_hi(k1), sc));
      sc = fmaf(bf_lo(q2), bf_lo(k2), fmaf(bf_hi(q2), bf_hi(k2), sc));
#pragma unroll
      for (int d = 16; d; d >>= 1) sc += __shfl_xor_sync(0xffffffffu, sc, d);
      sc = bf_rn(bf_rn(sc) * 0.07216878364870322f);
      const float mn = fmaxf(m, sc), a = ex2((m - mn) * 1.4426950408889634f), pr = ex2((sc - mn) * 1.4426950408889634f);
      m = mn;
      l = fmaf(l, a, pr);
      o[0] = fmaf(o[0], a, pr * bf_lo(v0)); o[1] = fmaf(o[1], a, pr * bf_hi(v0));
      o[2] = fmaf(o[2], a, pr * bf_lo(v1)); o[3] = fmaf(o[3], a, pr * bf_hi(v1));
      o[4] = fmaf(o[4], a, pr * bf_lo(v2)); o[5] = fmaf(o[5], a, pr * bf_hi(v2));
    }
    float inv;
    asm("rcp.approx.ftz.f32 %0, %1;" : "=f"(inv) : "f"(l));
    const int lane = tid_x() & 31;
    const int r = n & 15, c = 4 * ((r & 7) >> 1) + 2 * (r >> 3) + (r & 1);
    char* on = o_slot(item) + (lane >> 2) * 256 + (lane & 3) * 64 + (n >> 4) * 2048 +
               (((c >> 3) ^ ((lane >> 1) & 1)) << 4) + (c & 7) * 2;
#pragma unroll
    for (int i = 0; i < 3; i++) {
      *(__nv_bfloat16*)(on + i * B_SLOT) = __float2bfloat16(o[2 * i] * inv);
      *(__nv_bfloat16*)(on + i * B_SLOT + 32) = __float2bfloat16(o[2 * i + 1] * inv);
    }
  }
}
__device__ __forceinline__ void attn_helper(const Params& p, int hw, int item, int epoch) {
  int bud = WAIT_BUDGET;
  if (item < PF_N && hw < 2) {
    const char* g = (const char*)(hw ? p.vp[0] : p.kp[0]) + (size_t)(((item & 15) * NH + (item >> 4)) * SK) * DH * 2;
    const long long t0 = clock64();
#pragma unroll 1
    for (int i = 0; i < 32; i++) {
      while (clock64() - t0 < PF_WAIT + i * PF_GAP) __nanosleep(50);
      for (int k = 0; k < 6; k++) asm volatile("prefetch.global.L2 [%0];" ::"l"(g + i * 6144 + k * 1024 + (tid_x() & 31) * 32));
      __syncwarp();
    }
  }
#pragma unroll 1
  for (int it = 0; item < NITEMS; it++) {
    const uint32_t par = it & 1;
    int lane = tid_x() & 31;
    const int r = lane >> 1;
    const uint32_t a0 = B_ADDR(3) + (16 * hw + r) * 128 + (lane & 1) * 16 + ((r & 3) << 5);
    float acc[4] = {0.f, 0.f, 0.f, 0.f};
#pragma unroll 1
    for (int j = 0; j < 8; j++) {
      const uint32_t pb = a0 + (j & 1) * B_SLOT, bfull = BAR_PFULL + (j & 1) * 8, pfull = (j >> 1) & 1;
      mbar_wait(bud, j == 7 ? BAR_PMID : bfull, j == 7 ? par : pfull);
      sum_unit(acc[0], pb);
      if (j == 7) mbar_wait(bud, BAR_PMID + 8, par);
      sum_unit(acc[1], pb + 6144);
      if (j == 7) mbar_wait(bud, bfull, pfull);
      sum_unit(acc[2], pb + 2 * 6144);
      if (hw == 0) sum_unit(acc[3], pb + 3 * 6144);
      __syncwarp();
      mbar_arrive_if0(BAR_PFREE + (j & 1) * 8, lane);
      if (j == 5 && hw == 2) {
        if (lane == 0) TLP(60);
        if (item >= ORING && item < OFRESH) flag_wait(bud, &g_done[item - ORING], (epoch + 1) * 2);
        if (lane == 0) TLP(61);
      }
    }
    bool bad = false;
    const uint32_t la = SB + OFF_L + (((r & 7) >> 1) * 40 + 2 * (r >> 3) + (r & 1) + 4 * hw) * 4;
#pragma unroll
    for (int u = 0; u < 4; u++) {
      const float l = acc[u] + __shfl_xor_sync(0xffffffffu, acc[u], 1);
      if (u < 3 || hw == 0) {
        bad |= !(l >= 8.8817841970012523e-16f && l <= 1.125899906842624e15f);
        float inv;
        asm("rcp.approx.ftz.f32 %0, %1;" : "=f"(inv) : "f"(l));
        asm volatile("st.shared.f32 [%0], %1;" ::"r"(la + u * 48), "f"(inv) : "memory");
      }
    }
    publish_generic(BAR_LFULL, lane);
    if (lane == 0) TLP(40 + hw * 4);
    uint32_t anybad;
    asm volatile("{\n.reg .pred p, q;\nsetp.ne.u32 p, %1, 0;\nbarrier.red.or.pred q, 7, 96, p;\nselp.u32 %0, 1, 0, q;\n}\n"
                 : "=r"(anybad) : "r"((uint32_t)bad) : "memory");
    if (__any_sync(0xffffffffu, anybad)) {
      mbar_wait(bud, BAR_OFULL, par);
      slow_item(p, item, hw);
      bar_sync(7, 96);
    }
    if (hw == 1) {
      mbar_wait(bud, BAR_OFULL, par);
      if ((tid_x() & 31) == 0) {
        TLP(41 + hw * 4);
        asm volatile("red.release.gpu.global.add.s32 [%0], 1;" ::"l"(&g_ready[item]) : "memory");
        TLP(42 + hw * 4);
      }
      __syncwarp();
    }
    item = next_item();
  }
}

__device__ __forceinline__ int attn_producer(const Params& p, int item) {
  int bud = WAIT_BUDGET;
  uint32_t sa = 0, pa = 1;
  uint64_t pol;
  asm volatile("createpolicy.fractional.L2::evict_first.b64 %0, 1.0;" : "=l"(pol));
  const bool draws = item >= N_OCTA;
  {
    const int delay = start_delay(item);
    const long long t0 = clock64();
    while (clock64() - t0 < delay) __nanosleep(100);
  }
#pragma unroll 1
  for (int it = 0; item < NITEMS; it++) {
    const int blk = item >> 9, h = (item >> 4) & 31, b = item & 15;
    const int row0 = (b * NH + h) * SK;
#pragma unroll
    for (int c = 0; c < 10; c++) {
      mbar_wait(bud, BAR_EMPTYA + sa * 8, pa);
      TLP(c);
      mbar_expect(BAR_FULLA + sa * 8, A_SLOT + B_SLOT);
      tma3d(A_ADDR(sa), &p.wq[blk], BAR_FULLA + sa * 8, 0, c * 64, h * 3);
      mbar_wait(bud, BAR_EMPTYB + xs(c) * 8, c < NSLOT);
      TLP(10 + c);
      tma2d(B_ADDR(xs(c)), &p.x[blk], BAR_FULLA + sa * 8, c * 64, b * SQ);
      if (++sa == NSLOT) { sa = 0; pa ^= 1; }
    }
#pragma unroll
    for (int i = 0; i < 16; i++) {
      const bool isK = (i == 0) || ((i & 1) && i < 15);
      const int j = i == 0 ? 0 : (i == 15 ? 7 : (isK ? (i + 1) >> 1 : (i - 2) >> 1));
      mbar_wait(bud, BAR_EMPTYA + sa * 8, pa);
      TLP(20 + i);
      if (i == 11) item = draws ? NCTA + (int)atomicInc(&g_ticket, NITEMS - NCTA + N_ATT - 1) : NITEMS;
      if (i == 13) asm volatile("st.shared.s32 [%0], %1;" ::"r"(NEXT_ITEM), "r"(item) : "memory");
      mbar_expect(BAR_FULLA + sa * 8, A_SLOT);
      tma3d_hint(A_ADDR(sa), isK ? &p.k[blk] : &p.v[blk], BAR_FULLA + sa * 8, 0, row0 + j * 64, 0, pol);
      if (++sa == NSLOT) { sa = 0; pa ^= 1; }
    }
  }
  return item;
}

struct OJob { int tile, part, s0, s1; };
__device__ __forceinline__ OJob get_ojob(int cta, int last) {
  if (cta < N_OCTA) return OJob{cta, 0, 0, STEP1};
  const int u = last - NITEMS, part = 1 + (u >> 5);
  return OJob{u & 31, part, part == 1 ? STEP1 : part == 2 ? STEP2 : STEP3, part == 1 ? STEP2 : part == 2 ? STEP3 : part == 3 ? 2 * NH : 0};
}

template <int W>
__device__ __forceinline__ void oproj_consumer(const Params& p, const OJob job) {
  int bud = WAIT_BUDGET;
  const int tid = threadIdx.x & 127, lane = tid & 31, warp = tid >> 5;
  const int qrow = 8 * ((lane >> 1) & 1) + 4 * (lane >> 4) + 2 * ((lane >> 2) & 1) + (lane & 1);
  const uint32_t st_off = qrow * 128 + (((2 * warp + ((lane >> 3) & 1)) ^ (qrow & 7)) << 4);
  float a0[80], a1[80], ah[40];
  zero_regs(a0); zero_regs(a1); zero_regs(ah);
  int step = job.s0;
#pragma unroll 1
  while (step < job.s1) {
    const int nc = 3 * ((step < NH ? NH : job.s1) - step);
    uint32_t st = 0;
#pragma unroll 1
    for (int c = 0; c < nc; c++) {
      mbar_wait(bud, BAR_GFULL + st * 8, (step - job.s0) & 1);
      wg_fence();
      const uint32_t la = lo_sw(SB + st * O_STAGE), lb = lo_o(SB + st * O_STAGE + O_AB);
#define O_STEP(ks, sc)                                                        \
  mma80r<1, 1, 2 * 8192 + ks * 2048, W * 10240 + ks * 512>(ah, la, lb, sc);   \
  mma160r<1, 1, (W * 3) * 8192 + ks * 2048, ks * 512>(a0, la, lb, sc);        \
  mma160r<1, 1, (W * 3 + 1) * 8192 + ks * 2048, ks * 512>(a1, la, lb, sc);
      O_STEP(0, c != 0) O_STEP(1, 1)
      wg_commit();
      wg_wait<1>();
      mbar_arrive_if0(BAR_GEMPTY + (st == 0 ? 2 : st - 1) * 8, tid | (c == 0));
      wg_fence();
      O_STEP(2, 1) O_STEP(3, 1)
#undef O_STEP
      wg_commit();
      if (++st == 3) {
        st = 0;
        if (W == 0)
          asm volatile("{\n.reg .pred p;\nsetp.eq.u32 p, %1, 0;\n@p red.relaxed.gpu.global.add.s32 [%0], 1;\n}\n"
                       ::"l"(&g_done[step * 16 + (job.tile >> 1)]), "r"(tid) : "memory");
        TLG(step);
        step++;
      }
    }
    wg_wait<0>();
    reg_fence(a0); reg_fence(a1); reg_fence(ah);
    const uint32_t sg = SB + O_OUT + st_off;
    if (W == 1) {
      bar_arrive(3, 256);
      store_scaled(sg + 3 * B_SLOT, a0, 1.0f);
      publish(BAR_GOUT + 24, lane);
      bar_sync(9, 256);
      store_scaled(sg + 2 * B_SLOT + 10240, ah, 1.0f);
      publish(BAR_GOUT + 16, lane);
      store_scaled(sg + 4 * B_SLOT, a1, 1.0f);
      publish(BAR_GOUT + 32, lane);
    } else {
      bar_arrive(9, 256);
      bar_sync(3, 256);
      store_scaled(sg, a0, 1.0f);
      publish(BAR_GOUT, lane);
      store_scaled(sg + B_SLOT, a1, 1.0f);
      publish(BAR_GOUT + 8, lane);
      store_scaled(sg + 2 * B_SLOT, ah, 1.0f);
      publish(BAR_GOUT + 16, lane);
    }
  }
  TL_FLUSH();
  TLG(0);
  const int e0 = W * 128 + tid;
  const uint4* gp = g_part + ((job.tile >> 1) * SQ + job.part * 40) * (DM / 8) + (job.tile & 1) * 40;
  uint4* go = (uint4*)p.outp + ((job.tile >> 1) * SQ + job.part * 40) * (2 * DM / 8) + DM / 8 + (job.tile & 1) * 40;
  mbar_wait(bud, BAR_GRED, 0);
  TLG(1);
  uint4 v[7][3];
#pragma unroll
  for (int i = 0; i < 7; i++) {
    const int e = min(i * 256 + e0, 1599), r = e / 40, cc = e % 40;
#pragma unroll
    for (int q = 0; q < 3; q++) v[i][q] = __ldcg(gp + (((job.part + 1 + q) & 3) * NB * SQ + r) * (DM / 8) + cc);
  }
#pragma unroll
  for (int i = 0; i < 7; i++) {
    const int e = min(i * 256 + e0, 1599), r = e / 40, cc = e % 40, rr = job.part * 40 + r;
    const uint4 o = lds128(SB + O_OUT + (cc >> 3) * B_SLOT + rr * 128 + (((cc ^ rr) & 7) << 4));
    uint4 res;
    res.x = pack2((bf_lo(o.x) + bf_lo(v[i][0].x)) + (bf_lo(v[i][1].x) + bf_lo(v[i][2].x)), (bf_hi(o.x) + bf_hi(v[i][0].x)) + (bf_hi(v[i][1].x) + bf_hi(v[i][2].x)));
    res.y = pack2((bf_lo(o.y) + bf_lo(v[i][0].y)) + (bf_lo(v[i][1].y) + bf_lo(v[i][2].y)), (bf_hi(o.y) + bf_hi(v[i][0].y)) + (bf_hi(v[i][1].y) + bf_hi(v[i][2].y)));
    res.z = pack2((bf_lo(o.z) + bf_lo(v[i][0].z)) + (bf_lo(v[i][1].z) + bf_lo(v[i][2].z)), (bf_hi(o.z) + bf_hi(v[i][0].z)) + (bf_hi(v[i][1].z) + bf_hi(v[i][2].z)));
    res.w = pack2((bf_lo(o.w) + bf_lo(v[i][0].w)) + (bf_lo(v[i][1].w) + bf_lo(v[i][2].w)), (bf_hi(o.w) + bf_hi(v[i][0].w)) + (bf_hi(v[i][1].w) + bf_hi(v[i][2].w)));
    if (i * 256 + e0 < 1600) go[r * (2 * DM / 8) + cc] = res;
  }
  TLG(2);
  TL_FLUSH();
}

__device__ __forceinline__ void oproj_producer(const Params& p, const OJob job, int target) {
  int bud = WAIT_BUDGET;
  if (WO_PF) asm volatile("cp.async.bulk.prefetch.L2.global [%0], 7680;" ::"l"(p.wop[job.s0 >> 5] + (size_t)((job.s0 & 31) * DH + job.tile * 6) * DM) : "memory");
  if (WO_PF > 1) asm volatile("cp.async.bulk.prefetch.L2.global [%0], 7680;" ::"l"(p.wop[job.s0 >> 5] + (size_t)(((job.s0 + 1) & 31) * DH + job.tile * 6) * DM) : "memory");
  mbar_wait(bud, BAR_FREE, 0);
#pragma unroll 1
  for (int step = job.s0; step < job.s1; step++) {
    const int item = step * 16 + (job.tile >> 1);
    const char* og = o_slot(item);
    if (WO_PF && step + WO_PF < job.s1)
      asm volatile("cp.async.bulk.prefetch.L2.global [%0], 7680;" ::"l"(p.wop[(step + WO_PF) >> 5] + (size_t)(((step + WO_PF) & 31) * DH + job.tile * 6) * DM) : "memory");
    flag_wait(bud, &g_ready[item], target);
    asm volatile("fence.proxy.async.global;" ::: "memory");
#pragma unroll
    for (int kb = 0; kb < 3; kb++) {
      const uint32_t dst = SB + kb * O_STAGE, bar = BAR_GFULL + kb * 8;
      mbar_wait(bud, BAR_GEMPTY + kb * 8, ((step - job.s0) & 1) ^ 1);
      mbar_expect(bar, O_STAGE);
      tma3d(dst, &p.wo[step >> 5], bar, 0, ((step & 31) * 3 + kb) * 64, (job.tile & 1) * 5);
      bulk_load(dst + O_AB, og + kb * B_SLOT, B_SLOT, bar);
    }
  }
}

__device__ __forceinline__ void oproj_storer(const Params& p, const OJob job, int target) {
  int bud = WAIT_BUDGET;
  const int col = (job.tile & 1) * 320, row = (job.tile >> 1) * SQ;
  if (job.part == 0) {
    for (int k = 0; k < 3; k++) {
      mbar_wait(bud, BAR_GOUT + k * 8, 0);
      tma_store2d(&p.out, SB + O_OUT + k * B_SLOT, col + k * 64, row);
    }
    asm volatile("cp.async.bulk.commit_group;" ::: "memory");
    asm volatile("cp.async.bulk.wait_group.read 0;" ::: "memory");
    mbar_arrive2_if0(BAR_GEMPTY + 16, 0);
    mbar_wait(bud, BAR_GFULL + 16, 0);
    for (int k = 3; k < 5; k++) {
      mbar_wait(bud, BAR_GOUT + k * 8, 0);
      tma_store2d(&p.out, SB + O_OUT + k * B_SLOT, col + k * 64, row);
      asm volatile("cp.async.bulk.commit_group;" ::: "memory");
      asm volatile("cp.async.bulk.wait_group.read 0;" ::: "memory");
      __nanosleep(1000);
    }
  }
#pragma unroll 1
  for (int i = 0; i < 5; i++) {
    const int k = (0x42103 >> (4 * i)) & 15;
    mbar_wait(bud, BAR_GOUT + k * 8, job.part == 0);
    for (int q = 1; q < 4; q++) {
      const int sh = (job.part + q) & 3;
      tma_store2d(&p.part, SB + O_OUT + k * B_SLOT + sh * 5120, col + k * 64, job.part * NB * SQ + row + sh * 40);
    }
  }
  asm volatile("cp.async.bulk.commit_group;" ::: "memory");
  asm volatile("cp.async.bulk.wait_group 0;" ::: "memory");
  asm volatile("fence.proxy.async.global;" ::: "memory");
  asm volatile("red.release.gpu.global.add.s32 [%0], 1;" ::"l"(&g_pcnt[job.tile]) : "memory");
  flag_wait(bud, &g_pcnt[job.tile], 4 * target);
  mbar_arrive_if0(BAR_GRED, 0);
}

__global__ void __launch_bounds__(384, 1) fused_kernel(const __grid_constant__ Params p) {
  extern __shared__ __align__(1024) char smem_raw[];
  if ((smem_u32(smem_raw) & 0xFFFFFFu) != SB) return;
  const int cta = (((blockIdx.x >> 1) * PERM_M) % (NCTA / 2)) * 2 + (blockIdx.x & 1);
  const int warp = __shfl_sync(0xffffffffu, threadIdx.x >> 5, 0);
  if (threadIdx.x == 0) {
    for (int i = 0; i < NSLOT; i++) { mbar_init(BAR_FULLA + i * 8, 1); mbar_init(BAR_EMPTYA + i * 8, 2); mbar_init(BAR_EMPTYB + i * 8, 2); }
    proxy_fence();
  }
  if (threadIdx.x == 64) {
    mbar_init(BAR_XDONE, 1); mbar_init(BAR_QH, 4); mbar_init(BAR_QM, 4);
    mbar_init(BAR_PFULL, 4); mbar_init(BAR_PFULL + 8, 4); mbar_init(BAR_PFREE, 3); mbar_init(BAR_PFREE + 8, 3);
    mbar_init(BAR_LFULL, 3); mbar_init(BAR_PMID, 4); mbar_init(BAR_PMID + 8, 4); mbar_init(BAR_OFULL, 8);
  }
  if (threadIdx.x == 96) {
    for (int i = 0; i < O_NST; i++) { mbar_init(BAR_GFULL + i * 8, 1); mbar_init(BAR_GEMPTY + i * 8, 2); }
    for (int i = 0; i < 5; i++) mbar_init(BAR_GOUT + i * 8, i == 2 ? 8 : 4);
    mbar_init(BAR_GRED, 1); mbar_init(BAR_FREE, 2);
    proxy_fence();
  }
  if (warp == 1 && threadIdx.x < 32 + 12) asm volatile("prefetch.tensormap [%0];" ::"l"(&p.x[0] + (threadIdx.x - 32)) : "memory");
  __syncthreads();
  if (warp >= 8) {
    asm volatile("setmaxnreg.dec.sync.aligned.u32 40;");
    if (warp == 8) {
      if (elect_one()) {
        const OJob job = get_ojob(cta, attn_producer(p, cta));
        const int epoch = *(volatile int*)&g_epoch[cta];
        *(volatile int*)&g_epoch[cta] = epoch + 1;
        if (job.s0 < job.s1) oproj_producer(p, job, epoch + 1);
      }
    } else {
      const int epoch = __shfl_sync(0xffffffffu, *(volatile int*)&g_epoch[cta], 0);
      attn_helper(p, warp - 9, cta, epoch);
      if (warp == 9) {
        const OJob job = get_ojob(cta, next_item());
        if (job.s0 < job.s1 && elect_one()) oproj_storer(p, job, epoch + 1);
      }
    }
  } else {
    asm volatile("setmaxnreg.inc.sync.aligned.u32 232;");
    if (warp < 4) {
      const OJob job = get_ojob(cta, attn_consumer<0>(cta));
      if (job.s0 < job.s1) oproj_consumer<0>(p, job);
    } else {
      const OJob job = get_ojob(cta, attn_consumer<1>(cta));
      if (job.s0 < job.s1) oproj_consumer<1>(p, job);
    }
  }
}

typedef CUresult (*EncodeFn)(CUtensorMap*, CUtensorMapDataType, cuuint32_t, void*, const cuuint64_t*, const cuuint64_t*, const cuuint32_t*,
                             const cuuint32_t*, CUtensorMapInterleave, CUtensorMapSwizzle, CUtensorMapL2promotion, CUtensorMapFloatOOBfill);

void make3d(EncodeFn enc, CUtensorMap* m, const void* ptr, uint64_t rows, uint64_t cols, uint32_t box_rows, uint32_t box_blocks,
            CUtensorMapL2promotion promo = CU_TENSOR_MAP_L2_PROMOTION_L2_128B) {
  cuuint64_t gd[3] = {64, rows, cols / 64};
  cuuint64_t gs[2] = {cols * 2, 128};
  cuuint32_t bd[3] = {64, box_rows, box_blocks}, es[3] = {1, 1, 1};
  enc(m, CU_TENSOR_MAP_DATA_TYPE_BFLOAT16, 3, (void*)ptr, gd, gs, bd, es, CU_TENSOR_MAP_INTERLEAVE_NONE, CU_TENSOR_MAP_SWIZZLE_128B,
      promo, CU_TENSOR_MAP_FLOAT_OOB_FILL_NONE);
}
void make2d(EncodeFn enc, CUtensorMap* m, const void* ptr, uint64_t rows, uint64_t cols, uint32_t box_rows) {
  cuuint64_t gd[2] = {cols, rows};
  cuuint64_t gs[1] = {cols * 2};
  cuuint32_t bd[2] = {64, box_rows}, es[2] = {1, 1};
  enc(m, CU_TENSOR_MAP_DATA_TYPE_BFLOAT16, 2, (void*)ptr, gd, gs, bd, es, CU_TENSOR_MAP_INTERLEAVE_NONE, CU_TENSOR_MAP_SWIZZLE_128B,
      CU_TENSOR_MAP_L2_PROMOTION_L2_128B, CU_TENSOR_MAP_FLOAT_OOB_FILL_NONE);
}

}

extern "C" void kernel_launch(void* const* d_in, const int* in_sizes, int n_in, void* d_out, int out_size) {
  static EncodeFn enc = nullptr;
  static void* part = nullptr;
  if (!enc) {
    cudaGetSymbolAddress(&part, g_part);
    cudaDriverEntryPointQueryResult qr;
    cudaGetDriverEntryPoint("cuTensorMapEncodeTiled", (void**)&enc, cudaEnableDefault, &qr);
    cudaFuncSetAttribute(fused_kernel, cudaFuncAttributeMaxDynamicSharedMemorySize, SMEM_BYTES);
  }
  Params p;
  for (int s = 0; s < 2; s++) {
    make2d(enc, &p.x[s], d_in[5 * s + 0], NB * SQ, DM, SQ);
    make3d(enc, &p.k[s], d_in[5 * s + 1], (uint64_t)NB * NH * SK, DH, 64, 3);
    make3d(enc, &p.v[s], d_in[5 * s + 2], (uint64_t)NB * NH * SK, DH, 64, 3);
    make3d(enc, &p.wq[s], d_in[5 * s + 3], DM, NH * DH, 64, 3);
    make3d(enc, &p.wo[s], d_in[5 * s + 4], NH * DH, DM, 64, 5);
    p.xp[s] = (const __nv_bfloat16*)d_in[5 * s + 0];
    p.wqp[s] = (const __nv_bfloat16*)d_in[5 * s + 3];
    p.wop[s] = (const __nv_bfloat16*)d_in[5 * s + 4];
    p.kp[s] = (const __nv_bfloat16*)d_in[5 * s + 1];
    p.vp[s] = (const __nv_bfloat16*)d_in[5 * s + 2];
  }
  make2d(enc, &p.out, d_out, NB * SQ, 2 * DM, SQ);
  make2d(enc, &p.part, part, 4 * NB * SQ, DM, 40);
  p.outp = (__nv_bfloat16*)d_out;
  fused_kernel<<<NCTA, 384, SMEM_BYTES>>>(p);
}
```

```cpp
#include <cuda_runtime.h>
#include <cuda_bf16.h>
#include <cuda.h>
#include <stdint.h>

#define DEBUG_TIMEOUT 0

namespace {

constexpr int SQ = 160, DM = 640, NH = 32, SK = 512, DH = 192, NB = 16;
constexpr int NITEMS = 2 * NB * NH;
constexpr int NCTA = 132, N_OCTA = 32, N_ATT = NCTA - N_OCTA;
constexpr int ORING = 192, OFRESH = 800, STEP1 = 53, STEP2 = 58, STEP3 = 62;
constexpr int STAG_G = 4, PERM_G = 4, O_PAIR = 0, STAG_A0 = 15, STAG_SLOPE = 262, PERM_M = 20, PF_N = 32, PF_WAIT = 1500, PF_GAP = 300;
constexpr int OSLOTS = ORING + NITEMS - OFRESH;
#define W1_NG 3
constexpr int A_SLOT = 24576, B_SLOT = 20480, NSLOT = 5;
constexpr int OFF_A = 0;
constexpr int OFF_B = NSLOT * A_SLOT;
constexpr int O_STAGE = 61440, O_AB = 40960, O_NST = 3;
constexpr int OFF_L = OFF_B + NSLOT * B_SLOT;
constexpr int OFF_BAR = OFF_L + 160 * 4;
constexpr int SMEM_BYTES = OFF_BAR + 512 + 512;
constexpr int O_OUT = 2 * O_STAGE;
static_assert(O_OUT + 5 * B_SLOT <= OFF_L, "smem layout");
constexpr uint32_t SB = 1024;
constexpr uint32_t BARS = SB + OFF_BAR;
constexpr uint32_t BAR_FULLA = BARS, BAR_EMPTYA = BARS + 40, BAR_PMID = BARS + 80, BAR_EMPTYB = BARS + 120, BAR_XDONE = BARS + 160,
                   BAR_QH = BARS + 168, BAR_QM = BARS + 96, BAR_PFULL = BARS + 184, BAR_PFREE = BARS + 200, BAR_LFULL = BARS + 216,
                   BAR_OFULL = BARS + 224, BAR_GFULL = BARS + 248, BAR_GEMPTY = BARS + 280, BAR_GOUT = BARS + 328, BAR_GRED = BARS + 368,
                   BAR_FREE = BARS + 240, NEXT_ITEM = BARS + 320;
constexpr int O_ITEM_BYTES = SQ * DH * 2;

struct alignas(64) Params {
  CUtensorMap x[2], wq[2], k[2], v[2], wo[2], out, part;
  __nv_bfloat16* outp;
  const __nv_bfloat16 *xp[2], *wqp[2], *kp[2], *vp[2];
};

__device__ uint4 g_o[(size_t)OSLOTS * O_ITEM_BYTES / 16];
__device__ uint4 g_part[4 * NB * SQ * DM / 8];
__device__ int g_pcnt[4 * N_OCTA];
__device__ int g_ready[NITEMS];
__device__ int g_done[NITEMS];
__device__ unsigned g_ticket;
__device__ int g_epoch[NCTA];

#define TLP(id)
#define TLG(id)
#define TL(id)
#define TL_FLUSH()
__device__ __forceinline__ uint32_t smem_u32(const void* p) { return (uint32_t)__cvta_generic_to_shared(p); }
__device__ __forceinline__ void wg_fence() { asm volatile("wgmma.fence.sync.aligned;" ::: "memory"); }
__device__ __forceinline__ void wg_commit() { asm volatile("wgmma.commit_group.sync.aligned;" ::: "memory"); }
template <int N> __device__ __forceinline__ void wg_wait() { asm volatile("wgmma.wait_group.sync.aligned %0;" ::"n"(N) : "memory"); }
template <int N> __device__ __forceinline__ void reg_fence(float (&d)[N]) {
#pragma unroll
  for (int i = 0; i < N; i++) asm volatile("" : "+f"(d[i])::"memory");
}
template <int N> __device__ __forceinline__ void zero_regs(float (&d)[N]) {
#pragma unroll
  for (int i = 0; i < N; i++) d[i] = 0.f;
}
__device__ __forceinline__ void proxy_fence() { asm volatile("fence.proxy.async.shared::cta;" ::: "memory"); }
__device__ __forceinline__ void mbar_init(uint32_t bar, int cnt) { asm volatile("mbarrier.init.shared::cta.b64 [%0], %1;" ::"r"(bar), "r"(cnt) : "memory"); }
__device__ __forceinline__ void mbar_arrive_if0(uint32_t bar, uint32_t sel) {
  asm volatile("{\n.reg .pred p;\nsetp.eq.u32 p, %1, 0;\n@p mbarrier.arrive.shared::cta.b64 _, [%0];\n}\n" ::"r"(bar), "r"(sel) : "memory");
}
__device__ __forceinline__ void mbar_arrive2_if0(uint32_t bar, uint32_t sel) {
  asm volatile("{\n.reg .pred p;\nsetp.eq.u32 p, %1, 0;\n@p mbarrier.arrive.shared::cta.b64 _, [%0], 2;\n}\n" ::"r"(bar), "r"(sel) : "memory");
}
__device__ __forceinline__ void mbar_expect(uint32_t bar, uint32_t bytes) {
  asm volatile("mbarrier.arrive.expect_tx.shared::cta.b64 _, [%0], %1;" ::"r"(bar), "r"(bytes) : "memory");
}
__device__ __forceinline__ void mbar_wait(int& bud, uint32_t bar, uint32_t parity) {
  asm volatile(
      "{\n.reg .pred p;\n"
      "LW:\n"
      "mbarrier.try_wait.parity.shared::cta.b64 p, [%0], %1;\n"
      "@!p bra LW;\n}\n" ::"r"(bar), "r"(parity) : "memory");
}
constexpr int WAIT_BUDGET = 1 << 22;
__device__ __forceinline__ bool elect_one() {
  uint32_t p;
  asm volatile("{\n.reg .pred p;\nelect.sync _|p, 0xffffffff;\nselp.u32 %0, 1, 0, p;\n}\n" : "=r"(p));
  return p;
}
__device__ __forceinline__ void tma2d(uint32_t dst, const CUtensorMap* m, uint32_t bar, int c0, int c1) {
  asm volatile("cp.async.bulk.tensor.2d.shared::cluster.global.mbarrier::complete_tx::bytes [%0], [%1, {%3, %4}], [%2];"
               ::"r"(dst), "l"(m), "r"(bar), "r"(c0), "r"(c1) : "memory");
}
__device__ __forceinline__ void tma3d(uint32_t dst, const CUtensorMap* m, uint32_t bar, int c0, int c1, int c2) {
  asm volatile("cp.async.bulk.tensor.3d.shared::cluster.global.mbarrier::complete_tx::bytes [%0], [%1, {%3, %4, %5}], [%2];"
               ::"r"(dst), "l"(m), "r"(bar), "r"(c0), "r"(c1), "r"(c2) : "memory");
}
__device__ __forceinline__ void tma3d_hint(uint32_t dst, const CUtensorMap* m, uint32_t bar, int c0, int c1, int c2, uint64_t pol) {
  asm volatile("cp.async.bulk.tensor.3d.shared::cluster.global.mbarrier::complete_tx::bytes.L2::cache_hint [%0], [%1, {%3, %4, %5}], [%2], %6;"
               ::"r"(dst), "l"(m), "r"(bar), "r"(c0), "r"(c1), "r"(c2), "l"(pol) : "memory");
}
__device__ __forceinline__ void tma_store2d(const CUtensorMap* m, uint32_t src, int c0, int c1) {
  asm volatile("cp.async.bulk.tensor.2d.global.shared::cta.bulk_group [%0, {%2, %3}], [%1];" ::"l"(m), "r"(src), "r"(c0), "r"(c1) : "memory");
}
__device__ __forceinline__ void bar_sync(int id, int n) { asm volatile("bar.sync %0, %1;" ::"r"(id), "r"(n) : "memory"); }
__device__ __forceinline__ void bar_arrive(int id, int n) { asm volatile("bar.arrive %0, %1;" ::"r"(id), "r"(n) : "memory"); }
__device__ __forceinline__ float ex2(float x) { float y; asm("ex2.approx.ftz.f32 %0, %1;" : "=f"(y) : "f"(x)); return y; }
__device__ __forceinline__ uint32_t pack2(float lo, float hi) { uint32_t r; asm("cvt.rn.bf16x2.f32 %0, %1, %2;" : "=r"(r) : "f"(hi), "f"(lo)); return r; }
__device__ __forceinline__ void stsm_t(uint32_t a, uint32_t r0, uint32_t r1, uint32_t r2, uint32_t r3) {
  asm volatile("stmatrix.sync.aligned.m8n8.x4.trans.shared.b16 [%0], {%1,%2,%3,%4};" ::"r"(a), "r"(r0), "r"(r1), "r"(r2), "r"(r3) : "memory");
}
__device__ __forceinline__ uint64_t evict_first_policy() {
  uint64_t pol;
  asm volatile("createpolicy.fractional.L2::evict_first.b64 %0, 1.0;" : "=l"(pol));
  return pol;
}
__device__ __forceinline__ void bulk_load_hint(uint32_t dst, const void* src, uint32_t bytes, uint32_t bar, uint64_t pol) {
  asm volatile("cp.async.bulk.shared::cluster.global.mbarrier::complete_tx::bytes.L2::cache_hint [%0], [%1], %2, [%3], %4;"
               ::"r"(dst), "l"(src), "r"(bytes), "r"(bar), "l"(pol) : "memory");
}
__device__ __forceinline__ void flag_wait(int& bud, const int* p, int target) {
  while (true) {
    int v;
    asm volatile("ld.acquire.gpu.global.s32 %0, [%1];" : "=r"(v) : "l"(p) : "memory");
    if (v - target >= 0 || --bud <= 0) break;
    __nanosleep(64);
  }
}
__device__ __forceinline__ uint32_t lo_sw(uint32_t addr) { return (addr >> 4) | (1u << 16); }
__device__ __forceinline__ uint32_t lo_o(uint32_t addr) { return (addr >> 4) | (128u << 16); }
__device__ __forceinline__ uint32_t tid_x() { uint32_t t; asm volatile("mov.u32 %0, %tid.x;" : "=r"(t)); return t; }
__device__ __forceinline__ uint32_t opaque(uint32_t x) { uint32_t y; asm volatile("mov.u32 %0, %1;" : "=r"(y) : "r"(x)); return y; }

template <int TA, int TB, uint32_t OA, uint32_t OB>
__device__ __forceinline__ void mma160(float (&d)[80], uint32_t la, uint32_t lb) {
  asm volatile(
      "{\n.reg .pred p;\n.reg .b32 a, b;\n.reg .b64 da, db;\nsetp.eq.b32 p, 0, 0;\n"
      "add.u32 a, %80, %84;\nadd.u32 b, %81, %85;\nmov.b64 da, {a, 0x40000040};\nmov.b64 db, {b, %86};\n"
      "wgmma.mma_async.sync.aligned.m64n160k16.f32.bf16.bf16 {"
      "%0,%1,%2,%3,%4,%5,%6,%7,%8,%9,%10,%11,%12,%13,%14,%15,%16,%17,%18,%19,%20,%21,%22,%23,%24,%25,%26,%27,%28,%29,%30,%31,%32,%33,%34,%35,%36,"
      "%37,%38,%39,%40,%41,%42,%43,%44,%45,%46,%47,%48,%49,%50,%51,%52,%53,%54,%55,%56,%57,%58,%59,%60,%61,%62,%63,%64,%65,%66,%67,%68,%69,%70,%71,"
      "%72,%73,%74,%75,%76,%77,%78,%79"
      "}, da, db, p, 1, 1, %82, %83;\n}\n"
      :
      "+f"(d[0]),"+f"(d[1]),"+f"(d[2]),"+f"(d[3]),"+f"(d[4]),"+f"(d[5]),"+f"(d[6]),"+f"(d[7]),"+f"(d[8]),"+f"(d[9]),"+f"(d[10]),"+f"(d[11]),
      "+f"(d[12]),"+f"(d[13]),"+f"(d[14]),"+f"(d[15]),"+f"(d[16]),"+f"(d[17]),"+f"(d[18]),"+f"(d[19]),"+f"(d[20]),"+f"(d[21]),"+f"(d[22]),
      "+f"(d[23]),"+f"(d[24]),"+f"(d[25]),"+f"(d[26]),"+f"(d[27]),"+f"(d[28]),"+f"(d[29]),"+f"(d[30]),"+f"(d[31]),"+f"(d[32]),"+f"(d[33]),
      "+f"(d[34]),"+f"(d[35]),"+f"(d[36]),"+f"(d[37]),"+f"(d[38]),"+f"(d[39]),"+f"(d[40]),"+f"(d[41]),"+f"(d[42]),"+f"(d[43]),"+f"(d[44]),
      "+f"(d[45]),"+f"(d[46]),"+f"(d[47]),"+f"(d[48]),"+f"(d[49]),"+f"(d[50]),"+f"(d[51]),"+f"(d[52]),"+f"(d[53]),"+f"(d[54]),"+f"(d[55]),
      "+f"(d[56]),"+f"(d[57]),"+f"(d[58]),"+f"(d[59]),"+f"(d[60]),"+f"(d[61]),"+f"(d[62]),"+f"(d[63]),"+f"(d[64]),"+f"(d[65]),"+f"(d[66]),
      "+f"(d[67]),"+f"(d[68]),"+f"(d[69]),"+f"(d[70]),"+f"(d[71]),"+f"(d[72]),"+f"(d[73]),"+f"(d[74]),"+f"(d[75]),"+f"(d[76]),"+f"(d[77]),
      "+f"(d[78]),"+f"(d[79])
      : "r"(la), "r"(lb), "n"(TA), "n"(TB), "n"(OA >> 4), "n"(OB >> 4), "n"(TB ? 0xC0000010u : 0x40000040u));
}

template <int TA, int TB, uint32_t OA, uint32_t OB>
__device__ __forceinline__ void mma160z(float (&d)[80], uint32_t la, uint32_t lb) {
  asm volatile(
      "{\n.reg .pred p;\n.reg .b32 a, b;\n.reg .b64 da, db;\nsetp.ne.b32 p, 0, 0;\n"
      "add.u32 a, %80, %84;\nadd.u32 b, %81, %85;\nmov.b64 da, {a, 0x40000040};\nmov.b64 db, {b, %86};\n"
      "wgmma.mma_async.sync.aligned.m64n160k16.f32.bf16.bf16 {"
      "%0,%1,%2,%3,%4,%5,%6,%7,%8,%9,%10,%11,%12,%13,%14,%15,%16,%17,%18,%19,%20,%21,%22,%23,%24,%25,%26,%27,%28,%29,%30,%31,%32,%33,%34,%35,%36,"
      "%37,%38,%39,%40,%41,%42,%43,%44,%45,%46,%47,%48,%49,%50,%51,%52,%53,%54,%55,%56,%57,%58,%59,%60,%61,%62,%63,%64,%65,%66,%67,%68,%69,%70,%71,"
      "%72,%73,%74,%75,%76,%77,%78,%79"
      "}, da, db, p, 1, 1, %82, %83;\n}\n"
      :
      "=f"(d[0]),"=f"(d[1]),"=f"(d[2]),"=f"(d[3]),"=f"(d[4]),"=f"(d[5]),"=f"(d[6]),"=f"(d[7]),"=f"(d[8]),"=f"(d[9]),"=f"(d[10]),"=f"(d[11]),
      "=f"(d[12]),"=f"(d[13]),"=f"(d[14]),"=f"(d[15]),"=f"(d[16]),"=f"(d[17]),"=f"(d[18]),"=f"(d[19]),"=f"(d[20]),"=f"(d[21]),"=f"(d[22]),
      "=f"(d[23]),"=f"(d[24]),"=f"(d[25]),"=f"(d[26]),"=f"(d[27]),"=f"(d[28]),"=f"(d[29]),"=f"(d[30]),"=f"(d[31]),"=f"(d[32]),"=f"(d[33]),
      "=f"(d[34]),"=f"(d[35]),"=f"(d[36]),"=f"(d[37]),"=f"(d[38]),"=f"(d[39]),"=f"(d[40]),"=f"(d[41]),"=f"(d[42]),"=f"(d[43]),"=f"(d[44]),
      "=f"(d[45]),"=f"(d[46]),"=f"(d[47]),"=f"(d[48]),"=f"(d[49]),"=f"(d[50]),"=f"(d[51]),"=f"(d[52]),"=f"(d[53]),"=f"(d[54]),"=f"(d[55]),
      "=f"(d[56]),"=f"(d[57]),"=f"(d[58]),"=f"(d[59]),"=f"(d[60]),"=f"(d[61]),"=f"(d[62]),"=f"(d[63]),"=f"(d[64]),"=f"(d[65]),"=f"(d[66]),
      "=f"(d[67]),"=f"(d[68]),"=f"(d[69]),"=f"(d[70]),"=f"(d[71]),"=f"(d[72]),"=f"(d[73]),"=f"(d[74]),"=f"(d[75]),"=f"(d[76]),"=f"(d[77]),
      "=f"(d[78]),"=f"(d[79])
      : "r"(la), "r"(lb), "n"(TA), "n"(TB), "n"(OA >> 4), "n"(OB >> 4), "n"(TB ? 0xC0000010u : 0x40000040u));
}

template <int TA, int TB, uint32_t OA, uint32_t OB>
__device__ __forceinline__ void mma80(float (&d)[40], uint32_t la, uint32_t lb) {
  asm volatile(
      "{\n.reg .pred p;\n.reg .b32 a, b;\n.reg .b64 da, db;\nsetp.eq.b32 p, 0, 0;\n"
      "add.u32 a, %40, %44;\nadd.u32 b, %41, %45;\nmov.b64 da, {a, 0x40000040};\nmov.b64 db, {b, %46};\n"
      "wgmma.mma_async.sync.aligned.m64n80k16.f32.bf16.bf16 {"
      "%0,%1,%2,%3,%4,%5,%6,%7,%8,%9,%10,%11,%12,%13,%14,%15,%16,%17,%18,%19,%20,%21,%22,%23,%24,%25,%26,%27,%28,%29,%30,%31,%32,%33,%34,%35,%36,"
      "%37,%38,%39"
      "}, da, db, p, 1, 1, %42, %43;\n}\n"
      :
      "+f"(d[0]),"+f"(d[1]),"+f"(d[2]),"+f"(d[3]),"+f"(d[4]),"+f"(d[5]),"+f"(d[6]),"+f"(d[7]),"+f"(d[8]),"+f"(d[9]),"+f"(d[10]),"+f"(d[11]),
      "+f"(d[12]),"+f"(d[13]),"+f"(d[14]),"+f"(d[15]),"+f"(d[16]),"+f"(d[17]),"+f"(d[18]),"+f"(d[19]),"+f"(d[20]),"+f"(d[21]),"+f"(d[22]),
      "+f"(d[23]),"+f"(d[24]),"+f"(d[25]),"+f"(d[26]),"+f"(d[27]),"+f"(d[28]),"+f"(d[29]),"+f"(d[30]),"+f"(d[31]),"+f"(d[32]),"+f"(d[33]),
      "+f"(d[34]),"+f"(d[35]),"+f"(d[36]),"+f"(d[37]),"+f"(d[38]),"+f"(d[39])
      : "r"(la), "r"(lb), "n"(TA), "n"(TB), "n"(OA >> 4), "n"(OB >> 4), "n"(TB ? 0xC0000010u : 0x40000040u));
}

template <int TA, int TB, uint32_t OA, uint32_t OB>
__device__ __forceinline__ void mma80z(float (&d)[40], uint32_t la, uint32_t lb) {
  asm volatile(
      "{\n.reg .pred p;\n.reg .b32 a, b;\n.reg .b64 da, db;\nsetp.ne.b32 p, 0, 0;\n"
      "add.u32 a, %40, %44;\nadd.u32 b, %41, %45;\nmov.b64 da, {a, 0x40000040};\nmov.b64 db, {b, %46};\n"
      "wgmma.mma_async.sync.aligned.m64n80k16.f32.bf16.bf16 {"
      "%0,%1,%2,%3,%4,%5,%6,%7,%8,%9,%10,%11,%12,%13,%14,%15,%16,%17,%18,%19,%20,%21,%22,%23,%24,%25,%26,%27,%28,%29,%30,%31,%32,%33,%34,%35,%36,"
      "%37,%38,%39"
      "}, da, db, p, 1, 1, %42, %43;\n}\n"
      :
      "=f"(d[0]),"=f"(d[1]),"=f"(d[2]),"=f"(d[3]),"=f"(d[4]),"=f"(d[5]),"=f"(d[6]),"=f"(d[7]),"=f"(d[8]),"=f"(d[9]),"=f"(d[10]),"=f"(d[11]),
      "=f"(d[12]),"=f"(d[13]),"=f"(d[14]),"=f"(d[15]),"=f"(d[16]),"=f"(d[17]),"=f"(d[18]),"=f"(d[19]),"=f"(d[20]),"=f"(d[21]),"=f"(d[22]),
      "=f"(d[23]),"=f"(d[24]),"=f"(d[25]),"=f"(d[26]),"=f"(d[27]),"=f"(d[28]),"=f"(d[29]),"=f"(d[30]),"=f"(d[31]),"=f"(d[32]),"=f"(d[33]),
      "=f"(d[34]),"=f"(d[35]),"=f"(d[36]),"=f"(d[37]),"=f"(d[38]),"=f"(d[39])
      : "r"(la), "r"(lb), "n"(TA), "n"(TB), "n"(OA >> 4), "n"(OB >> 4), "n"(TB ? 0xC0000010u : 0x40000040u));
}

template <int TA, int TB, uint32_t OA, uint32_t OB>
__device__ __forceinline__ void mma160r(float (&d)[80], uint32_t la, uint32_t lb, int sc) {
  asm volatile(
      "{\n.reg .pred p;\n.reg .b32 a, b;\n.reg .b64 da, db;\nsetp.ne.b32 p, %87, 0;\n"
      "add.u32 a, %80, %84;\nadd.u32 b, %81, %85;\nmov.b64 da, {a, 0x40000040};\nmov.b64 db, {b, %86};\n"
      "wgmma.mma_async.sync.aligned.m64n160k16.f32.bf16.bf16 {"
      "%0,%1,%2,%3,%4,%5,%6,%7,%8,%9,%10,%11,%12,%13,%14,%15,%16,%17,%18,%19,%20,%21,%22,%23,%24,%25,%26,%27,%28,%29,%30,%31,%32,%33,%34,%35,%36,"
      "%37,%38,%39,%40,%41,%42,%43,%44,%45,%46,%47,%48,%49,%50,%51,%52,%53,%54,%55,%56,%57,%58,%59,%60,%61,%62,%63,%64,%65,%66,%67,%68,%69,%70,%71,"
      "%72,%73,%74,%75,%76,%77,%78,%79"
      "}, da, db, p, 1, 1, %82, %83;\n}\n"
      :
      "+f"(d[0]),"+f"(d[1]),"+f"(d[2]),"+f"(d[3]),"+f"(d[4]),"+f"(d[5]),"+f"(d[6]),"+f"(d[7]),"+f"(d[8]),"+f"(d[9]),"+f"(d[10]),"+f"(d[11]),
      "+f"(d[12]),"+f"(d[13]),"+f"(d[14]),"+f"(d[15]),"+f"(d[16]),"+f"(d[17]),"+f"(d[18]),"+f"(d[19]),"+f"(d[20]),"+f"(d[21]),"+f"(d[22]),
      "+f"(d[23]),"+f"(d[24]),"+f"(d[25]),"+f"(d[26]),"+f"(d[27]),"+f"(d[28]),"+f"(d[29]),"+f"(d[30]),"+f"(d[31]),"+f"(d[32]),"+f"(d[33]),
      "+f"(d[34]),"+f"(d[35]),"+f"(d[36]),"+f"(d[37]),"+f"(d[38]),"+f"(d[39]),"+f"(d[40]),"+f"(d[41]),"+f"(d[42]),"+f"(d[43]),"+f"(d[44]),
      "+f"(d[45]),"+f"(d[46]),"+f"(d[47]),"+f"(d[48]),"+f"(d[49]),"+f"(d[50]),"+f"(d[51]),"+f"(d[52]),"+f"(d[53]),"+f"(d[54]),"+f"(d[55]),
      "+f"(d[56]),"+f"(d[57]),"+f"(d[58]),"+f"(d[59]),"+f"(d[60]),"+f"(d[61]),"+f"(d[62]),"+f"(d[63]),"+f"(d[64]),"+f"(d[65]),"+f"(d[66]),
      "+f"(d[67]),"+f"(d[68]),"+f"(d[69]),"+f"(d[70]),"+f"(d[71]),"+f"(d[72]),"+f"(d[73]),"+f"(d[74]),"+f"(d[75]),"+f"(d[76]),"+f"(d[77]),
      "+f"(d[78]),"+f"(d[79])
      : "r"(la), "r"(lb), "n"(TA), "n"(TB), "n"(OA >> 4), "n"(OB >> 4), "n"(TB ? 0xC0000010u : 0x40000040u), "r"(sc));
}

template <int TA, int TB, uint32_t OA, uint32_t OB>
__device__ __forceinline__ void mma80r(float (&d)[40], uint32_t la, uint32_t lb, int sc) {
  asm volatile(
      "{\n.reg .pred p;\n.reg .b32 a, b;\n.reg .b64 da, db;\nsetp.ne.b32 p, %47, 0;\n"
      "add.u32 a, %40, %44;\nadd.u32 b, %41, %45;\nmov.b64 da, {a, 0x40000040};\nmov.b64 db, {b, %46};\n"
      "wgmma.mma_async.sync.aligned.m64n80k16.f32.bf16.bf16 {"
      "%0,%1,%2,%3,%4,%5,%6,%7,%8,%9,%10,%11,%12,%13,%14,%15,%16,%17,%18,%19,%20,%21,%22,%23,%24,%25,%26,%27,%28,%29,%30,%31,%32,%33,%34,%35,%36,"
      "%37,%38,%39"
      "}, da, db, p, 1, 1, %42, %43;\n}\n"
      :
      "+f"(d[0]),"+f"(d[1]),"+f"(d[2]),"+f"(d[3]),"+f"(d[4]),"+f"(d[5]),"+f"(d[6]),"+f"(d[7]),"+f"(d[8]),"+f"(d[9]),"+f"(d[10]),"+f"(d[11]),
      "+f"(d[12]),"+f"(d[13]),"+f"(d[14]),"+f"(d[15]),"+f"(d[16]),"+f"(d[17]),"+f"(d[18]),"+f"(d[19]),"+f"(d[20]),"+f"(d[21]),"+f"(d[22]),
      "+f"(d[23]),"+f"(d[24]),"+f"(d[25]),"+f"(d[26]),"+f"(d[27]),"+f"(d[28]),"+f"(d[29]),"+f"(d[30]),"+f"(d[31]),"+f"(d[32]),"+f"(d[33]),
      "+f"(d[34]),"+f"(d[35]),"+f"(d[36]),"+f"(d[37]),"+f"(d[38]),"+f"(d[39])
      : "r"(la), "r"(lb), "n"(TA), "n"(TB), "n"(OA >> 4), "n"(OB >> 4), "n"(TB ? 0xC0000010u : 0x40000040u), "r"(sc));
}

struct Ring { uint32_t s0, ph0; };
__device__ __forceinline__ void ring_pos(const Ring& r, int i, uint32_t& slot, uint32_t& ph) {
  uint32_t s = opaque(r.s0) + (i % NSLOT);
  uint32_t wrap = s >= NSLOT;
  slot = s - (wrap ? NSLOT : 0);
  ph = r.ph0 ^ ((i / NSLOT) & 1) ^ wrap;
}
__device__ __forceinline__ void ring_advance(Ring& r, int n) {
  uint32_t s, p;
  ring_pos(r, n, s, p);
  r.s0 = s; r.ph0 = p;
}
__host__ __device__ constexpr int idxK(int j) { return j == 0 ? 10 : 9 + 2 * j; }
__host__ __device__ constexpr int idxV(int j) { return j == 7 ? 25 : 12 + 2 * j; }
__host__ __device__ constexpr int xs(int c) { return c % NSLOT; }

__device__ __forceinline__ int start_delay(int cta) {
  return max(0, ((cta - N_OCTA) | (STAG_G - 1)) - STAG_A0) * STAG_SLOPE;
}
__device__ __forceinline__ char* o_slot(int item) {
  return (char*)g_o + (size_t)(item < OFRESH ? item % ORING : item - OFRESH + ORING) * O_ITEM_BYTES;
}
__device__ __forceinline__ int next_item(uint32_t a = NEXT_ITEM) {
  int v;
  asm volatile("ld.shared.s32 %0, [%1];" : "=r"(v) : "r"(a) : "memory");
  return __shfl_sync(0xffffffffu, v, 0);
}

template <int W, bool ACC>
__device__ __forceinline__ void mma_main(float (&d)[80], uint32_t aaddr, uint32_t baddr) {
  const uint32_t la = lo_sw(aaddr), lb = lo_sw(baddr);
  if (ACC) mma160<1, 0, W * 16384, 0>(d, la, lb); else mma160z<1, 0, W * 16384, 0>(d, la, lb);
  mma160<1, 0, W * 16384 + 1 * 2048, 1 * 32>(d, la, lb);
  mma160<1, 0, W * 16384 + 2 * 2048, 2 * 32>(d, la, lb);
  mma160<1, 0, W * 16384 + 3 * 2048, 3 * 32>(d, la, lb);
}
template <int W, bool ACC>
__device__ __forceinline__ void mma_mid(float (&d)[40], uint32_t aaddr, uint32_t baddr) {
  const uint32_t la = lo_sw(aaddr), lb = lo_sw(baddr);
  if (ACC) mma80<1, 0, 8192, W * 10240>(d, la, lb); else mma80z<1, 0, 8192, W * 10240>(d, la, lb);
  mma80<1, 0, 8192 + 1 * 2048, W * 10240 + 1 * 32>(d, la, lb);
  mma80<1, 0, 8192 + 2 * 2048, W * 10240 + 2 * 32>(d, la, lb);
  mma80<1, 0, 8192 + 3 * 2048, W * 10240 + 3 * 32>(d, la, lb);
}
template <int W, bool ACC>
__device__ __forceinline__ void mma_both(float (&dm)[80], float (&dh)[40], uint32_t aaddr, uint32_t baddr) {
  mma_mid<W, ACC>(dh, aaddr, baddr);
  mma_main<W, ACC>(dm, aaddr, baddr);
}
template <int KB, bool ACC>
__device__ __forceinline__ void s_mma(float (&sacc)[80], uint32_t kaddr) {
  const uint32_t la = lo_sw(kaddr), lb = lo_sw(SB + OFF_B);
  if (ACC) mma160<0, 0, KB * 8192, KB * B_SLOT>(sacc, la, lb); else mma160z<0, 0, KB * 8192, KB * B_SLOT>(sacc, la, lb);
  mma160<0, 0, KB * 8192 + 32, KB * B_SLOT + 32>(sacc, la, lb);
  mma160<0, 0, KB * 8192 + 64, KB * B_SLOT + 64>(sacc, la, lb);
  mma160<0, 0, KB * 8192 + 96, KB * B_SLOT + 96>(sacc, la, lb);
}
template <int N>
__device__ __forceinline__ void store_scaled(uint32_t addr, const float (&d)[N], float sc) {
#pragma unroll
  for (int J = 0; J < N / 8; J++)
    stsm_t(addr + J * 2048, pack2(d[8 * J] * sc, d[8 * J + 1] * sc), pack2(d[8 * J + 2] * sc, d[8 * J + 3] * sc),
           pack2(d[8 * J + 4] * sc, d[8 * J + 5] * sc), pack2(d[8 * J + 6] * sc, d[8 * J + 7] * sc));
}
__device__ __forceinline__ float4 lds_f4(uint32_t a) {
  float4 v;
  asm volatile("ld.shared.v4.f32 {%0,%1,%2,%3}, [%4];" : "=f"(v.x), "=f"(v.y), "=f"(v.z), "=f"(v.w) : "r"(a) : "memory");
  return v;
}
__device__ __forceinline__ void norm_pack(uint32_t* p, const float* d, const float4& i) {
  p[0] = pack2(d[0] * i.x, d[1] * i.y); p[1] = pack2(d[4] * i.z, d[5] * i.w);
  p[2] = pack2(d[2] * i.x, d[3] * i.y); p[3] = pack2(d[6] * i.z, d[7] * i.w);
  asm volatile("" : "+r"(p[0]), "+r"(p[1]), "+r"(p[2]), "+r"(p[3])::"memory");
}
template <int W>
__device__ __forceinline__ void pack_first(uint32_t (&pk)[60], const float (&om)[80], const float (&oh)[40], uint32_t laddr) {
  float4 n0 = lds_f4(laddr + W * 80), n1 = lds_f4(laddr + W * 80 + 16);
#pragma unroll
  for (int J = 0; J < 5; J++) {
    const float4 i = n0;
    n0 = n1;
    if (J + 2 < 5) n1 = lds_f4(laddr + W * 80 + (J + 2) * 16);
    norm_pack(&pk[20 + 4 * J], &om[8 * (5 * W + J)], i);
    norm_pack(&pk[4 * J], &oh[8 * J], i);
  }
}
template <int W, int J0, int J1>
__device__ __forceinline__ void pack_second(uint32_t (&pk)[60], const float (&om)[80], uint32_t laddr) {
  float4 n[J1 - J0];
#pragma unroll
  for (int J = J0; J < J1; J++) n[J - J0] = lds_f4(laddr + (1 - W) * 80 + J * 16);
#pragma unroll
  for (int J = J0; J < J1; J++) norm_pack(&pk[40 + 4 * J], &om[8 * (5 * (1 - W) + J)], n[J - J0]);
}
__device__ __forceinline__ char* o_ptr(int item) {
  const uint32_t t = tid_x();
  return o_slot(item) + ((t & 96) * 16 + (t & 28) * 8 + ((((t >> 1) ^ (t >> 4)) & 1) << 4) + (t & 1) * 8);
}
template <int W, int G0, int G1>
__device__ __forceinline__ void store_groups(char* op, const uint32_t (&pk)[60], uint32_t on) {
#pragma unroll
  for (int G = G0; G < G1; G++) {
    const int off = (G < 5 ? 1 : 2 * W) * B_SLOT + (5 * (G < 10 ? W : 1 - W) + G % 5) * 2048;
    asm volatile("{\n.reg .pred p;\nsetp.ne.u32 p, %5, 0;\n@p st.global.v2.b32 [%0], {%1, %2};\n@p st.global.v2.b32 [%0+256], {%3, %4};\n}\n"
                 ::"l"(op + off), "r"(pk[4 * G]), "r"(pk[4 * G + 1]), "r"(pk[4 * G + 2]), "r"(pk[4 * G + 3]), "r"(on) : "memory");
  }
}
__device__ __forceinline__ void publish_generic(uint32_t bar, int lane) {
  __syncwarp();
  mbar_arrive_if0(bar, lane);
}
__device__ __forceinline__ void publish(uint32_t bar, int lane) {
  proxy_fence();
  __syncwarp();
  mbar_arrive_if0(bar, lane);
}

#define A_ADDR(s) (SB + OFF_A + (s) * A_SLOT)
#define B_ADDR(s) (SB + OFF_B + (s) * B_SLOT)
#define WAIT_CHUNK(c, ro, sA)                \
  uint32_t sA;                               \
  {                                          \
    uint32_t pA_;                            \
    ring_pos(ring, (ro) + (c), sA, pA_);     \
    mbar_wait(bud, BAR_FULLA + sA * 8, pA_); \
  }
#define RELEASE_CHUNK(c, sA)                                  \
  mbar_arrive_if0(BAR_EMPTYA + (sA) * 8, tid);                \
  if ((c) < NSLOT) mbar_arrive_if0(BAR_EMPTYB + xs(c) * 8, tid);

template <int W>
__device__ __forceinline__ int attn_consumer(int item) {
  int bud = WAIT_BUDGET;
  const int tid = threadIdx.x & 127, lane = tid & 31, warp = tid >> 5;
  const uint32_t st_off = ((lane & 7) + 8 * (lane >> 4)) * 128 + (((2 * warp + ((lane >> 3) & 1)) ^ (lane & 7)) << 4);
  const uint32_t laddr = SB + OFF_L + (lane & 3) * 160;
  float om[80], oh[40], sacc[80];
  uint32_t pk[60];
#pragma unroll
  for (int i = 0; i < 40; i++) pk[i] = 0;
  zero_regs(om);
  Ring ring{0u, 0u};
  uint32_t par = 0;
  int prev = 0;
  const float qscale = 0.07216878364870322f * 1.4426950408889634f;
  constexpr uint32_t pown = B_ADDR(3 + W), poth = B_ADDR(4 - W);
  TL(0); TLG(62);
  {
    WAIT_CHUNK(0, 0, s0)
    wg_fence();
    mma_both<W, false>(sacc, oh, A_ADDR(s0), B_ADDR(xs(0)));
    wg_commit();
    WAIT_CHUNK(1, 0, s1)
    wg_fence();
    mma_both<W, true>(sacc, oh, A_ADDR(s1), B_ADDR(xs(1)));
    wg_commit();
    wg_wait<1>();
    RELEASE_CHUNK(0, s0)
  }
#pragma unroll 1
  for (int it = 0;; it++) {
    char* op = o_ptr(prev);
#pragma unroll
    for (int c = 2; c < 8 - W; c++) {
      WAIT_CHUNK(c, 0, sA)
      TL(40 + c);
      wg_fence();
      mma_both<W, true>(sacc, oh, A_ADDR(sA), B_ADDR(xs(c)));
      wg_commit();
      wg_wait<1>();
      uint32_t sP, pP;
      ring_pos(ring, c - 1, sP, pP);
      RELEASE_CHUNK(c - 1, sP)
      constexpr int NG = W == 0 ? 3 : W1_NG;
      if (c == 2) { pack_second<W, 0, 1>(pk, om, laddr); store_groups<W, 0 * NG, 1 * NG>(op, pk, it); }
      if (c == 3) { pack_second<W, 1, 2>(pk, om, laddr); store_groups<W, 1 * NG, 2 * NG>(op, pk, it); }
      if (c == 4) { pack_second<W, 2, 3>(pk, om, laddr); store_groups<W, 2 * NG, 3 * NG>(op, pk, it); }
      if (c == 5) { pack_second<W, 3, 4>(pk, om, laddr); store_groups<W, 3 * NG, 4 * NG>(op, pk, it); }
      if (c == 6) {
        pack_second<W, 4, 5>(pk, om, laddr);
        if (W == 1) {
          wg_wait<0>();
          RELEASE_CHUNK(6, sA)
          mbar_arrive_if0(BAR_XDONE, tid);
        }
        store_groups<W, 4 * NG, 15>(op, pk, it);
        __syncwarp();
        mbar_arrive_if0(BAR_OFULL, lane | (it == 0));
      }
    }
    uint32_t sK0, pK0, s7, p7;
    ring_pos(ring, idxK(W), sK0, pK0);
    ring_pos(ring, 7, s7, p7);
    if (W == 1) mbar_wait(bud, BAR_FULLA + s7 * 8, p7);
    WAIT_CHUNK(8, 0, s8)
    WAIT_CHUNK(9, 0, s9)
    TL(48);
    if (W == 0) {
      wg_fence();
      mma_mid<W, true>(oh, A_ADDR(s8), B_ADDR(xs(8)));
      mma_mid<W, true>(oh, A_ADDR(s9), B_ADDR(xs(9)));
      wg_commit();
      wg_wait<1>();
      RELEASE_CHUNK(7, s7)
      wg_fence();
      mma_main<W, true>(sacc, A_ADDR(s8), B_ADDR(xs(8)));
      mma_main<W, true>(sacc, A_ADDR(s9), B_ADDR(xs(9)));
      wg_commit();
      bar_arrive(5, 256);
      TL(49);
      wg_wait<1>();
      reg_fence(oh);
      mbar_wait(bud, BAR_XDONE, par);
      store_scaled(B_ADDR(1) + st_off, oh, qscale);
    } else {
      bar_sync(5, 256);
      wg_fence();
      mma_mid<W, true>(oh, A_ADDR(s7), B_ADDR(xs(7)));
      mma_mid<W, true>(oh, A_ADDR(s8), B_ADDR(xs(8)));
      mma_mid<W, true>(oh, A_ADDR(s9), B_ADDR(xs(9)));
      wg_commit();
      mma_main<W, true>(sacc, A_ADDR(s7), B_ADDR(xs(7)));
      wg_commit();
      mma_main<W, true>(sacc, A_ADDR(s8), B_ADDR(xs(8)));
      wg_commit();
      wg_wait<2>();
      reg_fence(oh);
      store_scaled(B_ADDR(1) + 10240 + st_off, oh, qscale);
      wg_fence();
      mma_main<W, true>(sacc, A_ADDR(s9), B_ADDR(xs(9)));
      wg_commit();
      bar_arrive(8, 256);
      TL(49);
      wg_wait<2>();
      RELEASE_CHUNK(7, s7)
      publish(BAR_QH, lane);
    }
    wg_wait<0>();
    reg_fence(sacc);
    TL(1);
    RELEASE_CHUNK(8, s8)
    RELEASE_CHUNK(9, s9)
    store_scaled(B_ADDR(2 * W) + st_off, sacc, qscale);
    if (W == 1) publish(BAR_QM, lane); else proxy_fence();
    TL(2);
    uint32_t sK = sK0, sV1 = 0;
    if (W == 0) {
      zero_regs(om); zero_regs(oh);
      reg_fence(om); reg_fence(oh);
      mbar_wait(bud, BAR_FULLA + sK0 * 8, pK0);
      bar_sync(8, 256);
      wg_fence();
      s_mma<0, false>(sacc, A_ADDR(sK));
      mbar_wait(bud, BAR_QH, par);
      TL(3);
      wg_fence();
      s_mma<1, true>(sacc, A_ADDR(sK));
      mbar_wait(bud, BAR_QM, par);
      TL(5);
      wg_fence();
      s_mma<2, true>(sacc, A_ADDR(sK));
      wg_commit();
      wg_commit();
      bar_arrive(2, 256);
    } else {
      uint32_t pV1;
      ring_pos(ring, idxV(0), sV1, pV1);
      mbar_wait(bud, BAR_FULLA + sK * 8, pK0);
      bar_sync(2, 256);
      wg_fence();
      s_mma<0, false>(sacc, A_ADDR(sK));
      s_mma<1, true>(sacc, A_ADDR(sK));
      s_mma<2, true>(sacc, A_ADDR(sK));
      wg_commit();
      TL(6);
      mbar_wait(bud, BAR_FULLA + sV1 * 8, pV1);
      mbar_wait(bud, BAR_PFULL, 0);
      TL(7);
      wg_fence();
      mma_both<W, false>(om, oh, A_ADDR(sV1), poth);
      wg_commit();
      bar_arrive(1, 256);
    }
    Ring rv;
    ring_pos(ring, idxV(W), rv.s0, rv.ph0);
#pragma unroll 1
    for (int jj = 0;; jj++) {
      wg_wait<1>();
      reg_fence(sacc);
      TL(8 + jj * 7);
      mbar_arrive2_if0(BAR_EMPTYA + sK * 8, tid);
      mbar_arrive_if0(BAR_EMPTYB + tid * 8, (tid >= 3) | (jj != 3));
#pragma unroll
      for (int J = 0; J < 10; J++) {
        stsm_t(pown + st_off + J * 2048, pack2(ex2(sacc[8 * J]), ex2(sacc[8 * J + 1])), pack2(ex2(sacc[8 * J + 2]), ex2(sacc[8 * J + 3])),
               pack2(ex2(sacc[8 * J + 4]), ex2(sacc[8 * J + 5])), pack2(ex2(sacc[8 * J + 6]), ex2(sacc[8 * J + 7])));
        if (W == 1 && (J == 2 || J == 5)) publish_generic(BAR_PMID + (J / 3) * 8, lane | (jj != 3));
        if (J == 4) {
          wg_wait<0>();
          mbar_arrive_if0(BAR_EMPTYA + sV1 * 8, tid | (W == 0 && jj == 0));
        }
      }
      publish(BAR_PFULL + W * 8, lane);
      TL(10 + jj * 7);
      if (jj == 3) break;
      uint32_t pK, pV1;
      ring_pos(rv, 1, sK, pK);
      ring_pos(rv, 2, sV1, pV1);
      mbar_wait(bud, BAR_FULLA + rv.s0 * 8, rv.ph0);
      bar_sync(1 + W, 256);
      wg_fence();
      mma_both<W, true>(om, oh, A_ADDR(rv.s0), pown);
      wg_commit();
      mbar_wait(bud, BAR_FULLA + sK * 8, pK);
      TL(11 + jj * 7);
      wg_fence();
      s_mma<0, false>(sacc, A_ADDR(sK));
      s_mma<1, true>(sacc, A_ADDR(sK));
      wg_commit();
      wg_wait<1>();
      mbar_arrive_if0(BAR_EMPTYA + rv.s0 * 8, tid);
      wg_fence();
      s_mma<2, true>(sacc, A_ADDR(sK));
      wg_commit();
      TL(13 + jj * 7);
      mbar_wait(bud, BAR_FULLA + sV1 * 8, pV1);
      mbar_wait(bud, BAR_PFREE + W * 8, jj & 1);
      mbar_wait(bud, BAR_PFULL + (1 - W) * 8, (jj + W) & 1);
      TL(14 + jj * 7);
      wg_fence();
      mma_both<W, true>(om, oh, A_ADDR(sV1), poth);
      wg_commit();
      bar_arrive(2 - W, 256);
      ring_advance(rv, 4);
    }
    uint32_t sV7, pV7;
    ring_pos(ring, idxV(7), sV7, pV7);
    prev = item;
    if (W == 1 && !DEBUG_TIMEOUT) item = next_item();
    if (W == 0) {
      uint32_t sV6, pV6;
      ring_pos(ring, idxV(6), sV6, pV6);
      mbar_wait(bud, BAR_FULLA + sV6 * 8, pV6);
      bar_sync(1, 256);
      wg_fence();
      mma_both<0, true>(om, oh, A_ADDR(sV6), pown);
      wg_commit();
      mbar_wait(bud, BAR_FULLA + sV7 * 8, pV7);
      wg_wait<0>();
      mbar_arrive_if0(BAR_EMPTYA + sV6 * 8, tid);
      mbar_wait(bud, BAR_PFULL + 8, 1);
      wg_fence();
      mma_both<0, true>(om, oh, A_ADDR(sV7), poth);
      wg_commit();
      bar_arrive(6, 256);
    } else {
      mbar_wait(bud, BAR_FULLA + sV7 * 8, pV7);
      bar_sync(6, 256);
    }
    TL(32);
    if (DEBUG_TIMEOUT) item = next_item(NEXT_ITEM + 4);
    else if (W == 0) item = next_item();
    if (item >= NITEMS) {
      if (W == 1) {
        wg_fence();
        mma_both<1, true>(om, oh, A_ADDR(sV7), pown);
        wg_commit();
      }
      wg_wait<0>();
      reg_fence(om); reg_fence(oh);
      TL(33);
      mbar_wait(bud, BAR_LFULL, par);
      mbar_arrive_if0(BAR_FREE, tid);
      TL(34);
      pack_first<W>(pk, om, oh, laddr);
      op = o_ptr(prev);
      store_groups<W, 0, 10>(op, pk, 1);
      pack_second<W, 0, 5>(pk, om, laddr);
      store_groups<W, 10, 15>(op, pk, 1);
      publish_generic(BAR_OFULL, lane);
      TL(35); TLG(63);
      TL_FLUSH();
      return item;
    }
    {
      if (W == 1) {
        wg_fence();
        mma_both<1, true>(om, oh, A_ADDR(sV7), pown);
        wg_commit();
      }
      WAIT_CHUNK(0, 26, s0)
      WAIT_CHUNK(1, 26, s1)
      if (W == 0) {
        wg_wait<0>();
        reg_fence(om); reg_fence(oh);
        TL(33);
        wg_fence();
        mma_main<W, false>(sacc, A_ADDR(s0), B_ADDR(xs(0)));
        wg_commit();
      } else {
        wg_fence();
        mma_main<W, false>(sacc, A_ADDR(s0), B_ADDR(xs(0)));
        mma_main<W, true>(sacc, A_ADDR(s1), B_ADDR(xs(1)));
        wg_commit();
        wg_wait<1>();
        reg_fence(om); reg_fence(oh);
        TL(33);
      }
      mbar_arrive_if0(BAR_EMPTYA + sV7 * 8, tid);
      mbar_wait(bud, BAR_LFULL, par);
      mbar_arrive_if0(BAR_EMPTYB + 24 + tid * 8, tid >= 2);
      TL(34);
      pack_first<W>(pk, om, oh, laddr);
      TL(36);
      wg_fence();
      mma_mid<W, false>(oh, A_ADDR(s0), B_ADDR(xs(0)));
      wg_commit();
      mma_mid<W, true>(oh, A_ADDR(s1), B_ADDR(xs(1)));
      if (W == 0) mma_main<W, true>(sacc, A_ADDR(s1), B_ADDR(xs(1)));
      wg_commit();
      TL(37);
      wg_wait<1>();
      RELEASE_CHUNK(0, s0)
      TL(35); TLG(63);
    }
    TL_FLUSH();
    TL(0); TLG(62);
    ring_advance(ring, 26);
    par ^= 1;
  }
}

__device__ __forceinline__ uint4 lds128(uint32_t a) {
  uint4 v;
  asm volatile("ld.shared.v4.b32 {%0,%1,%2,%3}, [%4];" : "=r"(v.x), "=r"(v.y), "=r"(v.z), "=r"(v.w) : "r"(a) : "memory");
  return v;
}
__device__ __forceinline__ void acc2(float& s, float& t, uint32_t w) {
  s += __uint_as_float(w << 16);
  t += __uint_as_float(w & 0xffff0000u);
}
__device__ __forceinline__ uint32_t badd2(uint32_t a, uint32_t b) { uint32_t r; asm("add.rn.bf16x2 %0, %1, %2;" : "=r"(r) : "r"(a), "r"(b)); return r; }
__device__ __forceinline__ void sum_unit(float& acc, uint32_t pb) {
  const uint4 v0 = lds128(pb), v1 = lds128(pb ^ 32), v2 = lds128(pb ^ 64), v3 = lds128(pb ^ 96);
  const uint32_t w0 = badd2(v0.x, v0.y), w1 = badd2(v0.z, v0.w);
  float s0 = acc + __uint_as_float(w0 << 16), t0 = __uint_as_float(w0 & 0xffff0000u);
  float s1 = __uint_as_float(w1 << 16), t1 = __uint_as_float(w1 & 0xffff0000u);
  acc2(s0, t0, badd2(v1.x, v1.y)); acc2(s1, t1, badd2(v1.z, v1.w));
  acc2(s0, t0, badd2(v2.x, v2.y)); acc2(s1, t1, badd2(v2.z, v2.w));
  acc2(s0, t0, badd2(v3.x, v3.y)); acc2(s1, t1, badd2(v3.z, v3.w));
  acc = (s0 + t0) + (s1 + t1);
}
__device__ __forceinline__ float bf_lo(uint32_t w) { return __uint_as_float(w << 16); }
__device__ __forceinline__ float bf_hi(uint32_t w) { return __uint_as_float(w & 0xffff0000u); }
__device__ __forceinline__ float bf_rn(float x) { return __bfloat162float(__float2bfloat16(x)); }
__device__ __forceinline__ void slow_item(const Params& p, int item, int hw) {
  const int blk = item >> 9, h = (item >> 4) & 31, b = item & 15;
#pragma unroll 1
  for (int n = hw; n < SQ; n += 3) {
    float q[6] = {0.f, 0.f, 0.f, 0.f, 0.f, 0.f};
    {
      const uint32_t* xr = (const uint32_t*)(p.xp[blk] + (size_t)(b * SQ + n) * DM);
      const uint32_t* wq = (const uint32_t*)(p.wqp[blk] + h * DH) + (tid_x() & 31);
#pragma unroll 2
      for (int k = 0; k < DM / 2; k++) {
        const uint32_t xv = xr[k];
#pragma unroll
        for (int i = 0; i < 3; i++) {
          const uint32_t w0 = wq[i * 32], w1 = wq[NH * DH / 2 + i * 32];
          q[2 * i] = fmaf(bf_lo(xv), bf_lo(w0), fmaf(bf_hi(xv), bf_lo(w1), q[2 * i]));
          q[2 * i + 1] = fmaf(bf_lo(xv), bf_hi(w0), fmaf(bf_hi(xv), bf_hi(w1), q[2 * i + 1]));
        }
        wq += NH * DH;
      }
    }
    const uint32_t q0 = pack2(q[0], q[1]), q1 = pack2(q[2], q[3]), q2 = pack2(q[4], q[5]);
    float o[6] = {0.f, 0.f, 0.f, 0.f, 0.f, 0.f}, m = -INFINITY, l = 0.f;
    const uint32_t* kg = (const uint32_t*)(p.kp[blk] + (size_t)(b * NH + h) * SK * DH) + (tid_x() & 31);
    const uint32_t* vg = (const uint32_t*)(p.vp[blk] + (size_t)(b * NH + h) * SK * DH) + (tid_x() & 31);
#pragma unroll 1
    for (int k = 0; k < SK; k++) {
      const uint32_t k0 = kg[0], k1 = kg[32], k2 = kg[64], v0 = vg[0], v1 = vg[32], v2 = vg[64];
      kg += DH / 2; vg += DH / 2;
      float sc = fmaf(bf_lo(q0), bf_lo(k0), bf_hi(q0) * bf_hi(k0));
      sc = fmaf(bf_lo(q1), bf_lo(k1), fmaf(bf_hi(q1), bf_hi(k1), sc));
      sc = fmaf(bf_lo(q2), bf_lo(k2), fmaf(bf_hi(q2), bf_hi(k2), sc));
#pragma unroll
      for (int d = 16; d; d >>= 1) sc += __shfl_xor_sync(0xffffffffu, sc, d);
      sc = bf_rn(bf_rn(sc) * 0.07216878364870322f);
      const float mn = fmaxf(m, sc), a = ex2((m - mn) * 1.4426950408889634f), pr = ex2((sc - mn) * 1.4426950408889634f);
      m = mn;
      l = fmaf(l, a, pr);
      o[0] = fmaf(o[0], a, pr * bf_lo(v0)); o[1] = fmaf(o[1], a, pr * bf_hi(v0));
      o[2] = fmaf(o[2], a, pr * bf_lo(v1)); o[3] = fmaf(o[3], a, pr * bf_hi(v1));
      o[4] = fmaf(o[4], a, pr * bf_lo(v2)); o[5] = fmaf(o[5], a, pr * bf_hi(v2));
    }
    float inv;
    asm("rcp.approx.ftz.f32 %0, %1;" : "=f"(inv) : "f"(l));
    const int lane = tid_x() & 31;
    const int r = n & 15, c = 4 * ((r & 7) >> 1) + 2 * (r >> 3) + (r & 1);
    char* on = o_slot(item) + (lane >> 2) * 256 + (lane & 3) * 64 + (n >> 4) * 2048 +
               (((c >> 3) ^ ((lane >> 1) & 1)) << 4) + (c & 7) * 2;
#pragma unroll
    for (int i = 0; i < 3; i++) {
      *(__nv_bfloat16*)(on + i * B_SLOT) = __float2bfloat16(o[2 * i] * inv);
      *(__nv_bfloat16*)(on + i * B_SLOT + 32) = __float2bfloat16(o[2 * i + 1] * inv);
    }
  }
}
__device__ __forceinline__ void attn_helper(const Params& p, int hw, int item, int epoch) {
  int bud = WAIT_BUDGET;
  if (item < PF_N && hw < 2) {
    const char* g = (const char*)(hw ? p.vp[0] : p.kp[0]) + (size_t)(((item & 15) * NH + (item >> 4)) * SK) * DH * 2;
    const long long t0 = clock64();
#pragma unroll 1
    for (int i = 0; i < 32; i++) {
      while (clock64() - t0 < PF_WAIT + i * PF_GAP) __nanosleep(50);
      for (int k = 0; k < 6; k++) asm volatile("prefetch.global.L2 [%0];" ::"l"(g + i * 6144 + k * 1024 + (tid_x() & 31) * 32));
      __syncwarp();
    }
  }
#pragma unroll 1
  for (int it = 0; item < NITEMS; it++) {
    const uint32_t par = it & 1;
    int lane = tid_x() & 31;
    const int r = lane >> 1;
    const uint32_t a0 = B_ADDR(3) + (16 * hw + r) * 128 + (lane & 1) * 16 + ((r & 3) << 5);
    float acc[4] = {0.f, 0.f, 0.f, 0.f};
#pragma unroll 1
    for (int j = 0; j < 8; j++) {
      const uint32_t pb = a0 + (j & 1) * B_SLOT, bfull = BAR_PFULL + (j & 1) * 8, pfull = (j >> 1) & 1;
      mbar_wait(bud, j == 7 ? BAR_PMID : bfull, j == 7 ? par : pfull);
      sum_unit(acc[0], pb);
      if (j == 7) mbar_wait(bud, BAR_PMID + 8, par);
      sum_unit(acc[1], pb + 6144);
      if (j == 7) mbar_wait(bud, bfull, pfull);
      sum_unit(acc[2], pb + 2 * 6144);
      if (hw == 0) sum_unit(acc[3], pb + 3 * 6144);
      __syncwarp();
      mbar_arrive_if0(BAR_PFREE + (j & 1) * 8, lane);
      if (j == 5 && hw == 2) {
        if (lane == 0) TLP(60);
        if (item >= ORING && item < OFRESH) flag_wait(bud, &g_done[item - ORING], (epoch + 1) * 2);
        if (lane == 0) TLP(61);
      }
    }
    bool bad = false;
    const uint32_t la = SB + OFF_L + (((r & 7) >> 1) * 40 + 2 * (r >> 3) + (r & 1) + 4 * hw) * 4;
#pragma unroll
    for (int u = 0; u < 4; u++) {
      const float l = acc[u] + __shfl_xor_sync(0xffffffffu, acc[u], 1);
      if (u < 3 || hw == 0) {
        bad |= !(l >= 8.8817841970012523e-16f && l <= 1.125899906842624e15f);
        float inv;
        asm("rcp.approx.ftz.f32 %0, %1;" : "=f"(inv) : "f"(l));
        asm volatile("st.shared.f32 [%0], %1;" ::"r"(la + u * 48), "f"(inv) : "memory");
      }
    }
    publish_generic(BAR_LFULL, lane);
    if (lane == 0) TLP(40 + hw * 4);
    uint32_t anybad;
    asm volatile("{\n.reg .pred p, q;\nsetp.ne.u32 p, %1, 0;\nbarrier.red.or.pred q, 7, 96, p;\nselp.u32 %0, 1, 0, q;\n}\n"
                 : "=r"(anybad) : "r"((uint32_t)bad) : "memory");
    if (__any_sync(0xffffffffu, anybad)) {
      mbar_wait(bud, BAR_OFULL, par);
      slow_item(p, item, hw);
      bar_sync(7, 96);
    }
    if (hw == 1) {
      mbar_wait(bud, BAR_OFULL, par);
      if ((tid_x() & 31) == 0) {
        TLP(41 + hw * 4);
        asm volatile("red.release.gpu.global.add.s32 [%0], 1;" ::"l"(&g_ready[item]) : "memory");
        TLP(42 + hw * 4);
      }
      __syncwarp();
    }
    item = next_item();
  }
}

__device__ __forceinline__ int attn_producer(const Params& p, int item) {
  int bud = WAIT_BUDGET;
  uint32_t sa = 0, pa = 1;
  const uint64_t pol = evict_first_policy();
  const bool draws = item >= N_OCTA;
  const int delay = start_delay(item);
  {
    const long long t0 = clock64();
    while (clock64() - t0 < delay) __nanosleep(100);
  }
#pragma unroll 1
  for (int it = 0; item < NITEMS; it++) {
    const int blk = item >> 9, h = (item >> 4) & 31, b = item & 15;
    const int row0 = (b * NH + h) * SK;
#pragma unroll
    for (int c = 0; c < 10; c++) {
      if (c >= NSLOT || (it | delay)) {
        mbar_wait(bud, BAR_EMPTYA + sa * 8, pa);
        TLP(c);
        mbar_expect(BAR_FULLA + sa * 8, A_SLOT + B_SLOT);
        tma3d(A_ADDR(sa), &p.wq[blk], BAR_FULLA + sa * 8, 0, c * 64, h * 3);
        mbar_wait(bud, BAR_EMPTYB + xs(c) * 8, c < NSLOT);
        TLP(10 + c);
        tma2d(B_ADDR(xs(c)), &p.x[blk], BAR_FULLA + sa * 8, c * 64, b * SQ);
      }
      if (++sa == NSLOT) { sa = 0; pa ^= 1; }
    }
#pragma unroll
    for (int i = 0; i < 16; i++) {
      const bool isK = (i == 0) || ((i & 1) && i < 15);
      const int j = i == 0 ? 0 : (i == 15 ? 7 : (isK ? (i + 1) >> 1 : (i - 2) >> 1));
      mbar_wait(bud, BAR_EMPTYA + sa * 8, pa);
      TLP(20 + i);
      if (i == 11) item = draws ? NCTA + (int)atomicInc(&g_ticket, NITEMS - NCTA + N_ATT - 1) : NITEMS;
      if (i == 13) asm volatile("st.shared.s32 [%0], %1;" ::"r"(NEXT_ITEM), "r"(item) : "memory");
      mbar_expect(BAR_FULLA + sa * 8, A_SLOT);
      tma3d_hint(A_ADDR(sa), isK ? &p.k[blk] : &p.v[blk], BAR_FULLA + sa * 8, 0, row0 + j * 64, 0, pol);
      if (++sa == NSLOT) { sa = 0; pa ^= 1; }
    }
  }
  return item;
}

struct OJob { int tile, part, s0, s1; };
__device__ __forceinline__ OJob get_ojob(int cta, int last) {
  if (cta < N_OCTA) return OJob{O_PAIR ? ((cta & 15) << 1) | (cta >> 4) : cta, 0, 0, STEP1};
  const int u = last - NITEMS, part = 1 + (u >> 5);
  return OJob{u & 31, part, part == 1 ? STEP1 : part == 2 ? STEP2 : STEP3, part == 1 ? STEP2 : part == 2 ? STEP3 : part == 3 ? 2 * NH : 0};
}

template <int W>
__device__ __forceinline__ void oproj_consumer(const Params& p, const OJob job) {
  int bud = WAIT_BUDGET;
  const int tid = threadIdx.x & 127, lane = tid & 31, warp = tid >> 5;
  const int qrow = 8 * ((lane >> 1) & 1) + 4 * (lane >> 4) + 2 * ((lane >> 2) & 1) + (lane & 1);
  const uint32_t st_off = qrow * 128 + (((2 * warp + ((lane >> 3) & 1)) ^ (qrow & 7)) << 4);
  float a0[80], a1[80], ah[40];
  zero_regs(a0); zero_regs(a1); zero_regs(ah);
  int step = job.s0;
#pragma unroll 1
  while (step < job.s1) {
    const int nc = 3 * ((step < NH ? NH : job.s1) - step);
    uint32_t st = 0;
#pragma unroll 1
    for (int c = 0; c < nc; c++) {
      mbar_wait(bud, BAR_GFULL + st * 8, (step - job.s0) & 1);
      wg_fence();
      const uint32_t la = lo_sw(SB + st * O_STAGE), lb = lo_o(SB + st * O_STAGE + O_AB);
#define O_STEP(ks, sc)                                                        \
  mma80r<1, 1, 2 * 8192 + ks * 2048, W * 10240 + ks * 512>(ah, la, lb, sc);   \
  mma160r<1, 1, (W * 3) * 8192 + ks * 2048, ks * 512>(a0, la, lb, sc);        \
  mma160r<1, 1, (W * 3 + 1) * 8192 + ks * 2048, ks * 512>(a1, la, lb, sc);
      O_STEP(0, c != 0) O_STEP(1, 1)
      wg_commit();
      wg_wait<1>();
      mbar_arrive_if0(BAR_GEMPTY + (st == 0 ? 2 : st - 1) * 8, tid | (c == 0));
      wg_fence();
      O_STEP(2, 1) O_STEP(3, 1)
#undef O_STEP
      wg_commit();
      if (++st == 3) {
        st = 0;
        if (W == 0)
          asm volatile("{\n.reg .pred p;\nsetp.eq.u32 p, %1, 0;\n@p red.relaxed.gpu.global.add.s32 [%0], 1;\n}\n"
                       ::"l"(&g_done[step * 16 + (job.tile >> 1)]), "r"(tid) : "memory");
        TLG(step);
        step++;
      }
    }
    wg_wait<0>();
    reg_fence(a0); reg_fence(a1); reg_fence(ah);
    const uint32_t sg = SB + O_OUT + st_off;
    if (W == 1) {
      bar_arrive(3, 256);
      store_scaled(sg + 3 * B_SLOT, a0, 1.0f);
      publish(BAR_GOUT + 24, lane);
      bar_sync(9, 256);
      store_scaled(sg + 2 * B_SLOT + 10240, ah, 1.0f);
      publish(BAR_GOUT + 16, lane);
      store_scaled(sg + 4 * B_SLOT, a1, 1.0f);
      publish(BAR_GOUT + 32, lane);
    } else {
      bar_arrive(9, 256);
      bar_sync(3, 256);
      store_scaled(sg, a0, 1.0f);
      publish(BAR_GOUT, lane);
      store_scaled(sg + B_SLOT, a1, 1.0f);
      publish(BAR_GOUT + 8, lane);
      store_scaled(sg + 2 * B_SLOT, ah, 1.0f);
      publish(BAR_GOUT + 16, lane);
    }
  }
  TL_FLUSH();
  TLG(0);
  float acc[7][8];
  uint32_t in[7], blk[7];
#pragma unroll
  for (int i = 0; i < 7; i++) {
    const int e = min(i * 256 + W * 128 + tid, 1599), r = e / 40, cc = e % 40;
    in[i] = r * 128 + (((cc ^ r) & 7) << 4);
    blk[i] = cc >> 3;
#pragma unroll
    for (int k = 0; k < 8; k++) acc[i][k] = 0.f;
  }
  bar_sync(10, 256);
#pragma unroll 1
  for (int q = 0; q < 4; q++) {
    if (q) mbar_wait(bud, BAR_GRED + (q - 1) * 8, 0);
    if (q == 3) TLG(1);
    const uint32_t base = q ? SB + (q - 1) * 25600 : SB + O_OUT + job.part * 5120, bs = q ? 5120 : B_SLOT;
    uint4 v[7];
#pragma unroll
    for (int i = 0; i < 7; i++) v[i] = lds128(base + blk[i] * bs + in[i]);
#pragma unroll
    for (int i = 0; i < 7; i++) {
      acc[i][0] += bf_lo(v[i].x); acc[i][1] += bf_hi(v[i].x); acc[i][2] += bf_lo(v[i].y); acc[i][3] += bf_hi(v[i].y);
      acc[i][4] += bf_lo(v[i].z); acc[i][5] += bf_hi(v[i].z); acc[i][6] += bf_lo(v[i].w); acc[i][7] += bf_hi(v[i].w);
    }
  }
  uint4* go = (uint4*)p.outp + ((job.tile >> 1) * SQ + job.part * 40) * (2 * DM / 8) + DM / 8 + (job.tile & 1) * 40;
#pragma unroll
  for (int i = 0; i < 7; i++) {
    const int r = in[i] >> 7, cc = blk[i] * 8 + (((in[i] >> 4) ^ r) & 7);
    if (i * 256 + W * 128 + tid < 1600)
      go[r * (2 * DM / 8) + cc] = make_uint4(pack2(acc[i][0], acc[i][1]), pack2(acc[i][2], acc[i][3]), pack2(acc[i][4], acc[i][5]), pack2(acc[i][6], acc[i][7]));
  }
  TLG(2);
  TL_FLUSH();
}

__device__ __forceinline__ void oproj_producer(const Params& p, const OJob job, int target) {
  int bud = WAIT_BUDGET;
  const uint64_t polo = evict_first_policy();
  mbar_wait(bud, BAR_FREE, 0);
#pragma unroll 1
  for (int step = job.s0; step < job.s1; step++) {
    const int item = step * 16 + (job.tile >> 1);
    const char* og = o_slot(item);
    flag_wait(bud, &g_ready[item], target);
    asm volatile("fence.proxy.async.global;" ::: "memory");
#pragma unroll
    for (int kb = 0; kb < 3; kb++) {
      const uint32_t dst = SB + kb * O_STAGE, bar = BAR_GFULL + kb * 8;
      mbar_wait(bud, BAR_GEMPTY + kb * 8, ((step - job.s0) & 1) ^ 1);
      mbar_expect(bar, O_STAGE);
      tma3d(dst, &p.wo[step >> 5], bar, 0, ((step & 31) * 3 + kb) * 64, (job.tile & 1) * 5);
      bulk_load_hint(dst + O_AB, og + kb * B_SLOT, B_SLOT, bar, polo);
    }
  }
  mbar_wait(bud, BAR_GEMPTY, ((job.s1 - job.s0) & 1) ^ 1);
  mbar_wait(bud, BAR_GEMPTY + 8, ((job.s1 - job.s0) & 1) ^ 1);
  uint32_t todo = 15 & ~(1 << job.part), dst = SB, bar = BAR_GRED;
  while (todo) {
#pragma unroll 1
    for (int q = 0; q < 4; q++) {
      if (!((todo >> q) & 1)) continue;
      int v;
      asm volatile("ld.acquire.gpu.global.s32 %0, [%1];" : "=r"(v) : "l"(&g_pcnt[job.tile * 4 + q]) : "memory");
      if (v - target < 0 && --bud > 0) continue;
      asm volatile("fence.proxy.async.global;" ::: "memory");
      mbar_expect(bar, 25600);
      for (int k = 0; k < 5; k++)
        tma2d(dst + k * 5120, &p.part, bar, (job.tile & 1) * 320 + k * 64, q * NB * SQ + (job.tile >> 1) * SQ + job.part * 40);
      todo &= ~(1 << q);
      dst += 25600;
      bar += 8;
    }
  }
}

__device__ __forceinline__ void oproj_storer(const Params& p, const OJob job) {
  int bud = WAIT_BUDGET;
  const int col = (job.tile & 1) * 320, row = (job.tile >> 1) * SQ;
  if (job.part == 0) {
    for (int k = 0; k < 3; k++) {
      mbar_wait(bud, BAR_GOUT + k * 8, 0);
      tma_store2d(&p.out, SB + O_OUT + k * B_SLOT, col + k * 64, row);
    }
    asm volatile("cp.async.bulk.commit_group;" ::: "memory");
    asm volatile("cp.async.bulk.wait_group.read 0;" ::: "memory");
    mbar_arrive2_if0(BAR_GEMPTY + 16, 0);
    mbar_wait(bud, BAR_GFULL + 16, 0);
    for (int k = 3; k < 5; k++) {
      mbar_wait(bud, BAR_GOUT + k * 8, 0);
      tma_store2d(&p.out, SB + O_OUT + k * B_SLOT, col + k * 64, row);
      asm volatile("cp.async.bulk.commit_group;" ::: "memory");
      asm volatile("cp.async.bulk.wait_group.read 0;" ::: "memory");
      __nanosleep(1000);
    }
  }
#pragma unroll 1
  for (int i = 0; i < 5; i++) {
    const int k = (0x42103 >> (4 * i)) & 15;
    mbar_wait(bud, BAR_GOUT + k * 8, job.part == 0);
    for (int q = 1; q < 4; q++) {
      const int sh = (job.part + q) & 3;
      tma_store2d(&p.part, SB + O_OUT + k * B_SLOT + sh * 5120, col + k * 64, job.part * NB * SQ + row + sh * 40);
    }
  }
  asm volatile("cp.async.bulk.commit_group;" ::: "memory");
  asm volatile("cp.async.bulk.wait_group 0;" ::: "memory");
  asm volatile("fence.proxy.async.global;" ::: "memory");
  asm volatile("red.release.gpu.global.add.s32 [%0], 1;" ::"l"(&g_pcnt[job.tile * 4 + job.part]) : "memory");
}

__global__ void __launch_bounds__(384, 1) fused_kernel(const __grid_constant__ Params p) {
  extern __shared__ __align__(1024) char smem_raw[];
  if ((smem_u32(smem_raw) & 0xFFFFFFu) != SB) return;
  const int cta = (((blockIdx.x / PERM_G) * PERM_M) % (NCTA / PERM_G)) * PERM_G + (blockIdx.x % PERM_G);
  const int warp = __shfl_sync(0xffffffffu, threadIdx.x >> 5, 0);
  if (threadIdx.x == 0) {
    for (int i = 0; i < NSLOT; i++) { mbar_init(BAR_FULLA + i * 8, 1); mbar_init(BAR_EMPTYA + i * 8, 2); mbar_init(BAR_EMPTYB + i * 8, 2); }
    proxy_fence();
    if (start_delay(cta) == 0) {
#pragma unroll 1
      for (int c = 0; c < NSLOT; c++) {
        mbar_expect(BAR_FULLA + c * 8, A_SLOT + B_SLOT);
        tma3d(A_ADDR(c), &p.wq[0], BAR_FULLA + c * 8, 0, c * 64, (cta >> 4) * 3);
        tma2d(B_ADDR(c), &p.x[0], BAR_FULLA + c * 8, c * 64, (cta & 15) * SQ);
      }
    }
  }
  if (threadIdx.x == 64) {
    mbar_init(BAR_XDONE, 1); mbar_init(BAR_QH, 4); mbar_init(BAR_QM, 4);
    mbar_init(BAR_PFULL, 4); mbar_init(BAR_PFULL + 8, 4); mbar_init(BAR_PFREE, 3); mbar_init(BAR_PFREE + 8, 3);
    mbar_init(BAR_LFULL, 3); mbar_init(BAR_PMID, 4); mbar_init(BAR_PMID + 8, 4); mbar_init(BAR_OFULL, 8);
  }
  if (threadIdx.x == 96) {
    for (int i = 0; i < O_NST; i++) { mbar_init(BAR_GFULL + i * 8, 1); mbar_init(BAR_GEMPTY + i * 8, 2); }
    for (int i = 0; i < 5; i++) mbar_init(BAR_GOUT + i * 8, i == 2 ? 8 : 4);
    mbar_init(BAR_GRED, 1); mbar_init(BAR_GRED + 8, 1); mbar_init(BAR_GRED + 16, 1); mbar_init(BAR_FREE, 2);
    proxy_fence();
  }
  if (warp == 1 && threadIdx.x < 32 + 12) asm volatile("prefetch.tensormap [%0];" ::"l"(&p.x[0] + (threadIdx.x - 32)) : "memory");
  __syncthreads();
  if (warp >= 8) {
    asm volatile("setmaxnreg.dec.sync.aligned.u32 40;");
    if (warp == 8) {
      if (elect_one()) {
        const OJob job = get_ojob(cta, attn_producer(p, cta));
        const int epoch = *(volatile int*)&g_epoch[cta];
        *(volatile int*)&g_epoch[cta] = epoch + 1;
        if (job.s0 < job.s1) oproj_producer(p, job, epoch + 1);
      }
    } else {
      const int epoch = __shfl_sync(0xffffffffu, *(volatile int*)&g_epoch[cta], 0);
      attn_helper(p, warp - 9, cta, epoch);
      if (warp == 9) {
        const OJob job = get_ojob(cta, next_item());
        if (job.s0 < job.s1 && elect_one()) oproj_storer(p, job);
      }
    }
  } else {
    asm volatile("setmaxnreg.inc.sync.aligned.u32 232;");
    if (warp < 4) {
      const OJob job = get_ojob(cta, attn_consumer<0>(cta));
      if (job.s0 < job.s1) oproj_consumer<0>(p, job);
    } else {
      const OJob job = get_ojob(cta, attn_consumer<1>(cta));
      if (job.s0 < job.s1) oproj_consumer<1>(p, job);
    }
  }
}

typedef CUresult (*EncodeFn)(CUtensorMap*, CUtensorMapDataType, cuuint32_t, void*, const cuuint64_t*, const cuuint64_t*, const cuuint32_t*,
                             const cuuint32_t*, CUtensorMapInterleave, CUtensorMapSwizzle, CUtensorMapL2promotion, CUtensorMapFloatOOBfill);

void make3d(EncodeFn enc, CUtensorMap* m, const void* ptr, uint64_t rows, uint64_t cols, uint32_t box_rows, uint32_t box_blocks,
            CUtensorMapL2promotion promo = CU_TENSOR_MAP_L2_PROMOTION_L2_128B) {
  cuuint64_t gd[3] = {64, rows, cols / 64};
  cuuint64_t gs[2] = {cols * 2, 128};
  cuuint32_t bd[3] = {64, box_rows, box_blocks}, es[3] = {1, 1, 1};
  enc(m, CU_TENSOR_MAP_DATA_TYPE_BFLOAT16, 3, (void*)ptr, gd, gs, bd, es, CU_TENSOR_MAP_INTERLEAVE_NONE, CU_TENSOR_MAP_SWIZZLE_128B,
      promo, CU_TENSOR_MAP_FLOAT_OOB_FILL_NONE);
}
void make2d(EncodeFn enc, CUtensorMap* m, const void* ptr, uint64_t rows, uint64_t cols, uint32_t box_rows) {
  cuuint64_t gd[2] = {cols, rows};
  cuuint64_t gs[1] = {cols * 2};
  cuuint32_t bd[2] = {64, box_rows}, es[2] = {1, 1};
  enc(m, CU_TENSOR_MAP_DATA_TYPE_BFLOAT16, 2, (void*)ptr, gd, gs, bd, es, CU_TENSOR_MAP_INTERLEAVE_NONE, CU_TENSOR_MAP_SWIZZLE_128B,
      CU_TENSOR_MAP_L2_PROMOTION_L2_128B, CU_TENSOR_MAP_FLOAT_OOB_FILL_NONE);
}

}

extern "C" void kernel_launch(void* const* d_in, const int* in_sizes, int n_in, void* d_out, int out_size) {
  static EncodeFn enc = nullptr;
  static void* part = nullptr;
  if (!enc) {
    cudaGetSymbolAddress(&part, g_part);
    cudaDriverEntryPointQueryResult qr;
    cudaGetDriverEntryPoint("cuTensorMapEncodeTiled", (void**)&enc, cudaEnableDefault, &qr);
    cudaFuncSetAttribute(fused_kernel, cudaFuncAttributeMaxDynamicSharedMemorySize, SMEM_BYTES);
  }
  Params p;
  for (int s = 0; s < 2; s++) {
    make2d(enc, &p.x[s], d_in[5 * s + 0], NB * SQ, DM, SQ);
    make3d(enc, &p.k[s], d_in[5 * s + 1], (uint64_t)NB * NH * SK, DH, 64, 3);
    make3d(enc, &p.v[s], d_in[5 * s + 2], (uint64_t)NB * NH * SK, DH, 64, 3);
    make3d(enc, &p.wq[s], d_in[5 * s + 3], DM, NH * DH, 64, 3);
    make3d(enc, &p.wo[s], d_in[5 * s + 4], NH * DH, DM, 64, 5);
    p.xp[s] = (const __nv_bfloat16*)d_in[5 * s + 0];
    p.wqp[s] = (const __nv_bfloat16*)d_in[5 * s + 3];
    p.kp[s] = (const __nv_bfloat16*)d_in[5 * s + 1];
    p.vp[s] = (const __nv_bfloat16*)d_in[5 * s + 2];
  }
  make2d(enc, &p.out, d_out, NB * SQ, 2 * DM, SQ);
  make2d(enc, &p.part, part, 4 * NB * SQ, DM, 40);
  p.outp = (__nv_bfloat16*)d_out;
  fused_kernel<<<NCTA, 384, SMEM_BYTES>>>(p);
}
```

```cpp
#include <cuda_runtime.h>
#include <cuda_bf16.h>
#include <cuda.h>
#include <stdint.h>

#define DEBUG_TIMEOUT 0

namespace {

constexpr int SQ = 160, DM = 640, NH = 32, SK = 512, DH = 192, NB = 16;
constexpr int NITEMS = 2 * NB * NH;
constexpr int NCTA = 132, N_OCTA = 32, N_ATT = NCTA - N_OCTA;
constexpr int ORING = 192, OFRESH = 800, STEP1 = 53, LEN1 = 17, LEN2 = 12, LSLOPE1 = 4, LSLOPE2 = 4;
constexpr int STAG_G = 4, PERM_G = 4, O_PAIR = 0, STAG_A0 = 15, STAG_SLOPE = 262, PERM_M = 20, PF_N = 32, PF_WAIT = 1500, PF_GAP = 300;
constexpr int OSLOTS = ORING + NITEMS - OFRESH;
#define W1_NG 3
constexpr int A_SLOT = 24576, B_SLOT = 20480, NSLOT = 5;
constexpr int OFF_A = 0;
constexpr int OFF_B = NSLOT * A_SLOT;
constexpr int O_STAGE = 61440, O_AB = 40960, O_NST = 3;
constexpr int OFF_L = OFF_B + NSLOT * B_SLOT;
constexpr int OFF_BAR = OFF_L + 160 * 4;
constexpr int SMEM_BYTES = OFF_BAR + 512 + 512;
constexpr int O_OUT = 2 * O_STAGE;
static_assert(O_OUT + 5 * B_SLOT <= OFF_L, "smem layout");
constexpr uint32_t SB = 1024;
constexpr uint32_t BARS = SB + OFF_BAR;
constexpr uint32_t BAR_FULLA = BARS, BAR_EMPTYA = BARS + 40, BAR_PMID = BARS + 80, BAR_EMPTYB = BARS + 120, BAR_XDONE = BARS + 160,
                   BAR_QH = BARS + 168, BAR_QM = BARS + 96, BAR_PFULL = BARS + 184, BAR_PFREE = BARS + 200, BAR_LFULL = BARS + 216,
                   BAR_OFULL = BARS + 224, BAR_GFULL = BARS + 248, BAR_GEMPTY = BARS + 280, BAR_GOUT = BARS + 328, BAR_GRED = BARS + 368,
                   BAR_FREE = BARS + 240, NEXT_ITEM = BARS + 320;
constexpr int O_ITEM_BYTES = SQ * DH * 2;

struct alignas(64) Params {
  CUtensorMap x[2], wq[2], k[2], v[2], wo[2], out, part;
  __nv_bfloat16* outp;
  const __nv_bfloat16 *xp[2], *wqp[2], *kp[2], *vp[2];
};

__device__ uint4 g_o[(size_t)OSLOTS * O_ITEM_BYTES / 16];
__device__ uint4 g_part[4 * NB * SQ * DM / 8];
__device__ int g_pcnt[4 * N_OCTA];
__device__ int g_ready[NITEMS];
__device__ int g_done[NITEMS];
__device__ unsigned g_ticket;
__device__ int g_epoch[NCTA];

#define TLP(id)
#define TLG(id)
#define TL(id)
#define TL_FLUSH()
__device__ __forceinline__ uint32_t smem_u32(const void* p) { return (uint32_t)__cvta_generic_to_shared(p); }
__device__ __forceinline__ void wg_fence() { asm volatile("wgmma.fence.sync.aligned;" ::: "memory"); }
__device__ __forceinline__ void wg_commit() { asm volatile("wgmma.commit_group.sync.aligned;" ::: "memory"); }
template <int N> __device__ __forceinline__ void wg_wait() { asm volatile("wgmma.wait_group.sync.aligned %0;" ::"n"(N) : "memory"); }
template <int N> __device__ __forceinline__ void reg_fence(float (&d)[N]) {
#pragma unroll
  for (int i = 0; i < N; i++) asm volatile("" : "+f"(d[i])::"memory");
}
template <int N> __device__ __forceinline__ void zero_regs(float (&d)[N]) {
#pragma unroll
  for (int i = 0; i < N; i++) d[i] = 0.f;
}
__device__ __forceinline__ void proxy_fence() { asm volatile("fence.proxy.async.shared::cta;" ::: "memory"); }
__device__ __forceinline__ void mbar_init(uint32_t bar, int cnt) { asm volatile("mbarrier.init.shared::cta.b64 [%0], %1;" ::"r"(bar), "r"(cnt) : "memory"); }
__device__ __forceinline__ void mbar_arrive_if0(uint32_t bar, uint32_t sel) {
  asm volatile("{\n.reg .pred p;\nsetp.eq.u32 p, %1, 0;\n@p mbarrier.arrive.shared::cta.b64 _, [%0];\n}\n" ::"r"(bar), "r"(sel) : "memory");
}
__device__ __forceinline__ void mbar_arrive2_if0(uint32_t bar, uint32_t sel) {
  asm volatile("{\n.reg .pred p;\nsetp.eq.u32 p, %1, 0;\n@p mbarrier.arrive.shared::cta.b64 _, [%0], 2;\n}\n" ::"r"(bar), "r"(sel) : "memory");
}
__device__ __forceinline__ void mbar_expect(uint32_t bar, uint32_t bytes) {
  asm volatile("mbarrier.arrive.expect_tx.shared::cta.b64 _, [%0], %1;" ::"r"(bar), "r"(bytes) : "memory");
}
__device__ __forceinline__ void mbar_wait(int& bud, uint32_t bar, uint32_t parity) {
  asm volatile(
      "{\n.reg .pred p;\n"
      "LW:\n"
      "mbarrier.try_wait.parity.shared::cta.b64 p, [%0], %1;\n"
      "@!p bra LW;\n}\n" ::"r"(bar), "r"(parity) : "memory");
}
constexpr int WAIT_BUDGET = 1 << 22;
__device__ __forceinline__ bool elect_one() {
  uint32_t p;
  asm volatile("{\n.reg .pred p;\nelect.sync _|p, 0xffffffff;\nselp.u32 %0, 1, 0, p;\n}\n" : "=r"(p));
  return p;
}
__device__ __forceinline__ void tma2d(uint32_t dst, const CUtensorMap* m, uint32_t bar, int c0, int c1) {
  asm volatile("cp.async.bulk.tensor.2d.shared::cluster.global.mbarrier::complete_tx::bytes [%0], [%1, {%3, %4}], [%2];"
               ::"r"(dst), "l"(m), "r"(bar), "r"(c0), "r"(c1) : "memory");
}
__device__ __forceinline__ void tma3d(uint32_t dst, const CUtensorMap* m, uint32_t bar, int c0, int c1, int c2) {
  asm volatile("cp.async.bulk.tensor.3d.shared::cluster.global.mbarrier::complete_tx::bytes [%0], [%1, {%3, %4, %5}], [%2];"
               ::"r"(dst), "l"(m), "r"(bar), "r"(c0), "r"(c1), "r"(c2) : "memory");
}
__device__ __forceinline__ void tma3d_hint(uint32_t dst, const CUtensorMap* m, uint32_t bar, int c0, int c1, int c2, uint64_t pol) {
  asm volatile("cp.async.bulk.tensor.3d.shared::cluster.global.mbarrier::complete_tx::bytes.L2::cache_hint [%0], [%1, {%3, %4, %5}], [%2], %6;"
               ::"r"(dst), "l"(m), "r"(bar), "r"(c0), "r"(c1), "r"(c2), "l"(pol) : "memory");
}
__device__ __forceinline__ void tma_store2d(const CUtensorMap* m, uint32_t src, int c0, int c1) {
  asm volatile("cp.async.bulk.tensor.2d.global.shared::cta.bulk_group [%0, {%2, %3}], [%1];" ::"l"(m), "r"(src), "r"(c0), "r"(c1) : "memory");
}
__device__ __forceinline__ void bar_sync(int id, int n) { asm volatile("bar.sync %0, %1;" ::"r"(id), "r"(n) : "memory"); }
__device__ __forceinline__ void bar_arrive(int id, int n) { asm volatile("bar.arrive %0, %1;" ::"r"(id), "r"(n) : "memory"); }
__device__ __forceinline__ float ex2(float x) { float y; asm("ex2.approx.ftz.f32 %0, %1;" : "=f"(y) : "f"(x)); return y; }
__device__ __forceinline__ uint32_t pack2(float lo, float hi) { uint32_t r; asm("cvt.rn.bf16x2.f32 %0, %1, %2;" : "=r"(r) : "f"(hi), "f"(lo)); return r; }
__device__ __forceinline__ void stsm_t(uint32_t a, uint32_t r0, uint32_t r1, uint32_t r2, uint32_t r3) {
  asm volatile("stmatrix.sync.aligned.m8n8.x4.trans.shared.b16 [%0], {%1,%2,%3,%4};" ::"r"(a), "r"(r0), "r"(r1), "r"(r2), "r"(r3) : "memory");
}
__device__ __forceinline__ uint64_t evict_first_policy() {
  uint64_t pol;
  asm volatile("createpolicy.fractional.L2::evict_first.b64 %0, 1.0;" : "=l"(pol));
  return pol;
}
__device__ __forceinline__ void bulk_load_hint(uint32_t dst, const void* src, uint32_t bytes, uint32_t bar, uint64_t pol) {
  asm volatile("cp.async.bulk.shared::cluster.global.mbarrier::complete_tx::bytes.L2::cache_hint [%0], [%1], %2, [%3], %4;"
               ::"r"(dst), "l"(src), "r"(bytes), "r"(bar), "l"(pol) : "memory");
}
__device__ __forceinline__ void flag_wait(int& bud, const int* p, int target) {
  while (true) {
    int v;
    asm volatile("ld.acquire.gpu.global.s32 %0, [%1];" : "=r"(v) : "l"(p) : "memory");
    if (v - target >= 0 || --bud <= 0) break;
    __nanosleep(64);
  }
}
__device__ __forceinline__ uint32_t lo_sw(uint32_t addr) { return (addr >> 4) | (1u << 16); }
__device__ __forceinline__ uint32_t lo_o(uint32_t addr) { return (addr >> 4) | (128u << 16); }
__device__ __forceinline__ uint32_t tid_x() { uint32_t t; asm volatile("mov.u32 %0, %tid.x;" : "=r"(t)); return t; }
__device__ __forceinline__ uint32_t opaque(uint32_t x) { uint32_t y; asm volatile("mov.u32 %0, %1;" : "=r"(y) : "r"(x)); return y; }

template <int TA, int TB, uint32_t OA, uint32_t OB>
__device__ __forceinline__ void mma160(float (&d)[80], uint32_t la, uint32_t lb) {
  asm volatile(
      "{\n.reg .pred p;\n.reg .b32 a, b;\n.reg .b64 da, db;\nsetp.eq.b32 p, 0, 0;\n"
      "add.u32 a, %80, %84;\nadd.u32 b, %81, %85;\nmov.b64 da, {a, 0x40000040};\nmov.b64 db, {b, %86};\n"
      "wgmma.mma_async.sync.aligned.m64n160k16.f32.bf16.bf16 {"
      "%0,%1,%2,%3,%4,%5,%6,%7,%8,%9,%10,%11,%12,%13,%14,%15,%16,%17,%18,%19,%20,%21,%22,%23,%24,%25,%26,%27,%28,%29,%30,%31,%32,%33,%34,%35,%36,"
      "%37,%38,%39,%40,%41,%42,%43,%44,%45,%46,%47,%48,%49,%50,%51,%52,%53,%54,%55,%56,%57,%58,%59,%60,%61,%62,%63,%64,%65,%66,%67,%68,%69,%70,%71,"
      "%72,%73,%74,%75,%76,%77,%78,%79"
      "}, da, db, p, 1, 1, %82, %83;\n}\n"
      :
      "+f"(d[0]),"+f"(d[1]),"+f"(d[2]),"+f"(d[3]),"+f"(d[4]),"+f"(d[5]),"+f"(d[6]),"+f"(d[7]),"+f"(d[8]),"+f"(d[9]),"+f"(d[10]),"+f"(d[11]),
      "+f"(d[12]),"+f"(d[13]),"+f"(d[14]),"+f"(d[15]),"+f"(d[16]),"+f"(d[17]),"+f"(d[18]),"+f"(d[19]),"+f"(d[20]),"+f"(d[21]),"+f"(d[22]),
      "+f"(d[23]),"+f"(d[24]),"+f"(d[25]),"+f"(d[26]),"+f"(d[27]),"+f"(d[28]),"+f"(d[29]),"+f"(d[30]),"+f"(d[31]),"+f"(d[32]),"+f"(d[33]),
      "+f"(d[34]),"+f"(d[35]),"+f"(d[36]),"+f"(d[37]),"+f"(d[38]),"+f"(d[39]),"+f"(d[40]),"+f"(d[41]),"+f"(d[42]),"+f"(d[43]),"+f"(d[44]),
      "+f"(d[45]),"+f"(d[46]),"+f"(d[47]),"+f"(d[48]),"+f"(d[49]),"+f"(d[50]),"+f"(d[51]),"+f"(d[52]),"+f"(d[53]),"+f"(d[54]),"+f"(d[55]),
      "+f"(d[56]),"+f"(d[57]),"+f"(d[58]),"+f"(d[59]),"+f"(d[60]),"+f"(d[61]),"+f"(d[62]),"+f"(d[63]),"+f"(d[64]),"+f"(d[65]),"+f"(d[66]),
      "+f"(d[67]),"+f"(d[68]),"+f"(d[69]),"+f"(d[70]),"+f"(d[71]),"+f"(d[72]),"+f"(d[73]),"+f"(d[74]),"+f"(d[75]),"+f"(d[76]),"+f"(d[77]),
      "+f"(d[78]),"+f"(d[79])
      : "r"(la), "r"(lb), "n"(TA), "n"(TB), "n"(OA >> 4), "n"(OB >> 4), "n"(TB ? 0xC0000010u : 0x40000040u));
}

template <int TA, int TB, uint32_t OA, uint32_t OB>
__device__ __forceinline__ void mma160z(float (&d)[80], uint32_t la, uint32_t lb) {
  asm volatile(
      "{\n.reg .pred p;\n.reg .b32 a, b;\n.reg .b64 da, db;\nsetp.ne.b32 p, 0, 0;\n"
      "add.u32 a, %80, %84;\nadd.u32 b, %81, %85;\nmov.b64 da, {a, 0x40000040};\nmov.b64 db, {b, %86};\n"
      "wgmma.mma_async.sync.aligned.m64n160k16.f32.bf16.bf16 {"
      "%0,%1,%2,%3,%4,%5,%6,%7,%8,%9,%10,%11,%12,%13,%14,%15,%16,%17,%18,%19,%20,%21,%22,%23,%24,%25,%26,%27,%28,%29,%30,%31,%32,%33,%34,%35,%36,"
      "%37,%38,%39,%40,%41,%42,%43,%44,%45,%46,%47,%48,%49,%50,%51,%52,%53,%54,%55,%56,%57,%58,%59,%60,%61,%62,%63,%64,%65,%66,%67,%68,%69,%70,%71,"
      "%72,%73,%74,%75,%76,%77,%78,%79"
      "}, da, db, p, 1, 1, %82, %83;\n}\n"
      :
      "=f"(d[0]),"=f"(d[1]),"=f"(d[2]),"=f"(d[3]),"=f"(d[4]),"=f"(d[5]),"=f"(d[6]),"=f"(d[7]),"=f"(d[8]),"=f"(d[9]),"=f"(d[10]),"=f"(d[11]),
      "=f"(d[12]),"=f"(d[13]),"=f"(d[14]),"=f"(d[15]),"=f"(d[16]),"=f"(d[17]),"=f"(d[18]),"=f"(d[19]),"=f"(d[20]),"=f"(d[21]),"=f"(d[22]),
      "=f"(d[23]),"=f"(d[24]),"=f"(d[25]),"=f"(d[26]),"=f"(d[27]),"=f"(d[28]),"=f"(d[29]),"=f"(d[30]),"=f"(d[31]),"=f"(d[32]),"=f"(d[33]),
      "=f"(d[34]),"=f"(d[35]),"=f"(d[36]),"=f"(d[37]),"=f"(d[38]),"=f"(d[39]),"=f"(d[40]),"=f"(d[41]),"=f"(d[42]),"=f"(d[43]),"=f"(d[44]),
      "=f"(d[45]),"=f"(d[46]),"=f"(d[47]),"=f"(d[48]),"=f"(d[49]),"=f"(d[50]),"=f"(d[51]),"=f"(d[52]),"=f"(d[53]),"=f"(d[54]),"=f"(d[55]),
      "=f"(d[56]),"=f"(d[57]),"=f"(d[58]),"=f"(d[59]),"=f"(d[60]),"=f"(d[61]),"=f"(d[62]),"=f"(d[63]),"=f"(d[64]),"=f"(d[65]),"=f"(d[66]),
      "=f"(d[67]),"=f"(d[68]),"=f"(d[69]),"=f"(d[70]),"=f"(d[71]),"=f"(d[72]),"=f"(d[73]),"=f"(d[74]),"=f"(d[75]),"=f"(d[76]),"=f"(d[77]),
      "=f"(d[78]),"=f"(d[79])
      : "r"(la), "r"(lb), "n"(TA), "n"(TB), "n"(OA >> 4), "n"(OB >> 4), "n"(TB ? 0xC0000010u : 0x40000040u));
}

template <int TA, int TB, uint32_t OA, uint32_t OB>
__device__ __forceinline__ void mma80(float (&d)[40], uint32_t la, uint32_t lb) {
  asm volatile(
      "{\n.reg .pred p;\n.reg .b32 a, b;\n.reg .b64 da, db;\nsetp.eq.b32 p, 0, 0;\n"
      "add.u32 a, %40, %44;\nadd.u32 b, %41, %45;\nmov.b64 da, {a, 0x40000040};\nmov.b64 db, {b, %46};\n"
      "wgmma.mma_async.sync.aligned.m64n80k16.f32.bf16.bf16 {"
      "%0,%1,%2,%3,%4,%5,%6,%7,%8,%9,%10,%11,%12,%13,%14,%15,%16,%17,%18,%19,%20,%21,%22,%23,%24,%25,%26,%27,%28,%29,%30,%31,%32,%33,%34,%35,%36,"
      "%37,%38,%39"
      "}, da, db, p, 1, 1, %42, %43;\n}\n"
      :
      "+f"(d[0]),"+f"(d[1]),"+f"(d[2]),"+f"(d[3]),"+f"(d[4]),"+f"(d[5]),"+f"(d[6]),"+f"(d[7]),"+f"(d[8]),"+f"(d[9]),"+f"(d[10]),"+f"(d[11]),
      "+f"(d[12]),"+f"(d[13]),"+f"(d[14]),"+f"(d[15]),"+f"(d[16]),"+f"(d[17]),"+f"(d[18]),"+f"(d[19]),"+f"(d[20]),"+f"(d[21]),"+f"(d[22]),
      "+f"(d[23]),"+f"(d[24]),"+f"(d[25]),"+f"(d[26]),"+f"(d[27]),"+f"(d[28]),"+f"(d[29]),"+f"(d[30]),"+f"(d[31]),"+f"(d[32]),"+f"(d[33]),
      "+f"(d[34]),"+f"(d[35]),"+f"(d[36]),"+f"(d[37]),"+f"(d[38]),"+f"(d[39])
      : "r"(la), "r"(lb), "n"(TA), "n"(TB), "n"(OA >> 4), "n"(OB >> 4), "n"(TB ? 0xC0000010u : 0x40000040u));
}

template <int TA, int TB, uint32_t OA, uint32_t OB>
__device__ __forceinline__ void mma80z(float (&d)[40], uint32_t la, uint32_t lb) {
  asm volatile(
      "{\n.reg .pred p;\n.reg .b32 a, b;\n.reg .b64 da, db;\nsetp.ne.b32 p, 0, 0;\n"
      "add.u32 a, %40, %44;\nadd.u32 b, %41, %45;\nmov.b64 da, {a, 0x40000040};\nmov.b64 db, {b, %46};\n"
      "wgmma.mma_async.sync.aligned.m64n80k16.f32.bf16.bf16 {"
      "%0,%1,%2,%3,%4,%5,%6,%7,%8,%9,%10,%11,%12,%13,%14,%15,%16,%17,%18,%19,%20,%21,%22,%23,%24,%25,%26,%27,%28,%29,%30,%31,%32,%33,%34,%35,%36,"
      "%37,%38,%39"
      "}, da, db, p, 1, 1, %42, %43;\n}\n"
      :
      "=f"(d[0]),"=f"(d[1]),"=f"(d[2]),"=f"(d[3]),"=f"(d[4]),"=f"(d[5]),"=f"(d[6]),"=f"(d[7]),"=f"(d[8]),"=f"(d[9]),"=f"(d[10]),"=f"(d[11]),
      "=f"(d[12]),"=f"(d[13]),"=f"(d[14]),"=f"(d[15]),"=f"(d[16]),"=f"(d[17]),"=f"(d[18]),"=f"(d[19]),"=f"(d[20]),"=f"(d[21]),"=f"(d[22]),
      "=f"(d[23]),"=f"(d[24]),"=f"(d[25]),"=f"(d[26]),"=f"(d[27]),"=f"(d[28]),"=f"(d[29]),"=f"(d[30]),"=f"(d[31]),"=f"(d[32]),"=f"(d[33]),
      "=f"(d[34]),"=f"(d[35]),"=f"(d[36]),"=f"(d[37]),"=f"(d[38]),"=f"(d[39])
      : "r"(la), "r"(lb), "n"(TA), "n"(TB), "n"(OA >> 4), "n"(OB >> 4), "n"(TB ? 0xC0000010u : 0x40000040u));
}

template <int TA, int TB, uint32_t OA, uint32_t OB>
__device__ __forceinline__ void mma160r(float (&d)[80], uint32_t la, uint32_t lb, int sc) {
  asm volatile(
      "{\n.reg .pred p;\n.reg .b32 a, b;\n.reg .b64 da, db;\nsetp.ne.b32 p, %87, 0;\n"
      "add.u32 a, %80, %84;\nadd.u32 b, %81, %85;\nmov.b64 da, {a, 0x40000040};\nmov.b64 db, {b, %86};\n"
      "wgmma.mma_async.sync.aligned.m64n160k16.f32.bf16.bf16 {"
      "%0,%1,%2,%3,%4,%5,%6,%7,%8,%9,%10,%11,%12,%13,%14,%15,%16,%17,%18,%19,%20,%21,%22,%23,%24,%25,%26,%27,%28,%29,%30,%31,%32,%33,%34,%35,%36,"
      "%37,%38,%39,%40,%41,%42,%43,%44,%45,%46,%47,%48,%49,%50,%51,%52,%53,%54,%55,%56,%57,%58,%59,%60,%61,%62,%63,%64,%65,%66,%67,%68,%69,%70,%71,"
      "%72,%73,%74,%75,%76,%77,%78,%79"
      "}, da, db, p, 1, 1, %82, %83;\n}\n"
      :
      "+f"(d[0]),"+f"(d[1]),"+f"(d[2]),"+f"(d[3]),"+f"(d[4]),"+f"(d[5]),"+f"(d[6]),"+f"(d[7]),"+f"(d[8]),"+f"(d[9]),"+f"(d[10]),"+f"(d[11]),
      "+f"(d[12]),"+f"(d[13]),"+f"(d[14]),"+f"(d[15]),"+f"(d[16]),"+f"(d[17]),"+f"(d[18]),"+f"(d[19]),"+f"(d[20]),"+f"(d[21]),"+f"(d[22]),
      "+f"(d[23]),"+f"(d[24]),"+f"(d[25]),"+f"(d[26]),"+f"(d[27]),"+f"(d[28]),"+f"(d[29]),"+f"(d[30]),"+f"(d[31]),"+f"(d[32]),"+f"(d[33]),
      "+f"(d[34]),"+f"(d[35]),"+f"(d[36]),"+f"(d[37]),"+f"(d[38]),"+f"(d[39]),"+f"(d[40]),"+f"(d[41]),"+f"(d[42]),"+f"(d[43]),"+f"(d[44]),
      "+f"(d[45]),"+f"(d[46]),"+f"(d[47]),"+f"(d[48]),"+f"(d[49]),"+f"(d[50]),"+f"(d[51]),"+f"(d[52]),"+f"(d[53]),"+f"(d[54]),"+f"(d[55]),
      "+f"(d[56]),"+f"(d[57]),"+f"(d[58]),"+f"(d[59]),"+f"(d[60]),"+f"(d[61]),"+f"(d[62]),"+f"(d[63]),"+f"(d[64]),"+f"(d[65]),"+f"(d[66]),
      "+f"(d[67]),"+f"(d[68]),"+f"(d[69]),"+f"(d[70]),"+f"(d[71]),"+f"(d[72]),"+f"(d[73]),"+f"(d[74]),"+f"(d[75]),"+f"(d[76]),"+f"(d[77]),
      "+f"(d[78]),"+f"(d[79])
      : "r"(la), "r"(lb), "n"(TA), "n"(TB), "n"(OA >> 4), "n"(OB >> 4), "n"(TB ? 0xC0000010u : 0x40000040u), "r"(sc));
}

template <int TA, int TB, uint32_t OA, uint32_t OB>
__device__ __forceinline__ void mma80r(float (&d)[40], uint32_t la, uint32_t lb, int sc) {
  asm volatile(
      "{\n.reg .pred p;\n.reg .b32 a, b;\n.reg .b64 da, db;\nsetp.ne.b32 p, %47, 0;\n"
      "add.u32 a, %40, %44;\nadd.u32 b, %41, %45;\nmov.b64 da, {a, 0x40000040};\nmov.b64 db, {b, %46};\n"
      "wgmma.mma_async.sync.aligned.m64n80k16.f32.bf16.bf16 {"
      "%0,%1,%2,%3,%4,%5,%6,%7,%8,%9,%10,%11,%12,%13,%14,%15,%16,%17,%18,%19,%20,%21,%22,%23,%24,%25,%26,%27,%28,%29,%30,%31,%32,%33,%34,%35,%36,"
      "%37,%38,%39"
      "}, da, db, p, 1, 1, %42, %43;\n}\n"
      :
      "+f"(d[0]),"+f"(d[1]),"+f"(d[2]),"+f"(d[3]),"+f"(d[4]),"+f"(d[5]),"+f"(d[6]),"+f"(d[7]),"+f"(d[8]),"+f"(d[9]),"+f"(d[10]),"+f"(d[11]),
      "+f"(d[12]),"+f"(d[13]),"+f"(d[14]),"+f"(d[15]),"+f"(d[16]),"+f"(d[17]),"+f"(d[18]),"+f"(d[19]),"+f"(d[20]),"+f"(d[21]),"+f"(d[22]),
      "+f"(d[23]),"+f"(d[24]),"+f"(d[25]),"+f"(d[26]),"+f"(d[27]),"+f"(d[28]),"+f"(d[29]),"+f"(d[30]),"+f"(d[31]),"+f"(d[32]),"+f"(d[33]),
      "+f"(d[34]),"+f"(d[35]),"+f"(d[36]),"+f"(d[37]),"+f"(d[38]),"+f"(d[39])
      : "r"(la), "r"(lb), "n"(TA), "n"(TB), "n"(OA >> 4), "n"(OB >> 4), "n"(TB ? 0xC0000010u : 0x40000040u), "r"(sc));
}

struct Ring { uint32_t s0, ph0; };
__device__ __forceinline__ void ring_pos(const Ring& r, int i, uint32_t& slot, uint32_t& ph) {
  uint32_t s = opaque(r.s0) + (i % NSLOT);
  uint32_t wrap = s >= NSLOT;
  slot = s - (wrap ? NSLOT : 0);
  ph = r.ph0 ^ ((i / NSLOT) & 1) ^ wrap;
}
__device__ __forceinline__ void ring_advance(Ring& r, int n) {
  uint32_t s, p;
  ring_pos(r, n, s, p);
  r.s0 = s; r.ph0 = p;
}
__host__ __device__ constexpr int idxK(int j) { return j == 0 ? 10 : 9 + 2 * j; }
__host__ __device__ constexpr int idxV(int j) { return j == 7 ? 25 : 12 + 2 * j; }
__host__ __device__ constexpr int xs(int c) { return c % NSLOT; }

__device__ __forceinline__ int start_delay(int cta) {
  return max(0, ((cta - N_OCTA) | (STAG_G - 1)) - STAG_A0) * STAG_SLOPE;
}
__device__ __forceinline__ char* o_slot(int item) {
  return (char*)g_o + (size_t)(item < OFRESH ? item % ORING : item - OFRESH + ORING) * O_ITEM_BYTES;
}
__device__ __forceinline__ int next_item(uint32_t a = NEXT_ITEM) {
  int v;
  asm volatile("ld.shared.s32 %0, [%1];" : "=r"(v) : "r"(a) : "memory");
  return __shfl_sync(0xffffffffu, v, 0);
}

template <int W, bool ACC>
__device__ __forceinline__ void mma_main(float (&d)[80], uint32_t aaddr, uint32_t baddr) {
  const uint32_t la = lo_sw(aaddr), lb = lo_sw(baddr);
  if (ACC) mma160<1, 0, W * 16384, 0>(d, la, lb); else mma160z<1, 0, W * 16384, 0>(d, la, lb);
  mma160<1, 0, W * 16384 + 1 * 2048, 1 * 32>(d, la, lb);
  mma160<1, 0, W * 16384 + 2 * 2048, 2 * 32>(d, la, lb);
  mma160<1, 0, W * 16384 + 3 * 2048, 3 * 32>(d, la, lb);
}
template <int W, bool ACC>
__device__ __forceinline__ void mma_mid(float (&d)[40], uint32_t aaddr, uint32_t baddr) {
  const uint32_t la = lo_sw(aaddr), lb = lo_sw(baddr);
  if (ACC) mma80<1, 0, 8192, W * 10240>(d, la, lb); else mma80z<1, 0, 8192, W * 10240>(d, la, lb);
  mma80<1, 0, 8192 + 1 * 2048, W * 10240 + 1 * 32>(d, la, lb);
  mma80<1, 0, 8192 + 2 * 2048, W * 10240 + 2 * 32>(d, la, lb);
  mma80<1, 0, 8192 + 3 * 2048, W * 10240 + 3 * 32>(d, la, lb);
}
template <int W, bool ACC>
__device__ __forceinline__ void mma_both(float (&dm)[80], float (&dh)[40], uint32_t aaddr, uint32_t baddr) {
  mma_mid<W, ACC>(dh, aaddr, baddr);
  mma_main<W, ACC>(dm, aaddr, baddr);
}
template <int KB, bool ACC>
__device__ __forceinline__ void s_mma(float (&sacc)[80], uint32_t kaddr) {
  const uint32_t la = lo_sw(kaddr), lb = lo_sw(SB + OFF_B);
  if (ACC) mma160<0, 0, KB * 8192, KB * B_SLOT>(sacc, la, lb); else mma160z<0, 0, KB * 8192, KB * B_SLOT>(sacc, la, lb);
  mma160<0, 0, KB * 8192 + 32, KB * B_SLOT + 32>(sacc, la, lb);
  mma160<0, 0, KB * 8192 + 64, KB * B_SLOT + 64>(sacc, la, lb);
  mma160<0, 0, KB * 8192 + 96, KB * B_SLOT + 96>(sacc, la, lb);
}
template <int N>
__device__ __forceinline__ void store_scaled(uint32_t addr, const float (&d)[N], float sc) {
#pragma unroll
  for (int J = 0; J < N / 8; J++)
    stsm_t(addr + J * 2048, pack2(d[8 * J] * sc, d[8 * J + 1] * sc), pack2(d[8 * J + 2] * sc, d[8 * J + 3] * sc),
           pack2(d[8 * J + 4] * sc, d[8 * J + 5] * sc), pack2(d[8 * J + 6] * sc, d[8 * J + 7] * sc));
}
__device__ __forceinline__ float4 lds_f4(uint32_t a) {
  float4 v;
  asm volatile("ld.shared.v4.f32 {%0,%1,%2,%3}, [%4];" : "=f"(v.x), "=f"(v.y), "=f"(v.z), "=f"(v.w) : "r"(a) : "memory");
  return v;
}
__device__ __forceinline__ void norm_pack(uint32_t* p, const float* d, const float4& i) {
  p[0] = pack2(d[0] * i.x, d[1] * i.y); p[1] = pack2(d[4] * i.z, d[5] * i.w);
  p[2] = pack2(d[2] * i.x, d[3] * i.y); p[3] = pack2(d[6] * i.z, d[7] * i.w);
  asm volatile("" : "+r"(p[0]), "+r"(p[1]), "+r"(p[2]), "+r"(p[3])::"memory");
}
template <int W>
__device__ __forceinline__ void pack_first(uint32_t (&pk)[60], const float (&om)[80], const float (&oh)[40], uint32_t laddr) {
  float4 n0 = lds_f4(laddr + W * 80), n1 = lds_f4(laddr + W * 80 + 16);
#pragma unroll
  for (int J = 0; J < 5; J++) {
    const float4 i = n0;
    n0 = n1;
    if (J + 2 < 5) n1 = lds_f4(laddr + W * 80 + (J + 2) * 16);
    norm_pack(&pk[20 + 4 * J], &om[8 * (5 * W + J)], i);
    norm_pack(&pk[4 * J], &oh[8 * J], i);
  }
}
template <int W, int J0, int J1>
__device__ __forceinline__ void pack_second(uint32_t (&pk)[60], const float (&om)[80], uint32_t laddr) {
  float4 n[J1 - J0];
#pragma unroll
  for (int J = J0; J < J1; J++) n[J - J0] = lds_f4(laddr + (1 - W) * 80 + J * 16);
#pragma unroll
  for (int J = J0; J < J1; J++) norm_pack(&pk[40 + 4 * J], &om[8 * (5 * (1 - W) + J)], n[J - J0]);
}
__device__ __forceinline__ char* o_ptr(int item) {
  const uint32_t t = tid_x();
  return o_slot(item) + ((t & 96) * 16 + (t & 28) * 8 + ((((t >> 1) ^ (t >> 4)) & 1) << 4) + (t & 1) * 8);
}
template <int W, int G0, int G1>
__device__ __forceinline__ void store_groups(char* op, const uint32_t (&pk)[60], uint32_t on) {
#pragma unroll
  for (int G = G0; G < G1; G++) {
    const int off = (G < 5 ? 1 : 2 * W) * B_SLOT + (5 * (G < 10 ? W : 1 - W) + G % 5) * 2048;
    asm volatile("{\n.reg .pred p;\nsetp.ne.u32 p, %5, 0;\n@p st.global.v2.b32 [%0], {%1, %2};\n@p st.global.v2.b32 [%0+256], {%3, %4};\n}\n"
                 ::"l"(op + off), "r"(pk[4 * G]), "r"(pk[4 * G + 1]), "r"(pk[4 * G + 2]), "r"(pk[4 * G + 3]), "r"(on) : "memory");
  }
}
__device__ __forceinline__ void publish_generic(uint32_t bar, int lane) {
  __syncwarp();
  mbar_arrive_if0(bar, lane);
}
__device__ __forceinline__ void publish(uint32_t bar, int lane) {
  proxy_fence();
  __syncwarp();
  mbar_arrive_if0(bar, lane);
}

#define A_ADDR(s) (SB + OFF_A + (s) * A_SLOT)
#define B_ADDR(s) (SB + OFF_B + (s) * B_SLOT)
#define WAIT_CHUNK(c, ro, sA)                \
  uint32_t sA;                               \
  {                                          \
    uint32_t pA_;                            \
    ring_pos(ring, (ro) + (c), sA, pA_);     \
    mbar_wait(bud, BAR_FULLA + sA * 8, pA_); \
  }
#define RELEASE_CHUNK(c, sA)                                  \
  mbar_arrive_if0(BAR_EMPTYA + (sA) * 8, tid);                \
  if ((c) < NSLOT) mbar_arrive_if0(BAR_EMPTYB + xs(c) * 8, tid);

template <int W>
__device__ __forceinline__ int attn_consumer(int item) {
  int bud = WAIT_BUDGET;
  const int tid = threadIdx.x & 127, lane = tid & 31, warp = tid >> 5;
  const uint32_t st_off = ((lane & 7) + 8 * (lane >> 4)) * 128 + (((2 * warp + ((lane >> 3) & 1)) ^ (lane & 7)) << 4);
  const uint32_t laddr = SB + OFF_L + (lane & 3) * 160;
  float om[80], oh[40], sacc[80];
  uint32_t pk[60];
#pragma unroll
  for (int i = 0; i < 40; i++) pk[i] = 0;
  zero_regs(om);
  Ring ring{0u, 0u};
  uint32_t par = 0;
  int prev = 0;
  const float qscale = 0.07216878364870322f * 1.4426950408889634f;
  constexpr uint32_t pown = B_ADDR(3 + W), poth = B_ADDR(4 - W);
  TL(0); TLG(62);
  {
    WAIT_CHUNK(0, 0, s0)
    wg_fence();
    mma_both<W, false>(sacc, oh, A_ADDR(s0), B_ADDR(xs(0)));
    wg_commit();
    WAIT_CHUNK(1, 0, s1)
    wg_fence();
    mma_both<W, true>(sacc, oh, A_ADDR(s1), B_ADDR(xs(1)));
    wg_commit();
    wg_wait<1>();
    RELEASE_CHUNK(0, s0)
  }
#pragma unroll 1
  for (int it = 0;; it++) {
    char* op = o_ptr(prev);
#pragma unroll
    for (int c = 2; c < 8 - W; c++) {
      WAIT_CHUNK(c, 0, sA)
      TL(40 + c);
      wg_fence();
      mma_both<W, true>(sacc, oh, A_ADDR(sA), B_ADDR(xs(c)));
      wg_commit();
      wg_wait<1>();
      uint32_t sP, pP;
      ring_pos(ring, c - 1, sP, pP);
      RELEASE_CHUNK(c - 1, sP)
      constexpr int NG = W == 0 ? 3 : W1_NG;
      if (c == 2) { pack_second<W, 0, 1>(pk, om, laddr); store_groups<W, 0 * NG, 1 * NG>(op, pk, it); }
      if (c == 3) { pack_second<W, 1, 2>(pk, om, laddr); store_groups<W, 1 * NG, 2 * NG>(op, pk, it); }
      if (c == 4) { pack_second<W, 2, 3>(pk, om, laddr); store_groups<W, 2 * NG, 3 * NG>(op, pk, it); }
      if (c == 5) { pack_second<W, 3, 4>(pk, om, laddr); store_groups<W, 3 * NG, 4 * NG>(op, pk, it); }
      if (c == 6) {
        pack_second<W, 4, 5>(pk, om, laddr);
        if (W == 1) {
          wg_wait<0>();
          RELEASE_CHUNK(6, sA)
          mbar_arrive_if0(BAR_XDONE, tid);
        }
        store_groups<W, 4 * NG, 15>(op, pk, it);
        __syncwarp();
        mbar_arrive_if0(BAR_OFULL, lane | (it == 0));
      }
    }
    uint32_t sK0, pK0, s7, p7;
    ring_pos(ring, idxK(W), sK0, pK0);
    ring_pos(ring, 7, s7, p7);
    if (W == 1) mbar_wait(bud, BAR_FULLA + s7 * 8, p7);
    WAIT_CHUNK(8, 0, s8)
    WAIT_CHUNK(9, 0, s9)
    TL(48);
    if (W == 0) {
      wg_fence();
      mma_mid<W, true>(oh, A_ADDR(s8), B_ADDR(xs(8)));
      mma_mid<W, true>(oh, A_ADDR(s9), B_ADDR(xs(9)));
      wg_commit();
      wg_wait<1>();
      RELEASE_CHUNK(7, s7)
      wg_fence();
      mma_main<W, true>(sacc, A_ADDR(s8), B_ADDR(xs(8)));
      mma_main<W, true>(sacc, A_ADDR(s9), B_ADDR(xs(9)));
      wg_commit();
      bar_arrive(5, 256);
      TL(49);
      wg_wait<1>();
      reg_fence(oh);
      mbar_wait(bud, BAR_XDONE, par);
      store_scaled(B_ADDR(1) + st_off, oh, qscale);
    } else {
      bar_sync(5, 256);
      wg_fence();
      mma_mid<W, true>(oh, A_ADDR(s7), B_ADDR(xs(7)));
      mma_mid<W, true>(oh, A_ADDR(s8), B_ADDR(xs(8)));
      mma_mid<W, true>(oh, A_ADDR(s9), B_ADDR(xs(9)));
      wg_commit();
      mma_main<W, true>(sacc, A_ADDR(s7), B_ADDR(xs(7)));
      wg_commit();
      mma_main<W, true>(sacc, A_ADDR(s8), B_ADDR(xs(8)));
      wg_commit();
      wg_wait<2>();
      reg_fence(oh);
      store_scaled(B_ADDR(1) + 10240 + st_off, oh, qscale);
      wg_fence();
      mma_main<W, true>(sacc, A_ADDR(s9), B_ADDR(xs(9)));
      wg_commit();
      bar_arrive(8, 256);
      TL(49);
      wg_wait<2>();
      RELEASE_CHUNK(7, s7)
      publish(BAR_QH, lane);
    }
    wg_wait<0>();
    reg_fence(sacc);
    TL(1);
    RELEASE_CHUNK(8, s8)
    RELEASE_CHUNK(9, s9)
    store_scaled(B_ADDR(2 * W) + st_off, sacc, qscale);
    if (W == 1) publish(BAR_QM, lane); else proxy_fence();
    TL(2);
    uint32_t sK = sK0, sV1 = 0;
    if (W == 0) {
      zero_regs(om); zero_regs(oh);
      reg_fence(om); reg_fence(oh);
      mbar_wait(bud, BAR_FULLA + sK0 * 8, pK0);
      bar_sync(8, 256);
      wg_fence();
      s_mma<0, false>(sacc, A_ADDR(sK));
      mbar_wait(bud, BAR_QH, par);
      TL(3);
      wg_fence();
      s_mma<1, true>(sacc, A_ADDR(sK));
      mbar_wait(bud, BAR_QM, par);
      TL(5);
      wg_fence();
      s_mma<2, true>(sacc, A_ADDR(sK));
      wg_commit();
      wg_commit();
      bar_arrive(2, 256);
    } else {
      uint32_t pV1;
      ring_pos(ring, idxV(0), sV1, pV1);
      mbar_wait(bud, BAR_FULLA + sK * 8, pK0);
      bar_sync(2, 256);
      wg_fence();
      s_mma<0, false>(sacc, A_ADDR(sK));
      s_mma<1, true>(sacc, A_ADDR(sK));
      s_mma<2, true>(sacc, A_ADDR(sK));
      wg_commit();
      TL(6);
      mbar_wait(bud, BAR_FULLA + sV1 * 8, pV1);
      mbar_wait(bud, BAR_PFULL, 0);
      TL(7);
      wg_fence();
      mma_both<W, false>(om, oh, A_ADDR(sV1), poth);
      wg_commit();
      bar_arrive(1, 256);
    }
    Ring rv;
    ring_pos(ring, idxV(W), rv.s0, rv.ph0);
#pragma unroll 1
    for (int jj = 0;; jj++) {
      wg_wait<1>();
      reg_fence(sacc);
      TL(8 + jj * 7);
      mbar_arrive2_if0(BAR_EMPTYA + sK * 8, tid);
      mbar_arrive_if0(BAR_EMPTYB + tid * 8, (tid >= 3) | (jj != 3));
#pragma unroll
      for (int J = 0; J < 10; J++) {
        stsm_t(pown + st_off + J * 2048, pack2(ex2(sacc[8 * J]), ex2(sacc[8 * J + 1])), pack2(ex2(sacc[8 * J + 2]), ex2(sacc[8 * J + 3])),
               pack2(ex2(sacc[8 * J + 4]), ex2(sacc[8 * J + 5])), pack2(ex2(sacc[8 * J + 6]), ex2(sacc[8 * J + 7])));
        if (W == 1 && (J == 2 || J == 5)) publish_generic(BAR_PMID + (J / 3) * 8, lane | (jj != 3));
        if (J == 4) {
          wg_wait<0>();
          mbar_arrive_if0(BAR_EMPTYA + sV1 * 8, tid | (W == 0 && jj == 0));
        }
      }
      publish(BAR_PFULL + W * 8, lane);
      TL(10 + jj * 7);
      if (jj == 3) break;
      uint32_t pK, pV1;
      ring_pos(rv, 1, sK, pK);
      ring_pos(rv, 2, sV1, pV1);
      mbar_wait(bud, BAR_FULLA + rv.s0 * 8, rv.ph0);
      bar_sync(1 + W, 256);
      wg_fence();
      mma_both<W, true>(om, oh, A_ADDR(rv.s0), pown);
      wg_commit();
      mbar_wait(bud, BAR_FULLA + sK * 8, pK);
      TL(11 + jj * 7);
      wg_fence();
      s_mma<0, false>(sacc, A_ADDR(sK));
      s_mma<1, true>(sacc, A_ADDR(sK));
      wg_commit();
      wg_wait<1>();
      mbar_arrive_if0(BAR_EMPTYA + rv.s0 * 8, tid);
      wg_fence();
      s_mma<2, true>(sacc, A_ADDR(sK));
      wg_commit();
      TL(13 + jj * 7);
      mbar_wait(bud, BAR_FULLA + sV1 * 8, pV1);
      mbar_wait(bud, BAR_PFREE + W * 8, jj & 1);
      mbar_wait(bud, BAR_PFULL + (1 - W) * 8, (jj + W) & 1);
      TL(14 + jj * 7);
      wg_fence();
      mma_both<W, true>(om, oh, A_ADDR(sV1), poth);
      wg_commit();
      bar_arrive(2 - W, 256);
      ring_advance(rv, 4);
    }
    uint32_t sV7, pV7;
    ring_pos(ring, idxV(7), sV7, pV7);
    prev = item;
    if (W == 1 && !DEBUG_TIMEOUT) item = next_item();
    if (W == 0) {
      uint32_t sV6, pV6;
      ring_pos(ring, idxV(6), sV6, pV6);
      mbar_wait(bud, BAR_FULLA + sV6 * 8, pV6);
      bar_sync(1, 256);
      wg_fence();
      mma_both<0, true>(om, oh, A_ADDR(sV6), pown);
      wg_commit();
      mbar_wait(bud, BAR_FULLA + sV7 * 8, pV7);
      wg_wait<0>();
      mbar_arrive_if0(BAR_EMPTYA + sV6 * 8, tid);
      mbar_wait(bud, BAR_PFULL + 8, 1);
      wg_fence();
      mma_both<0, true>(om, oh, A_ADDR(sV7), poth);
      wg_commit();
      bar_arrive(6, 256);
    } else {
      mbar_wait(bud, BAR_FULLA + sV7 * 8, pV7);
      bar_sync(6, 256);
    }
    TL(32);
    if (DEBUG_TIMEOUT) item = next_item(NEXT_ITEM + 4);
    else if (W == 0) item = next_item();
    if (item >= NITEMS) {
      if (W == 1) {
        wg_fence();
        mma_both<1, true>(om, oh, A_ADDR(sV7), pown);
        wg_commit();
      }
      wg_wait<0>();
      reg_fence(om); reg_fence(oh);
      TL(33);
      mbar_wait(bud, BAR_LFULL, par);
      mbar_arrive_if0(BAR_FREE, tid);
      TL(34);
      pack_first<W>(pk, om, oh, laddr);
      op = o_ptr(prev);
      store_groups<W, 0, 10>(op, pk, 1);
      pack_second<W, 0, 5>(pk, om, laddr);
      store_groups<W, 10, 15>(op, pk, 1);
      publish_generic(BAR_OFULL, lane);
      TL(35); TLG(63);
      TL_FLUSH();
      return item;
    }
    {
      if (W == 1) {
        wg_fence();
        mma_both<1, true>(om, oh, A_ADDR(sV7), pown);
        wg_commit();
      }
      WAIT_CHUNK(0, 26, s0)
      WAIT_CHUNK(1, 26, s1)
      if (W == 0) {
        wg_wait<0>();
        reg_fence(om); reg_fence(oh);
        TL(33);
        wg_fence();
        mma_main<W, false>(sacc, A_ADDR(s0), B_ADDR(xs(0)));
        wg_commit();
      } else {
        wg_fence();
        mma_main<W, false>(sacc, A_ADDR(s0), B_ADDR(xs(0)));
        mma_main<W, true>(sacc, A_ADDR(s1), B_ADDR(xs(1)));
        wg_commit();
        wg_wait<1>();
        reg_fence(om); reg_fence(oh);
        TL(33);
      }
      mbar_arrive_if0(BAR_EMPTYA + sV7 * 8, tid);
      mbar_wait(bud, BAR_LFULL, par);
      mbar_arrive_if0(BAR_EMPTYB + 24 + tid * 8, tid >= 2);
      TL(34);
      pack_first<W>(pk, om, oh, laddr);
      TL(36);
      wg_fence();
      mma_mid<W, false>(oh, A_ADDR(s0), B_ADDR(xs(0)));
      wg_commit();
      mma_mid<W, true>(oh, A_ADDR(s1), B_ADDR(xs(1)));
      if (W == 0) mma_main<W, true>(sacc, A_ADDR(s1), B_ADDR(xs(1)));
      wg_commit();
      TL(37);
      wg_wait<1>();
      RELEASE_CHUNK(0, s0)
      TL(35); TLG(63);
    }
    TL_FLUSH();
    TL(0); TLG(62);
    ring_advance(ring, 26);
    par ^= 1;
  }
}

__device__ __forceinline__ uint4 lds128(uint32_t a) {
  uint4 v;
  asm volatile("ld.shared.v4.b32 {%0,%1,%2,%3}, [%4];" : "=r"(v.x), "=r"(v.y), "=r"(v.z), "=r"(v.w) : "r"(a) : "memory");
  return v;
}
__device__ __forceinline__ void acc2(float& s, float& t, uint32_t w) {
  s += __uint_as_float(w << 16);
  t += __uint_as_float(w & 0xffff0000u);
}
__device__ __forceinline__ uint32_t badd2(uint32_t a, uint32_t b) { uint32_t r; asm("add.rn.bf16x2 %0, %1, %2;" : "=r"(r) : "r"(a), "r"(b)); return r; }
__device__ __forceinline__ void sum_unit(float& acc, uint32_t pb) {
  const uint4 v0 = lds128(pb), v1 = lds128(pb ^ 32), v2 = lds128(pb ^ 64), v3 = lds128(pb ^ 96);
  const uint32_t w0 = badd2(v0.x, v0.y), w1 = badd2(v0.z, v0.w);
  float s0 = acc + __uint_as_float(w0 << 16), t0 = __uint_as_float(w0 & 0xffff0000u);
  float s1 = __uint_as_float(w1 << 16), t1 = __uint_as_float(w1 & 0xffff0000u);
  acc2(s0, t0, badd2(v1.x, v1.y)); acc2(s1, t1, badd2(v1.z, v1.w));
  acc2(s0, t0, badd2(v2.x, v2.y)); acc2(s1, t1, badd2(v2.z, v2.w));
  acc2(s0, t0, badd2(v3.x, v3.y)); acc2(s1, t1, badd2(v3.z, v3.w));
  acc = (s0 + t0) + (s1 + t1);
}
__device__ __forceinline__ float bf_lo(uint32_t w) { return __uint_as_float(w << 16); }
__device__ __forceinline__ float bf_hi(uint32_t w) { return __uint_as_float(w & 0xffff0000u); }
__device__ __forceinline__ float bf_rn(float x) { return __bfloat162float(__float2bfloat16(x)); }
__device__ __forceinline__ void slow_item(const Params& p, int item, int hw) {
  const int blk = item >> 9, h = (item >> 4) & 31, b = item & 15;
#pragma unroll 1
  for (int n = hw; n < SQ; n += 3) {
    float q[6] = {0.f, 0.f, 0.f, 0.f, 0.f, 0.f};
    {
      const uint32_t* xr = (const uint32_t*)(p.xp[blk] + (size_t)(b * SQ + n) * DM);
      const uint32_t* wq = (const uint32_t*)(p.wqp[blk] + h * DH) + (tid_x() & 31);
#pragma unroll 2
      for (int k = 0; k < DM / 2; k++) {
        const uint32_t xv = xr[k];
#pragma unroll
        for (int i = 0; i < 3; i++) {
          const uint32_t w0 = wq[i * 32], w1 = wq[NH * DH / 2 + i * 32];
          q[2 * i] = fmaf(bf_lo(xv), bf_lo(w0), fmaf(bf_hi(xv), bf_lo(w1), q[2 * i]));
          q[2 * i + 1] = fmaf(bf_lo(xv), bf_hi(w0), fmaf(bf_hi(xv), bf_hi(w1), q[2 * i + 1]));
        }
        wq += NH * DH;
      }
    }
    const uint32_t q0 = pack2(q[0], q[1]), q1 = pack2(q[2], q[3]), q2 = pack2(q[4], q[5]);
    float o[6] = {0.f, 0.f, 0.f, 0.f, 0.f, 0.f}, m = -INFINITY, l = 0.f;
    const uint32_t* kg = (const uint32_t*)(p.kp[blk] + (size_t)(b * NH + h) * SK * DH) + (tid_x() & 31);
    const uint32_t* vg = (const uint32_t*)(p.vp[blk] + (size_t)(b * NH + h) * SK * DH) + (tid_x() & 31);
#pragma unroll 1
    for (int k = 0; k < SK; k++) {
      const uint32_t k0 = kg[0], k1 = kg[32], k2 = kg[64], v0 = vg[0], v1 = vg[32], v2 = vg[64];
      kg += DH / 2; vg += DH / 2;
      float sc = fmaf(bf_lo(q0), bf_lo(k0), bf_hi(q0) * bf_hi(k0));
      sc = fmaf(bf_lo(q1), bf_lo(k1), fmaf(bf_hi(q1), bf_hi(k1), sc));
      sc = fmaf(bf_lo(q2), bf_lo(k2), fmaf(bf_hi(q2), bf_hi(k2), sc));
#pragma unroll
      for (int d = 16; d; d >>= 1) sc += __shfl_xor_sync(0xffffffffu, sc, d);
      sc = bf_rn(bf_rn(sc) * 0.07216878364870322f);
      const float mn = fmaxf(m, sc), a = ex2((m - mn) * 1.4426950408889634f), pr = ex2((sc - mn) * 1.4426950408889634f);
      m = mn;
      l = fmaf(l, a, pr);
      o[0] = fmaf(o[0], a, pr * bf_lo(v0)); o[1] = fmaf(o[1], a, pr * bf_hi(v0));
      o[2] = fmaf(o[2], a, pr * bf_lo(v1)); o[3] = fmaf(o[3], a, pr * bf_hi(v1));
      o[4] = fmaf(o[4], a, pr * bf_lo(v2)); o[5] = fmaf(o[5], a, pr * bf_hi(v2));
    }
    float inv;
    asm("rcp.approx.ftz.f32 %0, %1;" : "=f"(inv) : "f"(l));
    const int lane = tid_x() & 31;
    const int r = n & 15, c = 4 * ((r & 7) >> 1) + 2 * (r >> 3) + (r & 1);
    char* on = o_slot(item) + (lane >> 2) * 256 + (lane & 3) * 64 + (n >> 4) * 2048 +
               (((c >> 3) ^ ((lane >> 1) & 1)) << 4) + (c & 7) * 2;
#pragma unroll
    for (int i = 0; i < 3; i++) {
      *(__nv_bfloat16*)(on + i * B_SLOT) = __float2bfloat16(o[2 * i] * inv);
      *(__nv_bfloat16*)(on + i * B_SLOT + 32) = __float2bfloat16(o[2 * i + 1] * inv);
    }
  }
}
__device__ __forceinline__ void attn_helper(const Params& p, int hw, int item, int epoch) {
  int bud = WAIT_BUDGET;
  if (item < PF_N && hw < 2) {
    const char* g = (const char*)(hw ? p.vp[0] : p.kp[0]) + (size_t)(((item & 15) * NH + (item >> 4)) * SK) * DH * 2;
    const long long t0 = clock64();
#pragma unroll 1
    for (int i = 0; i < 32; i++) {
      while (clock64() - t0 < PF_WAIT + i * PF_GAP) __nanosleep(50);
      for (int k = 0; k < 6; k++) asm volatile("prefetch.global.L2 [%0];" ::"l"(g + i * 6144 + k * 1024 + (tid_x() & 31) * 32));
      __syncwarp();
    }
  }
#pragma unroll 1
  for (int it = 0; item < NITEMS; it++) {
    const uint32_t par = it & 1;
    int lane = tid_x() & 31;
    const int r = lane >> 1;
    const uint32_t a0 = B_ADDR(3) + (16 * hw + r) * 128 + (lane & 1) * 16 + ((r & 3) << 5);
    float acc[4] = {0.f, 0.f, 0.f, 0.f};
#pragma unroll 1
    for (int j = 0; j < 8; j++) {
      const uint32_t pb = a0 + (j & 1) * B_SLOT, bfull = BAR_PFULL + (j & 1) * 8, pfull = (j >> 1) & 1;
      mbar_wait(bud, j == 7 ? BAR_PMID : bfull, j == 7 ? par : pfull);
      sum_unit(acc[0], pb);
      if (j == 7) mbar_wait(bud, BAR_PMID + 8, par);
      sum_unit(acc[1], pb + 6144);
      if (j == 7) mbar_wait(bud, bfull, pfull);
      sum_unit(acc[2], pb + 2 * 6144);
      if (hw == 0) sum_unit(acc[3], pb + 3 * 6144);
      __syncwarp();
      mbar_arrive_if0(BAR_PFREE + (j & 1) * 8, lane);
      if (j == 5 && hw == 2) {
        if (lane == 0) TLP(60);
        if (item >= ORING && item < OFRESH) flag_wait(bud, &g_done[item - ORING], (epoch + 1) * 2);
        if (lane == 0) TLP(61);
      }
    }
    bool bad = false;
    const uint32_t la = SB + OFF_L + (((r & 7) >> 1) * 40 + 2 * (r >> 3) + (r & 1) + 4 * hw) * 4;
#pragma unroll
    for (int u = 0; u < 4; u++) {
      const float l = acc[u] + __shfl_xor_sync(0xffffffffu, acc[u], 1);
      if (u < 3 || hw == 0) {
        bad |= !(l >= 8.8817841970012523e-16f && l <= 1.125899906842624e15f);
        float inv;
        asm("rcp.approx.ftz.f32 %0, %1;" : "=f"(inv) : "f"(l));
        asm volatile("st.shared.f32 [%0], %1;" ::"r"(la + u * 48), "f"(inv) : "memory");
      }
    }
    publish_generic(BAR_LFULL, lane);
    if (lane == 0) TLP(40 + hw * 4);
    uint32_t anybad;
    asm volatile("{\n.reg .pred p, q;\nsetp.ne.u32 p, %1, 0;\nbarrier.red.or.pred q, 7, 96, p;\nselp.u32 %0, 1, 0, q;\n}\n"
                 : "=r"(anybad) : "r"((uint32_t)bad) : "memory");
    if (__any_sync(0xffffffffu, anybad)) {
      mbar_wait(bud, BAR_OFULL, par);
      slow_item(p, item, hw);
      bar_sync(7, 96);
    }
    if (hw == 1) {
      mbar_wait(bud, BAR_OFULL, par);
      if ((tid_x() & 31) == 0) {
        TLP(41 + hw * 4);
        asm volatile("red.release.gpu.global.add.s32 [%0], 1;" ::"l"(&g_ready[item]) : "memory");
        TLP(42 + hw * 4);
      }
      __syncwarp();
    }
    item = next_item();
  }
}

__device__ __forceinline__ int attn_producer(const Params& p, int item) {
  int bud = WAIT_BUDGET;
  uint32_t sa = 0, pa = 1;
  const uint64_t pol = evict_first_policy();
  const bool draws = item >= N_OCTA;
  const int delay = start_delay(item);
  {
    const long long t0 = clock64();
    while (clock64() - t0 < delay) __nanosleep(100);
  }
#pragma unroll 1
  for (int it = 0; item < NITEMS; it++) {
    const int blk = item >> 9, h = (item >> 4) & 31, b = item & 15;
    const int row0 = (b * NH + h) * SK;
#pragma unroll
    for (int c = 0; c < 10; c++) {
      if (c >= NSLOT || (it | delay)) {
        mbar_wait(bud, BAR_EMPTYA + sa * 8, pa);
        TLP(c);
        mbar_expect(BAR_FULLA + sa * 8, A_SLOT + B_SLOT);
        tma3d(A_ADDR(sa), &p.wq[blk], BAR_FULLA + sa * 8, 0, c * 64, h * 3);
        mbar_wait(bud, BAR_EMPTYB + xs(c) * 8, c < NSLOT);
        TLP(10 + c);
        tma2d(B_ADDR(xs(c)), &p.x[blk], BAR_FULLA + sa * 8, c * 64, b * SQ);
      }
      if (++sa == NSLOT) { sa = 0; pa ^= 1; }
    }
#pragma unroll
    for (int i = 0; i < 16; i++) {
      const bool isK = (i == 0) || ((i & 1) && i < 15);
      const int j = i == 0 ? 0 : (i == 15 ? 7 : (isK ? (i + 1) >> 1 : (i - 2) >> 1));
      mbar_wait(bud, BAR_EMPTYA + sa * 8, pa);
      TLP(20 + i);
      if (i == 11) item = draws ? NCTA + (int)atomicInc(&g_ticket, NITEMS - NCTA + N_ATT - 1) : NITEMS;
      if (i == 13) asm volatile("st.shared.s32 [%0], %1;" ::"r"(NEXT_ITEM), "r"(item) : "memory");
      mbar_expect(BAR_FULLA + sa * 8, A_SLOT);
      tma3d_hint(A_ADDR(sa), isK ? &p.k[blk] : &p.v[blk], BAR_FULLA + sa * 8, 0, row0 + j * 64, 0, pol);
      if (++sa == NSLOT) { sa = 0; pa ^= 1; }
    }
  }
  return item;
}

struct OJob { int tile, part, c0, n; };
__device__ __forceinline__ OJob get_ojob(int cta, int last) {
  if (cta < N_OCTA) return OJob{O_PAIR ? ((cta & 15) << 1) | (cta >> 4) : cta, 0, 0, 3 * STEP1};
  const int u = last - NITEMS, part = 1 + (u >> 5), tile = part == 3 ? 95 - u : u & 31;
  const int c1 = 3 * STEP1, c2 = c1 + LEN1 - ((tile * LSLOPE1 + 16) >> 5), c3 = c2 + LEN2 - ((tile * LSLOPE2 + 16) >> 5);
  return OJob{tile, part, part == 1 ? c1 : part == 2 ? c2 : c3, part == 1 ? c2 - c1 + 1 : part == 2 ? c3 - c2 + 1 : part == 3 ? 189 - c3 + 1 : 0};
}
__device__ __forceinline__ uint32_t first_stage(const OJob& job) { return (uint32_t)(300 - job.n) % 3; }

template <int W>
__device__ __forceinline__ void oproj_consumer(const Params& p, const OJob job) {
  int bud = WAIT_BUDGET;
  const int tid = threadIdx.x & 127, lane = tid & 31, warp = tid >> 5;
  const int qrow = 8 * ((lane >> 1) & 1) + 4 * (lane >> 4) + 2 * ((lane >> 2) & 1) + (lane & 1);
  const uint32_t st_off = qrow * 128 + (((2 * warp + ((lane >> 3) & 1)) ^ (qrow & 7)) << 4);
  float a0[80], a1[80], ah[40];
  zero_regs(a0); zero_regs(a1); zero_regs(ah);
  int left = job.n, step = 0;
  uint32_t st = first_stage(job), ph = 0;
#pragma unroll 1
  while (left) {
    const int nc = left > 3 * NH ? 3 * NH : left;
    left -= nc;
#pragma unroll 1
    for (int c = 0; c < nc; c++) {
      mbar_wait(bud, BAR_GFULL + st * 8, (ph >> st) & 1);
      ph ^= 1 << st;
      wg_fence();
      const uint32_t la = lo_sw(SB + st * O_STAGE), lb = lo_o(SB + st * O_STAGE + O_AB);
#define O_STEP(ks, sc)                                                        \
  mma80r<1, 1, 2 * 8192 + ks * 2048, W * 10240 + ks * 512>(ah, la, lb, sc);   \
  mma160r<1, 1, (W * 3) * 8192 + ks * 2048, ks * 512>(a0, la, lb, sc);        \
  mma160r<1, 1, (W * 3 + 1) * 8192 + ks * 2048, ks * 512>(a1, la, lb, sc);
      O_STEP(0, c != 0) O_STEP(1, 1)
      wg_commit();
      wg_wait<1>();
      mbar_arrive_if0(BAR_GEMPTY + (st == 0 ? 2 : st - 1) * 8, tid | (c == 0));
      wg_fence();
      O_STEP(2, 1) O_STEP(3, 1)
#undef O_STEP
      wg_commit();
      if (++st == 3) {
        st = 0;
        if (W == 0)
          asm volatile("{\n.reg .pred p;\nsetp.eq.u32 p, %1, 0;\n@p red.relaxed.gpu.global.add.s32 [%0], 1;\n}\n"
                       ::"l"(&g_done[step * 16 + (job.tile >> 1)]), "r"(tid | job.part) : "memory");
        TLG(step);
        step++;
      }
    }
    wg_wait<0>();
    reg_fence(a0); reg_fence(a1); reg_fence(ah);
    const uint32_t sg = SB + O_OUT + st_off;
    if (W == 1) {
      bar_arrive(3, 256);
      store_scaled(sg + 3 * B_SLOT, a0, 1.0f);
      publish(BAR_GOUT + 24, lane);
      bar_sync(9, 256);
      store_scaled(sg + 2 * B_SLOT + 10240, ah, 1.0f);
      publish(BAR_GOUT + 16, lane);
      store_scaled(sg + 4 * B_SLOT, a1, 1.0f);
      publish(BAR_GOUT + 32, lane);
    } else {
      bar_arrive(9, 256);
      bar_sync(3, 256);
      store_scaled(sg, a0, 1.0f);
      publish(BAR_GOUT, lane);
      store_scaled(sg + B_SLOT, a1, 1.0f);
      publish(BAR_GOUT + 8, lane);
      store_scaled(sg + 2 * B_SLOT, ah, 1.0f);
      publish(BAR_GOUT + 16, lane);
    }
  }
  TL_FLUSH();
  TLG(0);
  float acc[7][8];
  uint32_t in[7], blk[7];
#pragma unroll
  for (int i = 0; i < 7; i++) {
    const int e = min(i * 256 + W * 128 + tid, 1599), r = e / 40, cc = e % 40;
    in[i] = r * 128 + (((cc ^ r) & 7) << 4);
    blk[i] = cc >> 3;
#pragma unroll
    for (int k = 0; k < 8; k++) acc[i][k] = 0.f;
  }
  bar_sync(10, 256);
#pragma unroll 1
  for (int q = 0; q < 4; q++) {
    if (q) mbar_wait(bud, BAR_GRED + (q - 1) * 8, 0);
    if (q == 3) TLG(1);
    const uint32_t base = q ? SB + (q - 1) * 25600 : SB + O_OUT + job.part * 5120, bs = q ? 5120 : B_SLOT;
    uint4 v[7];
#pragma unroll
    for (int i = 0; i < 7; i++) v[i] = lds128(base + blk[i] * bs + in[i]);
#pragma unroll
    for (int i = 0; i < 7; i++) {
      acc[i][0] += bf_lo(v[i].x); acc[i][1] += bf_hi(v[i].x); acc[i][2] += bf_lo(v[i].y); acc[i][3] += bf_hi(v[i].y);
      acc[i][4] += bf_lo(v[i].z); acc[i][5] += bf_hi(v[i].z); acc[i][6] += bf_lo(v[i].w); acc[i][7] += bf_hi(v[i].w);
    }
  }
  uint4* go = (uint4*)p.outp + ((job.tile >> 1) * SQ + job.part * 40) * (2 * DM / 8) + DM / 8 + (job.tile & 1) * 40;
#pragma unroll
  for (int i = 0; i < 7; i++) {
    const int r = in[i] >> 7, cc = blk[i] * 8 + (((in[i] >> 4) ^ r) & 7);
    if (i * 256 + W * 128 + tid < 1600)
      go[r * (2 * DM / 8) + cc] = make_uint4(pack2(acc[i][0], acc[i][1]), pack2(acc[i][2], acc[i][3]), pack2(acc[i][4], acc[i][5]), pack2(acc[i][6], acc[i][7]));
  }
  TLG(2);
  TL_FLUSH();
}

__device__ __forceinline__ void oproj_producer(const Params& p, const OJob job, int target) {
  int bud = WAIT_BUDGET;
  const uint64_t polo = evict_first_policy();
  mbar_wait(bud, BAR_FREE, 0);
  uint32_t st = first_stage(job), ph = 7;
  int seen = -1;
#pragma unroll 1
  for (int i = 0; i < job.n; i++) {
    const int c = job.part && i == job.n - 1 ? 188 + job.part : job.c0 + i, step = c / 3, kb = c - 3 * step;
    const int item = step * 16 + (job.tile >> 1);
    if (step != seen) {
      flag_wait(bud, &g_ready[item], target);
      asm volatile("fence.proxy.async.global;" ::: "memory");
      seen = step;
    }
    const uint32_t dst = SB + st * O_STAGE, bar = BAR_GFULL + st * 8;
    const char* og = o_slot(item) + kb * B_SLOT;
    mbar_wait(bud, BAR_GEMPTY + st * 8, (ph >> st) & 1);
    ph ^= 1 << st;
    mbar_expect(bar, O_STAGE);
    tma3d(dst, &p.wo[step >> 5], bar, 0, (c - (step >> 5) * 3 * NH) * 64, (job.tile & 1) * 5);
    bulk_load_hint(dst + O_AB, og, B_SLOT, bar, polo);
    if (++st == 3) st = 0;
  }
  mbar_wait(bud, BAR_GEMPTY, ph & 1);
  mbar_wait(bud, BAR_GEMPTY + 8, (ph >> 1) & 1);
  uint32_t todo = 15 & ~(1 << job.part), dst = SB, bar = BAR_GRED;
  while (todo) {
#pragma unroll 1
    for (int q = 0; q < 4; q++) {
      if (!((todo >> q) & 1)) continue;
      int v;
      asm volatile("ld.acquire.gpu.global.s32 %0, [%1];" : "=r"(v) : "l"(&g_pcnt[job.tile * 4 + q]) : "memory");
      if (v - target < 0 && --bud > 0) continue;
      asm volatile("fence.proxy.async.global;" ::: "memory");
      mbar_expect(bar, 25600);
      for (int k = 0; k < 5; k++)
        tma2d(dst + k * 5120, &p.part, bar, (job.tile & 1) * 320 + k * 64, q * NB * SQ + (job.tile >> 1) * SQ + job.part * 40);
      todo &= ~(1 << q);
      dst += 25600;
      bar += 8;
    }
  }
}

__device__ __forceinline__ void oproj_storer(const Params& p, const OJob job) {
  int bud = WAIT_BUDGET;
  const int col = (job.tile & 1) * 320, row = (job.tile >> 1) * SQ;
  if (job.part == 0) {
    for (int k = 0; k < 3; k++) {
      mbar_wait(bud, BAR_GOUT + k * 8, 0);
      tma_store2d(&p.out, SB + O_OUT + k * B_SLOT, col + k * 64, row);
    }
    asm volatile("cp.async.bulk.commit_group;" ::: "memory");
    asm volatile("cp.async.bulk.wait_group.read 0;" ::: "memory");
    mbar_arrive2_if0(BAR_GEMPTY + 16, 0);
    mbar_wait(bud, BAR_GFULL + 16, 0);
    for (int k = 3; k < 5; k++) {
      mbar_wait(bud, BAR_GOUT + k * 8, 0);
      tma_store2d(&p.out, SB + O_OUT + k * B_SLOT, col + k * 64, row);
      asm volatile("cp.async.bulk.commit_group;" ::: "memory");
      asm volatile("cp.async.bulk.wait_group.read 0;" ::: "memory");
      __nanosleep(1000);
    }
  }
#pragma unroll 1
  for (int i = 0; i < 5; i++) {
    const int k = (0x42103 >> (4 * i)) & 15;
    mbar_wait(bud, BAR_GOUT + k * 8, job.part == 0);
    for (int q = 1; q < 4; q++) {
      const int sh = (job.part + q) & 3;
      tma_store2d(&p.part, SB + O_OUT + k * B_SLOT + sh * 5120, col + k * 64, job.part * NB * SQ + row + sh * 40);
    }
  }
  asm volatile("cp.async.bulk.commit_group;" ::: "memory");
  asm volatile("cp.async.bulk.wait_group 0;" ::: "memory");
  asm volatile("fence.proxy.async.global;" ::: "memory");
  asm volatile("red.release.gpu.global.add.s32 [%0], 1;" ::"l"(&g_pcnt[job.tile * 4 + job.part]) : "memory");
}

__global__ void __launch_bounds__(384, 1) fused_kernel(const __grid_constant__ Params p) {
  extern __shared__ __align__(1024) char smem_raw[];
  if ((smem_u32(smem_raw) & 0xFFFFFFu) != SB) return;
  const int cta = (((blockIdx.x / PERM_G) * PERM_M) % (NCTA / PERM_G)) * PERM_G + (blockIdx.x % PERM_G);
  const int warp = __shfl_sync(0xffffffffu, threadIdx.x >> 5, 0);
  if (threadIdx.x == 0) {
    for (int i = 0; i < NSLOT; i++) { mbar_init(BAR_FULLA + i * 8, 1); mbar_init(BAR_EMPTYA + i * 8, 2); mbar_init(BAR_EMPTYB + i * 8, 2); }
    proxy_fence();
    if (start_delay(cta) == 0) {
#pragma unroll 1
      for (int c = 0; c < NSLOT; c++) {
        mbar_expect(BAR_FULLA + c * 8, A_SLOT + B_SLOT);
        tma3d(A_ADDR(c), &p.wq[0], BAR_FULLA + c * 8, 0, c * 64, (cta >> 4) * 3);
        tma2d(B_ADDR(c), &p.x[0], BAR_FULLA + c * 8, c * 64, (cta & 15) * SQ);
      }
    }
  }
  if (threadIdx.x == 64) {
    mbar_init(BAR_XDONE, 1); mbar_init(BAR_QH, 4); mbar_init(BAR_QM, 4);
    mbar_init(BAR_PFULL, 4); mbar_init(BAR_PFULL + 8, 4); mbar_init(BAR_PFREE, 3); mbar_init(BAR_PFREE + 8, 3);
    mbar_init(BAR_LFULL, 3); mbar_init(BAR_PMID, 4); mbar_init(BAR_PMID + 8, 4); mbar_init(BAR_OFULL, 8);
  }
  if (threadIdx.x == 96) {
    for (int i = 0; i < O_NST; i++) { mbar_init(BAR_GFULL + i * 8, 1); mbar_init(BAR_GEMPTY + i * 8, 2); }
    for (int i = 0; i < 5; i++) mbar_init(BAR_GOUT + i * 8, i == 2 ? 8 : 4);
    mbar_init(BAR_GRED, 1); mbar_init(BAR_GRED + 8, 1); mbar_init(BAR_GRED + 16, 1); mbar_init(BAR_FREE, 2);
    proxy_fence();
  }
  if (warp == 1 && threadIdx.x < 32 + 12) asm volatile("prefetch.tensormap [%0];" ::"l"(&p.x[0] + (threadIdx.x - 32)) : "memory");
  __syncthreads();
  if (warp >= 8) {
    asm volatile("setmaxnreg.dec.sync.aligned.u32 40;");
    if (warp == 8) {
      if (elect_one()) {
        const OJob job = get_ojob(cta, attn_producer(p, cta));
        const int epoch = *(volatile int*)&g_epoch[cta];
        *(volatile int*)&g_epoch[cta] = epoch + 1;
        if (job.n) oproj_producer(p, job, epoch + 1);
      }
    } else {
      const int epoch = __shfl_sync(0xffffffffu, *(volatile int*)&g_epoch[cta], 0);
      attn_helper(p, warp - 9, cta, epoch);
      if (warp == 9) {
        const OJob job = get_ojob(cta, next_item());
        if (job.n && elect_one()) oproj_storer(p, job);
      }
    }
  } else {
    asm volatile("setmaxnreg.inc.sync.aligned.u32 232;");
    if (warp < 4) {
      const OJob job = get_ojob(cta, attn_consumer<0>(cta));
      if (job.n) oproj_consumer<0>(p, job);
    } else {
      const OJob job = get_ojob(cta, attn_consumer<1>(cta));
      if (job.n) oproj_consumer<1>(p, job);
    }
  }
}

typedef CUresult (*EncodeFn)(CUtensorMap*, CUtensorMapDataType, cuuint32_t, void*, const cuuint64_t*, const cuuint64_t*, const cuuint32_t*,
                             const cuuint32_t*, CUtensorMapInterleave, CUtensorMapSwizzle, CUtensorMapL2promotion, CUtensorMapFloatOOBfill);

void make3d(EncodeFn enc, CUtensorMap* m, const void* ptr, uint64_t rows, uint64_t cols, uint32_t box_rows, uint32_t box_blocks,
            CUtensorMapL2promotion promo = CU_TENSOR_MAP_L2_PROMOTION_L2_128B) {
  cuuint64_t gd[3] = {64, rows, cols / 64};
  cuuint64_t gs[2] = {cols * 2, 128};
  cuuint32_t bd[3] = {64, box_rows, box_blocks}, es[3] = {1, 1, 1};
  enc(m, CU_TENSOR_MAP_DATA_TYPE_BFLOAT16, 3, (void*)ptr, gd, gs, bd, es, CU_TENSOR_MAP_INTERLEAVE_NONE, CU_TENSOR_MAP_SWIZZLE_128B,
      promo, CU_TENSOR_MAP_FLOAT_OOB_FILL_NONE);
}
void make2d(EncodeFn enc, CUtensorMap* m, const void* ptr, uint64_t rows, uint64_t cols, uint32_t box_rows) {
  cuuint64_t gd[2] = {cols, rows};
  cuuint64_t gs[1] = {cols * 2};
  cuuint32_t bd[2] = {64, box_rows}, es[2] = {1, 1};
  enc(m, CU_TENSOR_MAP_DATA_TYPE_BFLOAT16, 2, (void*)ptr, gd, gs, bd, es, CU_TENSOR_MAP_INTERLEAVE_NONE, CU_TENSOR_MAP_SWIZZLE_128B,
      CU_TENSOR_MAP_L2_PROMOTION_L2_128B, CU_TENSOR_MAP_FLOAT_OOB_FILL_NONE);
}

}

extern "C" void kernel_launch(void* const* d_in, const int* in_sizes, int n_in, void* d_out, int out_size) {
  static EncodeFn enc = nullptr;
  static void* part = nullptr;
  if (!enc) {
    cudaGetSymbolAddress(&part, g_part);
    cudaDriverEntryPointQueryResult qr;
    cudaGetDriverEntryPoint("cuTensorMapEncodeTiled", (void**)&enc, cudaEnableDefault, &qr);
    cudaFuncSetAttribute(fused_kernel, cudaFuncAttributeMaxDynamicSharedMemorySize, SMEM_BYTES);
  }
  Params p;
  for (int s = 0; s < 2; s++) {
    make2d(enc, &p.x[s], d_in[5 * s + 0], NB * SQ, DM, SQ);
    make3d(enc, &p.k[s], d_in[5 * s + 1], (uint64_t)NB * NH * SK, DH, 64, 3);
    make3d(enc, &p.v[s], d_in[5 * s + 2], (uint64_t)NB * NH * SK, DH, 64, 3);
    make3d(enc, &p.wq[s], d_in[5 * s + 3], DM, NH * DH, 64, 3);
    make3d(enc, &p.wo[s], d_in[5 * s + 4], NH * DH, DM, 64, 5);
    p.xp[s] = (const __nv_bfloat16*)d_in[5 * s + 0];
    p.wqp[s] = (const __nv_bfloat16*)d_in[5 * s + 3];
    p.kp[s] = (const __nv_bfloat16*)d_in[5 * s + 1];
    p.vp[s] = (const __nv_bfloat16*)d_in[5 * s + 2];
  }
  make2d(enc, &p.out, d_out, NB * SQ, 2 * DM, SQ);
  make2d(enc, &p.part, part, 4 * NB * SQ, DM, 40);
  p.outp = (__nv_bfloat16*)d_out;
  fused_kernel<<<NCTA, 384, SMEM_BYTES>>>(p);
}
```

```cpp
#include <cuda_runtime.h>
#include <cuda_bf16.h>
#include <cuda.h>
#include <stdint.h>

#define DEBUG_TIMEOUT 0

namespace {

constexpr int SQ = 160, DM = 640, NH = 32, SK = 512, DH = 192, NB = 16;
constexpr int NITEMS = 2 * NB * NH;
constexpr int NCTA = 132, N_OCTA = 32, N_ATT = NCTA - N_OCTA;
constexpr int ORING = 192, OFRESH = 800, CHUNK1 = 157, LEN1 = 18, LEN2 = 13, LSLOPE1 = 4, LSLOPE2 = 4;
constexpr int STAG_G = 4, PERM_G = 4, O_PAIR = 0, STAG_A0 = 15, STAG_SLOPE = 262, PERM_M = 20, PF_N = 32, PF_WAIT = 1500, PF_GAP = 300;
constexpr int OSLOTS = ORING + NITEMS - OFRESH;
#define W1_NG 3
constexpr int A_SLOT = 24576, B_SLOT = 20480, NSLOT = 5;
constexpr int OFF_A = 0;
constexpr int OFF_B = NSLOT * A_SLOT;
constexpr int O_STAGE = 61440, O_AB = 40960, O_NST = 3;
constexpr int OFF_L = OFF_B + NSLOT * B_SLOT;
constexpr int OFF_BAR = OFF_L + 160 * 4;
constexpr int SMEM_BYTES = OFF_BAR + 512 + 512;
constexpr int O_OUT = 2 * O_STAGE;
static_assert(O_OUT + 5 * B_SLOT <= OFF_L, "smem layout");
constexpr uint32_t SB = 1024;
constexpr uint32_t BARS = SB + OFF_BAR;
constexpr uint32_t BAR_FULLA = BARS, BAR_EMPTYA = BARS + 40, BAR_PMID = BARS + 80, BAR_EMPTYB = BARS + 120, BAR_XDONE = BARS + 160,
                   BAR_QH = BARS + 168, BAR_QM = BARS + 96, BAR_PFULL = BARS + 184, BAR_PFREE = BARS + 200, BAR_LFULL = BARS + 216,
                   BAR_OFULL = BARS + 224, BAR_GFULL = BARS + 248, BAR_GEMPTY = BARS + 280, BAR_GOUT = BARS + 328, BAR_GRED = BARS + 368,
                   BAR_FREE = BARS + 240, NEXT_ITEM = BARS + 320;
constexpr int O_ITEM_BYTES = SQ * DH * 2;

struct alignas(64) Params {
  CUtensorMap x[2], wq[2], k[2], v[2], wo[2], out, part;
  __nv_bfloat16* outp;
  const __nv_bfloat16 *xp[2], *wqp[2], *kp[2], *vp[2];
};

__device__ uint4 g_o[(size_t)OSLOTS * O_ITEM_BYTES / 16];
__device__ uint4 g_part[4 * NB * SQ * DM / 8];
__device__ int g_pcnt[4 * N_OCTA];
__device__ int g_ready[NITEMS];
__device__ int g_done[NITEMS];
__device__ unsigned g_ticket;
__device__ int g_epoch[NCTA];

#define TLP(id)
#define TLG(id)
#define TL(id)
#define TL_FLUSH()
__device__ __forceinline__ uint32_t smem_u32(const void* p) { return (uint32_t)__cvta_generic_to_shared(p); }
__device__ __forceinline__ void wg_fence() { asm volatile("wgmma.fence.sync.aligned;" ::: "memory"); }
__device__ __forceinline__ void wg_commit() { asm volatile("wgmma.commit_group.sync.aligned;" ::: "memory"); }
template <int N> __device__ __forceinline__ void wg_wait() { asm volatile("wgmma.wait_group.sync.aligned %0;" ::"n"(N) : "memory"); }
template <int N> __device__ __forceinline__ void reg_fence(float (&d)[N]) {
#pragma unroll
  for (int i = 0; i < N; i++) asm volatile("" : "+f"(d[i])::"memory");
}
template <int N> __device__ __forceinline__ void zero_regs(float (&d)[N]) {
#pragma unroll
  for (int i = 0; i < N; i++) d[i] = 0.f;
}
__device__ __forceinline__ void proxy_fence() { asm volatile("fence.proxy.async.shared::cta;" ::: "memory"); }
__device__ __forceinline__ void mbar_init(uint32_t bar, int cnt) { asm volatile("mbarrier.init.shared::cta.b64 [%0], %1;" ::"r"(bar), "r"(cnt) : "memory"); }
__device__ __forceinline__ void mbar_arrive_if0(uint32_t bar, uint32_t sel) {
  asm volatile("{\n.reg .pred p;\nsetp.eq.u32 p, %1, 0;\n@p mbarrier.arrive.shared::cta.b64 _, [%0];\n}\n" ::"r"(bar), "r"(sel) : "memory");
}
__device__ __forceinline__ void mbar_arrive2_if0(uint32_t bar, uint32_t sel) {
  asm volatile("{\n.reg .pred p;\nsetp.eq.u32 p, %1, 0;\n@p mbarrier.arrive.shared::cta.b64 _, [%0], 2;\n}\n" ::"r"(bar), "r"(sel) : "memory");
}
__device__ __forceinline__ void mbar_expect(uint32_t bar, uint32_t bytes) {
  asm volatile("mbarrier.arrive.expect_tx.shared::cta.b64 _, [%0], %1;" ::"r"(bar), "r"(bytes) : "memory");
}
__device__ __forceinline__ void mbar_wait(int& bud, uint32_t bar, uint32_t parity) {
  asm volatile(
      "{\n.reg .pred p;\n"
      "LW:\n"
      "mbarrier.try_wait.parity.shared::cta.b64 p, [%0], %1;\n"
      "@!p bra LW;\n}\n" ::"r"(bar), "r"(parity) : "memory");
}
constexpr int WAIT_BUDGET = 1 << 22;
__device__ __forceinline__ bool elect_one() {
  uint32_t p;
  asm volatile("{\n.reg .pred p;\nelect.sync _|p, 0xffffffff;\nselp.u32 %0, 1, 0, p;\n}\n" : "=r"(p));
  return p;
}
__device__ __forceinline__ void tma2d(uint32_t dst, const CUtensorMap* m, uint32_t bar, int c0, int c1) {
  asm volatile("cp.async.bulk.tensor.2d.shared::cluster.global.mbarrier::complete_tx::bytes [%0], [%1, {%3, %4}], [%2];"
               ::"r"(dst), "l"(m), "r"(bar), "r"(c0), "r"(c1) : "memory");
}
__device__ __forceinline__ void tma3d(uint32_t dst, const CUtensorMap* m, uint32_t bar, int c0, int c1, int c2) {
  asm volatile("cp.async.bulk.tensor.3d.shared::cluster.global.mbarrier::complete_tx::bytes [%0], [%1, {%3, %4, %5}], [%2];"
               ::"r"(dst), "l"(m), "r"(bar), "r"(c0), "r"(c1), "r"(c2) : "memory");
}
__device__ __forceinline__ void tma3d_hint(uint32_t dst, const CUtensorMap* m, uint32_t bar, int c0, int c1, int c2, uint64_t pol) {
  asm volatile("cp.async.bulk.tensor.3d.shared::cluster.global.mbarrier::complete_tx::bytes.L2::cache_hint [%0], [%1, {%3, %4, %5}], [%2], %6;"
               ::"r"(dst), "l"(m), "r"(bar), "r"(c0), "r"(c1), "r"(c2), "l"(pol) : "memory");
}
__device__ __forceinline__ void tma_store2d(const CUtensorMap* m, uint32_t src, int c0, int c1) {
  asm volatile("cp.async.bulk.tensor.2d.global.shared::cta.bulk_group [%0, {%2, %3}], [%1];" ::"l"(m), "r"(src), "r"(c0), "r"(c1) : "memory");
}
__device__ __forceinline__ void bar_sync(int id, int n) { asm volatile("bar.sync %0, %1;" ::"r"(id), "r"(n) : "memory"); }
__device__ __forceinline__ void bar_arrive(int id, int n) { asm volatile("bar.arrive %0, %1;" ::"r"(id), "r"(n) : "memory"); }
__device__ __forceinline__ float ex2(float x) { float y; asm("ex2.approx.ftz.f32 %0, %1;" : "=f"(y) : "f"(x)); return y; }
__device__ __forceinline__ uint32_t pack2(float lo, float hi) { uint32_t r; asm("cvt.rn.bf16x2.f32 %0, %1, %2;" : "=r"(r) : "f"(hi), "f"(lo)); return r; }
__device__ __forceinline__ void stsm_t(uint32_t a, uint32_t r0, uint32_t r1, uint32_t r2, uint32_t r3) {
  asm volatile("stmatrix.sync.aligned.m8n8.x4.trans.shared.b16 [%0], {%1,%2,%3,%4};" ::"r"(a), "r"(r0), "r"(r1), "r"(r2), "r"(r3) : "memory");
}
__device__ __forceinline__ uint64_t evict_first_policy() {
  uint64_t pol;
  asm volatile("createpolicy.fractional.L2::evict_first.b64 %0, 1.0;" : "=l"(pol));
  return pol;
}
__device__ __forceinline__ void bulk_load_hint(uint32_t dst, const void* src, uint32_t bytes, uint32_t bar, uint64_t pol) {
  asm volatile("cp.async.bulk.shared::cluster.global.mbarrier::complete_tx::bytes.L2::cache_hint [%0], [%1], %2, [%3], %4;"
               ::"r"(dst), "l"(src), "r"(bytes), "r"(bar), "l"(pol) : "memory");
}
__device__ __forceinline__ void flag_wait(int& bud, const int* p, int target) {
  while (true) {
    int v;
    asm volatile("ld.acquire.gpu.global.s32 %0, [%1];" : "=r"(v) : "l"(p) : "memory");
    if (v - target >= 0 || --bud <= 0) break;
    __nanosleep(64);
  }
}
__device__ __forceinline__ uint32_t lo_sw(uint32_t addr) { return (addr >> 4) | (1u << 16); }
__device__ __forceinline__ uint32_t lo_o(uint32_t addr) { return (addr >> 4) | (128u << 16); }
__device__ __forceinline__ uint32_t tid_x() { uint32_t t; asm volatile("mov.u32 %0, %tid.x;" : "=r"(t)); return t; }
__device__ __forceinline__ uint32_t opaque(uint32_t x) { uint32_t y; asm volatile("mov.u32 %0, %1;" : "=r"(y) : "r"(x)); return y; }

template <int TA, int TB, uint32_t OA, uint32_t OB>
__device__ __forceinline__ void mma160(float (&d)[80], uint32_t la, uint32_t lb) {
  asm volatile(
      "{\n.reg .pred p;\n.reg .b32 a, b;\n.reg .b64 da, db;\nsetp.eq.b32 p, 0, 0;\n"
      "add.u32 a, %80, %84;\nadd.u32 b, %81, %85;\nmov.b64 da, {a, 0x40000040};\nmov.b64 db, {b, %86};\n"
      "wgmma.mma_async.sync.aligned.m64n160k16.f32.bf16.bf16 {"
      "%0,%1,%2,%3,%4,%5,%6,%7,%8,%9,%10,%11,%12,%13,%14,%15,%16,%17,%18,%19,%20,%21,%22,%23,%24,%25,%26,%27,%28,%29,%30,%31,%32,%33,%34,%35,%36,"
      "%37,%38,%39,%40,%41,%42,%43,%44,%45,%46,%47,%48,%49,%50,%51,%52,%53,%54,%55,%56,%57,%58,%59,%60,%61,%62,%63,%64,%65,%66,%67,%68,%69,%70,%71,"
      "%72,%73,%74,%75,%76,%77,%78,%79"
      "}, da, db, p, 1, 1, %82, %83;\n}\n"
      :
      "+f"(d[0]),"+f"(d[1]),"+f"(d[2]),"+f"(d[3]),"+f"(d[4]),"+f"(d[5]),"+f"(d[6]),"+f"(d[7]),"+f"(d[8]),"+f"(d[9]),"+f"(d[10]),"+f"(d[11]),
      "+f"(d[12]),"+f"(d[13]),"+f"(d[14]),"+f"(d[15]),"+f"(d[16]),"+f"(d[17]),"+f"(d[18]),"+f"(d[19]),"+f"(d[20]),"+f"(d[21]),"+f"(d[22]),
      "+f"(d[23]),"+f"(d[24]),"+f"(d[25]),"+f"(d[26]),"+f"(d[27]),"+f"(d[28]),"+f"(d[29]),"+f"(d[30]),"+f"(d[31]),"+f"(d[32]),"+f"(d[33]),
      "+f"(d[34]),"+f"(d[35]),"+f"(d[36]),"+f"(d[37]),"+f"(d[38]),"+f"(d[39]),"+f"(d[40]),"+f"(d[41]),"+f"(d[42]),"+f"(d[43]),"+f"(d[44]),
      "+f"(d[45]),"+f"(d[46]),"+f"(d[47]),"+f"(d[48]),"+f"(d[49]),"+f"(d[50]),"+f"(d[51]),"+f"(d[52]),"+f"(d[53]),"+f"(d[54]),"+f"(d[55]),
      "+f"(d[56]),"+f"(d[57]),"+f"(d[58]),"+f"(d[59]),"+f"(d[60]),"+f"(d[61]),"+f"(d[62]),"+f"(d[63]),"+f"(d[64]),"+f"(d[65]),"+f"(d[66]),
      "+f"(d[67]),"+f"(d[68]),"+f"(d[69]),"+f"(d[70]),"+f"(d[71]),"+f"(d[72]),"+f"(d[73]),"+f"(d[74]),"+f"(d[75]),"+f"(d[76]),"+f"(d[77]),
      "+f"(d[78]),"+f"(d[79])
      : "r"(la), "r"(lb), "n"(TA), "n"(TB), "n"(OA >> 4), "n"(OB >> 4), "n"(TB ? 0xC0000010u : 0x40000040u));
}

template <int TA, int TB, uint32_t OA, uint32_t OB>
__device__ __forceinline__ void mma160z(float (&d)[80], uint32_t la, uint32_t lb) {
  asm volatile(
      "{\n.reg .pred p;\n.reg .b32 a, b;\n.reg .b64 da, db;\nsetp.ne.b32 p, 0, 0;\n"
      "add.u32 a, %80, %84;\nadd.u32 b, %81, %85;\nmov.b64 da, {a, 0x40000040};\nmov.b64 db, {b, %86};\n"
      "wgmma.mma_async.sync.aligned.m64n160k16.f32.bf16.bf16 {"
      "%0,%1,%2,%3,%4,%5,%6,%7,%8,%9,%10,%11,%12,%13,%14,%15,%16,%17,%18,%19,%20,%21,%22,%23,%24,%25,%26,%27,%28,%29,%30,%31,%32,%33,%34,%35,%36,"
      "%37,%38,%39,%40,%41,%42,%43,%44,%45,%46,%47,%48,%49,%50,%51,%52,%53,%54,%55,%56,%57,%58,%59,%60,%61,%62,%63,%64,%65,%66,%67,%68,%69,%70,%71,"
      "%72,%73,%74,%75,%76,%77,%78,%79"
      "}, da, db, p, 1, 1, %82, %83;\n}\n"
      :
      "=f"(d[0]),"=f"(d[1]),"=f"(d[2]),"=f"(d[3]),"=f"(d[4]),"=f"(d[5]),"=f"(d[6]),"=f"(d[7]),"=f"(d[8]),"=f"(d[9]),"=f"(d[10]),"=f"(d[11]),
      "=f"(d[12]),"=f"(d[13]),"=f"(d[14]),"=f"(d[15]),"=f"(d[16]),"=f"(d[17]),"=f"(d[18]),"=f"(d[19]),"=f"(d[20]),"=f"(d[21]),"=f"(d[22]),
      "=f"(d[23]),"=f"(d[24]),"=f"(d[25]),"=f"(d[26]),"=f"(d[27]),"=f"(d[28]),"=f"(d[29]),"=f"(d[30]),"=f"(d[31]),"=f"(d[32]),"=f"(d[33]),
      "=f"(d[34]),"=f"(d[35]),"=f"(d[36]),"=f"(d[37]),"=f"(d[38]),"=f"(d[39]),"=f"(d[40]),"=f"(d[41]),"=f"(d[42]),"=f"(d[43]),"=f"(d[44]),
      "=f"(d[45]),"=f"(d[46]),"=f"(d[47]),"=f"(d[48]),"=f"(d[49]),"=f"(d[50]),"=f"(d[51]),"=f"(d[52]),"=f"(d[53]),"=f"(d[54]),"=f"(d[55]),
      "=f"(d[56]),"=f"(d[57]),"=f"(d[58]),"=f"(d[59]),"=f"(d[60]),"=f"(d[61]),"=f"(d[62]),"=f"(d[63]),"=f"(d[64]),"=f"(d[65]),"=f"(d[66]),
      "=f"(d[67]),"=f"(d[68]),"=f"(d[69]),"=f"(d[70]),"=f"(d[71]),"=f"(d[72]),"=f"(d[73]),"=f"(d[74]),"=f"(d[75]),"=f"(d[76]),"=f"(d[77]),
      "=f"(d[78]),"=f"(d[79])
      : "r"(la), "r"(lb), "n"(TA), "n"(TB), "n"(OA >> 4), "n"(OB >> 4), "n"(TB ? 0xC0000010u : 0x40000040u));
}

template <int TA, int TB, uint32_t OA, uint32_t OB>
__device__ __forceinline__ void mma80(float (&d)[40], uint32_t la, uint32_t lb) {
  asm volatile(
      "{\n.reg .pred p;\n.reg .b32 a, b;\n.reg .b64 da, db;\nsetp.eq.b32 p, 0, 0;\n"
      "add.u32 a, %40, %44;\nadd.u32 b, %41, %45;\nmov.b64 da, {a, 0x40000040};\nmov.b64 db, {b, %46};\n"
      "wgmma.mma_async.sync.aligned.m64n80k16.f32.bf16.bf16 {"
      "%0,%1,%2,%3,%4,%5,%6,%7,%8,%9,%10,%11,%12,%13,%14,%15,%16,%17,%18,%19,%20,%21,%22,%23,%24,%25,%26,%27,%28,%29,%30,%31,%32,%33,%34,%35,%36,"
      "%37,%38,%39"
      "}, da, db, p, 1, 1, %42, %43;\n}\n"
      :
      "+f"(d[0]),"+f"(d[1]),"+f"(d[2]),"+f"(d[3]),"+f"(d[4]),"+f"(d[5]),"+f"(d[6]),"+f"(d[7]),"+f"(d[8]),"+f"(d[9]),"+f"(d[10]),"+f"(d[11]),
      "+f"(d[12]),"+f"(d[13]),"+f"(d[14]),"+f"(d[15]),"+f"(d[16]),"+f"(d[17]),"+f"(d[18]),"+f"(d[19]),"+f"(d[20]),"+f"(d[21]),"+f"(d[22]),
      "+f"(d[23]),"+f"(d[24]),"+f"(d[25]),"+f"(d[26]),"+f"(d[27]),"+f"(d[28]),"+f"(d[29]),"+f"(d[30]),"+f"(d[31]),"+f"(d[32]),"+f"(d[33]),
      "+f"(d[34]),"+f"(d[35]),"+f"(d[36]),"+f"(d[37]),"+f"(d[38]),"+f"(d[39])
      : "r"(la), "r"(lb), "n"(TA), "n"(TB), "n"(OA >> 4), "n"(OB >> 4), "n"(TB ? 0xC0000010u : 0x40000040u));
}

template <int TA, int TB, uint32_t OA, uint32_t OB>
__device__ __forceinline__ void mma80z(float (&d)[40], uint32_t la, uint32_t lb) {
  asm volatile(
      "{\n.reg .pred p;\n.reg .b32 a, b;\n.reg .b64 da, db;\nsetp.ne.b32 p, 0, 0;\n"
      "add.u32 a, %40, %44;\nadd.u32 b, %41, %45;\nmov.b64 da, {a, 0x40000040};\nmov.b64 db, {b, %46};\n"
      "wgmma.mma_async.sync.aligned.m64n80k16.f32.bf16.bf16 {"
      "%0,%1,%2,%3,%4,%5,%6,%7,%8,%9,%10,%11,%12,%13,%14,%15,%16,%17,%18,%19,%20,%21,%22,%23,%24,%25,%26,%27,%28,%29,%30,%31,%32,%33,%34,%35,%36,"
      "%37,%38,%39"
      "}, da, db, p, 1, 1, %42, %43;\n}\n"
      :
      "=f"(d[0]),"=f"(d[1]),"=f"(d[2]),"=f"(d[3]),"=f"(d[4]),"=f"(d[5]),"=f"(d[6]),"=f"(d[7]),"=f"(d[8]),"=f"(d[9]),"=f"(d[10]),"=f"(d[11]),
      "=f"(d[12]),"=f"(d[13]),"=f"(d[14]),"=f"(d[15]),"=f"(d[16]),"=f"(d[17]),"=f"(d[18]),"=f"(d[19]),"=f"(d[20]),"=f"(d[21]),"=f"(d[22]),
      "=f"(d[23]),"=f"(d[24]),"=f"(d[25]),"=f"(d[26]),"=f"(d[27]),"=f"(d[28]),"=f"(d[29]),"=f"(d[30]),"=f"(d[31]),"=f"(d[32]),"=f"(d[33]),
      "=f"(d[34]),"=f"(d[35]),"=f"(d[36]),"=f"(d[37]),"=f"(d[38]),"=f"(d[39])
      : "r"(la), "r"(lb), "n"(TA), "n"(TB), "n"(OA >> 4), "n"(OB >> 4), "n"(TB ? 0xC0000010u : 0x40000040u));
}

template <int TA, int TB, uint32_t OA, uint32_t OB>
__device__ __forceinline__ void mma160r(float (&d)[80], uint32_t la, uint32_t lb, int sc) {
  asm volatile(
      "{\n.reg .pred p;\n.reg .b32 a, b;\n.reg .b64 da, db;\nsetp.ne.b32 p, %87, 0;\n"
      "add.u32 a, %80, %84;\nadd.u32 b, %81, %85;\nmov.b64 da, {a, 0x40000040};\nmov.b64 db, {b, %86};\n"
      "wgmma.mma_async.sync.aligned.m64n160k16.f32.bf16.bf16 {"
      "%0,%1,%2,%3,%4,%5,%6,%7,%8,%9,%10,%11,%12,%13,%14,%15,%16,%17,%18,%19,%20,%21,%22,%23,%24,%25,%26,%27,%28,%29,%30,%31,%32,%33,%34,%35,%36,"
      "%37,%38,%39,%40,%41,%42,%43,%44,%45,%46,%47,%48,%49,%50,%51,%52,%53,%54,%55,%56,%57,%58,%59,%60,%61,%62,%63,%64,%65,%66,%67,%68,%69,%70,%71,"
      "%72,%73,%74,%75,%76,%77,%78,%79"
      "}, da, db, p, 1, 1, %82, %83;\n}\n"
      :
      "+f"(d[0]),"+f"(d[1]),"+f"(d[2]),"+f"(d[3]),"+f"(d[4]),"+f"(d[5]),"+f"(d[6]),"+f"(d[7]),"+f"(d[8]),"+f"(d[9]),"+f"(d[10]),"+f"(d[11]),
      "+f"(d[12]),"+f"(d[13]),"+f"(d[14]),"+f"(d[15]),"+f"(d[16]),"+f"(d[17]),"+f"(d[18]),"+f"(d[19]),"+f"(d[20]),"+f"(d[21]),"+f"(d[22]),
      "+f"(d[23]),"+f"(d[24]),"+f"(d[25]),"+f"(d[26]),"+f"(d[27]),"+f"(d[28]),"+f"(d[29]),"+f"(d[30]),"+f"(d[31]),"+f"(d[32]),"+f"(d[33]),
      "+f"(d[34]),"+f"(d[35]),"+f"(d[36]),"+f"(d[37]),"+f"(d[38]),"+f"(d[39]),"+f"(d[40]),"+f"(d[41]),"+f"(d[42]),"+f"(d[43]),"+f"(d[44]),
      "+f"(d[45]),"+f"(d[46]),"+f"(d[47]),"+f"(d[48]),"+f"(d[49]),"+f"(d[50]),"+f"(d[51]),"+f"(d[52]),"+f"(d[53]),"+f"(d[54]),"+f"(d[55]),
      "+f"(d[56]),"+f"(d[57]),"+f"(d[58]),"+f"(d[59]),"+f"(d[60]),"+f"(d[61]),"+f"(d[62]),"+f"(d[63]),"+f"(d[64]),"+f"(d[65]),"+f"(d[66]),
      "+f"(d[67]),"+f"(d[68]),"+f"(d[69]),"+f"(d[70]),"+f"(d[71]),"+f"(d[72]),"+f"(d[73]),"+f"(d[74]),"+f"(d[75]),"+f"(d[76]),"+f"(d[77]),
      "+f"(d[78]),"+f"(d[79])
      : "r"(la), "r"(lb), "n"(TA), "n"(TB), "n"(OA >> 4), "n"(OB >> 4), "n"(TB ? 0xC0000010u : 0x40000040u), "r"(sc));
}

template <int TA, int TB, uint32_t OA, uint32_t OB>
__device__ __forceinline__ void mma80r(float (&d)[40], uint32_t la, uint32_t lb, int sc) {
  asm volatile(
      "{\n.reg .pred p;\n.reg .b32 a, b;\n.reg .b64 da, db;\nsetp.ne.b32 p, %47, 0;\n"
      "add.u32 a, %40, %44;\nadd.u32 b, %41, %45;\nmov.b64 da, {a, 0x40000040};\nmov.b64 db, {b, %46};\n"
      "wgmma.mma_async.sync.aligned.m64n80k16.f32.bf16.bf16 {"
      "%0,%1,%2,%3,%4,%5,%6,%7,%8,%9,%10,%11,%12,%13,%14,%15,%16,%17,%18,%19,%20,%21,%22,%23,%24,%25,%26,%27,%28,%29,%30,%31,%32,%33,%34,%35,%36,"
      "%37,%38,%39"
      "}, da, db, p, 1, 1, %42, %43;\n}\n"
      :
      "+f"(d[0]),"+f"(d[1]),"+f"(d[2]),"+f"(d[3]),"+f"(d[4]),"+f"(d[5]),"+f"(d[6]),"+f"(d[7]),"+f"(d[8]),"+f"(d[9]),"+f"(d[10]),"+f"(d[11]),
      "+f"(d[12]),"+f"(d[13]),"+f"(d[14]),"+f"(d[15]),"+f"(d[16]),"+f"(d[17]),"+f"(d[18]),"+f"(d[19]),"+f"(d[20]),"+f"(d[21]),"+f"(d[22]),
      "+f"(d[23]),"+f"(d[24]),"+f"(d[25]),"+f"(d[26]),"+f"(d[27]),"+f"(d[28]),"+f"(d[29]),"+f"(d[30]),"+f"(d[31]),"+f"(d[32]),"+f"(d[33]),
      "+f"(d[34]),"+f"(d[35]),"+f"(d[36]),"+f"(d[37]),"+f"(d[38]),"+f"(d[39])
      : "r"(la), "r"(lb), "n"(TA), "n"(TB), "n"(OA >> 4), "n"(OB >> 4), "n"(TB ? 0xC0000010u : 0x40000040u), "r"(sc));
}

struct Ring { uint32_t s0, ph0; };
__device__ __forceinline__ void ring_pos(const Ring& r, int i, uint32_t& slot, uint32_t& ph) {
  uint32_t s = opaque(r.s0) + (i % NSLOT);
  uint32_t wrap = s >= NSLOT;
  slot = s - (wrap ? NSLOT : 0);
  ph = r.ph0 ^ ((i / NSLOT) & 1) ^ wrap;
}
__device__ __forceinline__ void ring_advance(Ring& r, int n) {
  uint32_t s, p;
  ring_pos(r, n, s, p);
  r.s0 = s; r.ph0 = p;
}
__host__ __device__ constexpr int idxK(int j) { return j == 0 ? 10 : 9 + 2 * j; }
__host__ __device__ constexpr int idxV(int j) { return j == 7 ? 25 : 12 + 2 * j; }
__host__ __device__ constexpr int xs(int c) { return c % NSLOT; }

__device__ __forceinline__ int start_delay(int cta) {
  return max(0, ((cta - N_OCTA) | (STAG_G - 1)) - STAG_A0) * STAG_SLOPE;
}
__device__ __forceinline__ char* o_slot(int item) {
  return (char*)g_o + (size_t)(item < OFRESH ? item % ORING : item - OFRESH + ORING) * O_ITEM_BYTES;
}
__device__ __forceinline__ int next_item(uint32_t a = NEXT_ITEM) {
  int v;
  asm volatile("ld.shared.s32 %0, [%1];" : "=r"(v) : "r"(a) : "memory");
  return __shfl_sync(0xffffffffu, v, 0);
}

template <int W, bool ACC>
__device__ __forceinline__ void mma_main(float (&d)[80], uint32_t aaddr, uint32_t baddr) {
  const uint32_t la = lo_sw(aaddr), lb = lo_sw(baddr);
  if (ACC) mma160<1, 0, W * 16384, 0>(d, la, lb); else mma160z<1, 0, W * 16384, 0>(d, la, lb);
  mma160<1, 0, W * 16384 + 1 * 2048, 1 * 32>(d, la, lb);
  mma160<1, 0, W * 16384 + 2 * 2048, 2 * 32>(d, la, lb);
  mma160<1, 0, W * 16384 + 3 * 2048, 3 * 32>(d, la, lb);
}
template <int W, bool ACC>
__device__ __forceinline__ void mma_mid(float (&d)[40], uint32_t aaddr, uint32_t baddr) {
  const uint32_t la = lo_sw(aaddr), lb = lo_sw(baddr);
  if (ACC) mma80<1, 0, 8192, W * 10240>(d, la, lb); else mma80z<1, 0, 8192, W * 10240>(d, la, lb);
  mma80<1, 0, 8192 + 1 * 2048, W * 10240 + 1 * 32>(d, la, lb);
  mma80<1, 0, 8192 + 2 * 2048, W * 10240 + 2 * 32>(d, la, lb);
  mma80<1, 0, 8192 + 3 * 2048, W * 10240 + 3 * 32>(d, la, lb);
}
template <int W, bool ACC>
__device__ __forceinline__ void mma_both(float (&dm)[80], float (&dh)[40], uint32_t aaddr, uint32_t baddr) {
  mma_mid<W, ACC>(dh, aaddr, baddr);
  mma_main<W, ACC>(dm, aaddr, baddr);
}
template <int KB, bool ACC>
__device__ __forceinline__ void s_mma(float (&sacc)[80], uint32_t kaddr) {
  const uint32_t la = lo_sw(kaddr), lb = lo_sw(SB + OFF_B);
  if (ACC) mma160<0, 0, KB * 8192, KB * B_SLOT>(sacc, la, lb); else mma160z<0, 0, KB * 8192, KB * B_SLOT>(sacc, la, lb);
  mma160<0, 0, KB * 8192 + 32, KB * B_SLOT + 32>(sacc, la, lb);
  mma160<0, 0, KB * 8192 + 64, KB * B_SLOT + 64>(sacc, la, lb);
  mma160<0, 0, KB * 8192 + 96, KB * B_SLOT + 96>(sacc, la, lb);
}
template <int N>
__device__ __forceinline__ void store_scaled(uint32_t addr, const float (&d)[N], float sc) {
#pragma unroll
  for (int J = 0; J < N / 8; J++)
    stsm_t(addr + J * 2048, pack2(d[8 * J] * sc, d[8 * J + 1] * sc), pack2(d[8 * J + 2] * sc, d[8 * J + 3] * sc),
           pack2(d[8 * J + 4] * sc, d[8 * J + 5] * sc), pack2(d[8 * J + 6] * sc, d[8 * J + 7] * sc));
}
__device__ __forceinline__ float4 lds_f4(uint32_t a) {
  float4 v;
  asm volatile("ld.shared.v4.f32 {%0,%1,%2,%3}, [%4];" : "=f"(v.x), "=f"(v.y), "=f"(v.z), "=f"(v.w) : "r"(a) : "memory");
  return v;
}
__device__ __forceinline__ void norm_pack(uint32_t* p, const float* d, const float4& i) {
  p[0] = pack2(d[0] * i.x, d[1] * i.y); p[1] = pack2(d[4] * i.z, d[5] * i.w);
  p[2] = pack2(d[2] * i.x, d[3] * i.y); p[3] = pack2(d[6] * i.z, d[7] * i.w);
  asm volatile("" : "+r"(p[0]), "+r"(p[1]), "+r"(p[2]), "+r"(p[3])::"memory");
}
template <int W>
__device__ __forceinline__ void pack_first(uint32_t (&pk)[60], const float (&om)[80], const float (&oh)[40], uint32_t laddr) {
  float4 n0 = lds_f4(laddr + W * 80), n1 = lds_f4(laddr + W * 80 + 16);
#pragma unroll
  for (int J = 0; J < 5; J++) {
    const float4 i = n0;
    n0 = n1;
    if (J + 2 < 5) n1 = lds_f4(laddr + W * 80 + (J + 2) * 16);
    norm_pack(&pk[20 + 4 * J], &om[8 * (5 * W + J)], i);
    norm_pack(&pk[4 * J], &oh[8 * J], i);
  }
}
template <int W, int J0, int J1>
__device__ __forceinline__ void pack_second(uint32_t (&pk)[60], const float (&om)[80], uint32_t laddr) {
  float4 n[J1 - J0];
#pragma unroll
  for (int J = J0; J < J1; J++) n[J - J0] = lds_f4(laddr + (1 - W) * 80 + J * 16);
#pragma unroll
  for (int J = J0; J < J1; J++) norm_pack(&pk[40 + 4 * J], &om[8 * (5 * (1 - W) + J)], n[J - J0]);
}
__device__ __forceinline__ char* o_ptr(int item) {
  const uint32_t t = tid_x();
  return o_slot(item) + ((t & 96) * 16 + (t & 28) * 8 + ((((t >> 1) ^ (t >> 4)) & 1) << 4) + (t & 1) * 8);
}
template <int W, int G0, int G1>
__device__ __forceinline__ void store_groups(char* op, const uint32_t (&pk)[60], uint32_t on) {
#pragma unroll
  for (int G = G0; G < G1; G++) {
    const int off = (G < 5 ? 1 : 2 * W) * B_SLOT + (5 * (G < 10 ? W : 1 - W) + G % 5) * 2048;
    asm volatile("{\n.reg .pred p;\nsetp.ne.u32 p, %5, 0;\n@p st.global.v2.b32 [%0], {%1, %2};\n@p st.global.v2.b32 [%0+256], {%3, %4};\n}\n"
                 ::"l"(op + off), "r"(pk[4 * G]), "r"(pk[4 * G + 1]), "r"(pk[4 * G + 2]), "r"(pk[4 * G + 3]), "r"(on) : "memory");
  }
}
__device__ __forceinline__ void publish_generic(uint32_t bar, int lane) {
  __syncwarp();
  mbar_arrive_if0(bar, lane);
}
__device__ __forceinline__ void publish(uint32_t bar, int lane) {
  proxy_fence();
  __syncwarp();
  mbar_arrive_if0(bar, lane);
}

#define A_ADDR(s) (SB + OFF_A + (s) * A_SLOT)
#define B_ADDR(s) (SB + OFF_B + (s) * B_SLOT)
#define WAIT_CHUNK(c, ro, sA)                \
  uint32_t sA;                               \
  {                                          \
    uint32_t pA_;                            \
    ring_pos(ring, (ro) + (c), sA, pA_);     \
    mbar_wait(bud, BAR_FULLA + sA * 8, pA_); \
  }
#define RELEASE_CHUNK(c, sA)                                  \
  mbar_arrive_if0(BAR_EMPTYA + (sA) * 8, tid);                \
  if ((c) < NSLOT) mbar_arrive_if0(BAR_EMPTYB + xs(c) * 8, tid);

template <int W>
__device__ __forceinline__ int attn_consumer(int item) {
  int bud = WAIT_BUDGET;
  const int tid = threadIdx.x & 127, lane = tid & 31, warp = tid >> 5;
  const uint32_t st_off = ((lane & 7) + 8 * (lane >> 4)) * 128 + (((2 * warp + ((lane >> 3) & 1)) ^ (lane & 7)) << 4);
  const uint32_t laddr = SB + OFF_L + (lane & 3) * 160;
  float om[80], oh[40], sacc[80];
  uint32_t pk[60];
#pragma unroll
  for (int i = 0; i < 40; i++) pk[i] = 0;
  zero_regs(om);
  Ring ring{0u, 0u};
  uint32_t par = 0;
  int prev = 0;
  const float qscale = 0.07216878364870322f * 1.4426950408889634f;
  constexpr uint32_t pown = B_ADDR(3 + W), poth = B_ADDR(4 - W);
  TL(0); TLG(62);
  {
    WAIT_CHUNK(0, 0, s0)
    wg_fence();
    mma_both<W, false>(sacc, oh, A_ADDR(s0), B_ADDR(xs(0)));
    wg_commit();
    WAIT_CHUNK(1, 0, s1)
    wg_fence();
    mma_both<W, true>(sacc, oh, A_ADDR(s1), B_ADDR(xs(1)));
    wg_commit();
    wg_wait<1>();
    RELEASE_CHUNK(0, s0)
  }
#pragma unroll 1
  for (int it = 0;; it++) {
    char* op = o_ptr(prev);
#pragma unroll
    for (int c = 2; c < 8 - W; c++) {
      WAIT_CHUNK(c, 0, sA)
      TL(40 + c);
      wg_fence();
      mma_both<W, true>(sacc, oh, A_ADDR(sA), B_ADDR(xs(c)));
      wg_commit();
      wg_wait<1>();
      uint32_t sP, pP;
      ring_pos(ring, c - 1, sP, pP);
      RELEASE_CHUNK(c - 1, sP)
      constexpr int NG = W == 0 ? 3 : W1_NG;
      if (c == 2) { pack_second<W, 0, 1>(pk, om, laddr); store_groups<W, 0 * NG, 1 * NG>(op, pk, it); }
      if (c == 3) { pack_second<W, 1, 2>(pk, om, laddr); store_groups<W, 1 * NG, 2 * NG>(op, pk, it); }
      if (c == 4) { pack_second<W, 2, 3>(pk, om, laddr); store_groups<W, 2 * NG, 3 * NG>(op, pk, it); }
      if (c == 5) { pack_second<W, 3, 4>(pk, om, laddr); store_groups<W, 3 * NG, 4 * NG>(op, pk, it); }
      if (c == 6) {
        pack_second<W, 4, 5>(pk, om, laddr);
        if (W == 1) {
          wg_wait<0>();
          RELEASE_CHUNK(6, sA)
          mbar_arrive_if0(BAR_XDONE, tid);
        }
        store_groups<W, 4 * NG, 15>(op, pk, it);
        __syncwarp();
        mbar_arrive_if0(BAR_OFULL, lane | (it == 0));
      }
    }
    uint32_t sK0, pK0, s7, p7;
    ring_pos(ring, idxK(W), sK0, pK0);
    ring_pos(ring, 7, s7, p7);
    if (W == 1) mbar_wait(bud, BAR_FULLA + s7 * 8, p7);
    WAIT_CHUNK(8, 0, s8)
    if (W == 0) {
      wg_fence();
      mma_both<W, true>(sacc, oh, A_ADDR(s8), B_ADDR(xs(8)));
      wg_commit();
      wg_wait<1>();
      RELEASE_CHUNK(7, s7)
    }
    WAIT_CHUNK(9, 0, s9)
    TL(48);
    if (W == 0) {
      wg_fence();
      mma_mid<W, true>(oh, A_ADDR(s9), B_ADDR(xs(9)));
      wg_commit();
      mma_main<W, true>(sacc, A_ADDR(s9), B_ADDR(xs(9)));
      wg_commit();
      bar_arrive(5, 256);
      TL(49);
      wg_wait<1>();
      reg_fence(oh);
      mbar_wait(bud, BAR_XDONE, par);
      store_scaled(B_ADDR(1) + st_off, oh, qscale);
    } else {
      bar_sync(5, 256);
      wg_fence();
      mma_mid<W, true>(oh, A_ADDR(s7), B_ADDR(xs(7)));
      mma_mid<W, true>(oh, A_ADDR(s8), B_ADDR(xs(8)));
      mma_mid<W, true>(oh, A_ADDR(s9), B_ADDR(xs(9)));
      wg_commit();
      mma_main<W, true>(sacc, A_ADDR(s7), B_ADDR(xs(7)));
      wg_commit();
      mma_main<W, true>(sacc, A_ADDR(s8), B_ADDR(xs(8)));
      wg_commit();
      wg_wait<2>();
      reg_fence(oh);
      store_scaled(B_ADDR(1) + 10240 + st_off, oh, qscale);
      wg_fence();
      mma_main<W, true>(sacc, A_ADDR(s9), B_ADDR(xs(9)));
      wg_commit();
      bar_arrive(8, 256);
      TL(49);
      wg_wait<2>();
      RELEASE_CHUNK(7, s7)
      publish(BAR_QH, lane);
    }
    wg_wait<0>();
    reg_fence(sacc);
    TL(1);
    RELEASE_CHUNK(8, s8)
    RELEASE_CHUNK(9, s9)
    store_scaled(B_ADDR(2 * W) + st_off, sacc, qscale);
    if (W == 1) publish(BAR_QM, lane); else proxy_fence();
    TL(2);
    uint32_t sK = sK0, sV1 = 0;
    if (W == 0) {
      zero_regs(om); zero_regs(oh);
      reg_fence(om); reg_fence(oh);
      mbar_wait(bud, BAR_FULLA + sK0 * 8, pK0);
      bar_sync(8, 256);
      wg_fence();
      s_mma<0, false>(sacc, A_ADDR(sK));
      mbar_wait(bud, BAR_QH, par);
      TL(3);
      wg_fence();
      s_mma<1, true>(sacc, A_ADDR(sK));
      mbar_wait(bud, BAR_QM, par);
      TL(5);
      wg_fence();
      s_mma<2, true>(sacc, A_ADDR(sK));
      wg_commit();
      wg_commit();
      bar_arrive(2, 256);
    } else {
      uint32_t pV1;
      ring_pos(ring, idxV(0), sV1, pV1);
      mbar_wait(bud, BAR_FULLA + sK * 8, pK0);
      bar_sync(2, 256);
      wg_fence();
      s_mma<0, false>(sacc, A_ADDR(sK));
      s_mma<1, true>(sacc, A_ADDR(sK));
      s_mma<2, true>(sacc, A_ADDR(sK));
      wg_commit();
      TL(6);
      mbar_wait(bud, BAR_FULLA + sV1 * 8, pV1);
      mbar_wait(bud, BAR_PFULL, 0);
      TL(7);
      wg_fence();
      mma_both<W, false>(om, oh, A_ADDR(sV1), poth);
      wg_commit();
      bar_arrive(1, 256);
    }
    Ring rv;
    ring_pos(ring, idxV(W), rv.s0, rv.ph0);
#pragma unroll 1
    for (int jj = 0;; jj++) {
      wg_wait<1>();
      reg_fence(sacc);
      TL(8 + jj * 7);
      mbar_arrive2_if0(BAR_EMPTYA + sK * 8, tid);
      mbar_arrive_if0(BAR_EMPTYB + tid * 8, (tid >= 3) | (jj != 3));
#pragma unroll
      for (int J = 0; J < 10; J++) {
        stsm_t(pown + st_off + J * 2048, pack2(ex2(sacc[8 * J]), ex2(sacc[8 * J + 1])), pack2(ex2(sacc[8 * J + 2]), ex2(sacc[8 * J + 3])),
               pack2(ex2(sacc[8 * J + 4]), ex2(sacc[8 * J + 5])), pack2(ex2(sacc[8 * J + 6]), ex2(sacc[8 * J + 7])));
        if (W == 1 && (J == 2 || J == 5)) publish_generic(BAR_PMID + (J / 3) * 8, lane | (jj != 3));
        if (J == 4) {
          wg_wait<0>();
          mbar_arrive_if0(BAR_EMPTYA + sV1 * 8, tid | (W == 0 && jj == 0));
        }
      }
      publish(BAR_PFULL + W * 8, lane);
      TL(10 + jj * 7);
      if (jj == 3) break;
      uint32_t pK, pV1;
      ring_pos(rv, 1, sK, pK);
      ring_pos(rv, 2, sV1, pV1);
      mbar_wait(bud, BAR_FULLA + rv.s0 * 8, rv.ph0);
      bar_sync(1 + W, 256);
      wg_fence();
      mma_both<W, true>(om, oh, A_ADDR(rv.s0), pown);
      wg_commit();
      mbar_wait(bud, BAR_FULLA + sK * 8, pK);
      TL(11 + jj * 7);
      wg_fence();
      s_mma<0, false>(sacc, A_ADDR(sK));
      s_mma<1, true>(sacc, A_ADDR(sK));
      wg_commit();
      wg_wait<1>();
      mbar_arrive_if0(BAR_EMPTYA + rv.s0 * 8, tid);
      wg_fence();
      s_mma<2, true>(sacc, A_ADDR(sK));
      wg_commit();
      TL(13 + jj * 7);
      mbar_wait(bud, BAR_FULLA + sV1 * 8, pV1);
      mbar_wait(bud, BAR_PFREE + W * 8, jj & 1);
      mbar_wait(bud, BAR_PFULL + (1 - W) * 8, (jj + W) & 1);
      TL(14 + jj * 7);
      wg_fence();
      mma_both<W, true>(om, oh, A_ADDR(sV1), poth);
      wg_commit();
      bar_arrive(2 - W, 256);
      ring_advance(rv, 4);
    }
    uint32_t sV7, pV7;
    ring_pos(ring, idxV(7), sV7, pV7);
    prev = item;
    if (W == 1 && !DEBUG_TIMEOUT) item = next_item();
    if (W == 0) {
      uint32_t sV6, pV6;
      ring_pos(ring, idxV(6), sV6, pV6);
      mbar_wait(bud, BAR_FULLA + sV6 * 8, pV6);
      bar_sync(1, 256);
      wg_fence();
      mma_both<0, true>(om, oh, A_ADDR(sV6), pown);
      wg_commit();
      mbar_wait(bud, BAR_FULLA + sV7 * 8, pV7);
      wg_wait<0>();
      mbar_arrive_if0(BAR_EMPTYA + sV6 * 8, tid);
      mbar_wait(bud, BAR_PFULL + 8, 1);
      wg_fence();
      mma_both<0, true>(om, oh, A_ADDR(sV7), poth);
      wg_commit();
      bar_arrive(6, 256);
    } else {
      mbar_wait(bud, BAR_FULLA + sV7 * 8, pV7);
      bar_sync(6, 256);
    }
    TL(32);
    if (DEBUG_TIMEOUT) item = next_item(NEXT_ITEM + 4);
    else if (W == 0) item = next_item();
    if (item >= NITEMS) {
      if (W == 1) {
        wg_fence();
        mma_both<1, true>(om, oh, A_ADDR(sV7), pown);
        wg_commit();
      }
      wg_wait<0>();
      reg_fence(om); reg_fence(oh);
      TL(33);
      mbar_wait(bud, BAR_LFULL, par);
      mbar_arrive_if0(BAR_FREE, tid);
      TL(34);
      pack_first<W>(pk, om, oh, laddr);
      op = o_ptr(prev);
      store_groups<W, 0, 10>(op, pk, 1);
      pack_second<W, 0, 5>(pk, om, laddr);
      store_groups<W, 10, 15>(op, pk, 1);
      publish_generic(BAR_OFULL, lane);
      TL(35); TLG(63);
      TL_FLUSH();
      return item;
    }
    {
      if (W == 1) {
        wg_fence();
        mma_both<1, true>(om, oh, A_ADDR(sV7), pown);
        wg_commit();
      }
      WAIT_CHUNK(0, 26, s0)
      WAIT_CHUNK(1, 26, s1)
      if (W == 0) {
        wg_wait<0>();
        reg_fence(om); reg_fence(oh);
        TL(33);
        wg_fence();
        mma_main<W, false>(sacc, A_ADDR(s0), B_ADDR(xs(0)));
        wg_commit();
      } else {
        wg_fence();
        mma_main<W, false>(sacc, A_ADDR(s0), B_ADDR(xs(0)));
        mma_main<W, true>(sacc, A_ADDR(s1), B_ADDR(xs(1)));
        wg_commit();
        wg_wait<1>();
        reg_fence(om); reg_fence(oh);
        TL(33);
      }
      mbar_arrive_if0(BAR_EMPTYA + sV7 * 8, tid);
      mbar_wait(bud, BAR_LFULL, par);
      mbar_arrive_if0(BAR_EMPTYB + 24 + tid * 8, tid >= 2);
      TL(34);
      pack_first<W>(pk, om, oh, laddr);
      TL(36);
      wg_fence();
      mma_mid<W, false>(oh, A_ADDR(s0), B_ADDR(xs(0)));
      wg_commit();
      mma_mid<W, true>(oh, A_ADDR(s1), B_ADDR(xs(1)));
      if (W == 0) mma_main<W, true>(sacc, A_ADDR(s1), B_ADDR(xs(1)));
      wg_commit();
      TL(37);
      wg_wait<1>();
      RELEASE_CHUNK(0, s0)
      TL(35); TLG(63);
    }
    TL_FLUSH();
    TL(0); TLG(62);
    ring_advance(ring, 26);
    par ^= 1;
  }
}

__device__ __forceinline__ uint4 lds128(uint32_t a) {
  uint4 v;
  asm volatile("ld.shared.v4.b32 {%0,%1,%2,%3}, [%4];" : "=r"(v.x), "=r"(v.y), "=r"(v.z), "=r"(v.w) : "r"(a) : "memory");
  return v;
}
__device__ __forceinline__ void acc2(float& s, float& t, uint32_t w) {
  s += __uint_as_float(w << 16);
  t += __uint_as_float(w & 0xffff0000u);
}
__device__ __forceinline__ uint32_t badd2(uint32_t a, uint32_t b) { uint32_t r; asm("add.rn.bf16x2 %0, %1, %2;" : "=r"(r) : "r"(a), "r"(b)); return r; }
__device__ __forceinline__ void sum_unit(float& acc, uint32_t pb) {
  const uint4 v0 = lds128(pb), v1 = lds128(pb ^ 32), v2 = lds128(pb ^ 64), v3 = lds128(pb ^ 96);
  const uint32_t w0 = badd2(v0.x, v0.y), w1 = badd2(v0.z, v0.w);
  float s0 = acc + __uint_as_float(w0 << 16), t0 = __uint_as_float(w0 & 0xffff0000u);
  float s1 = __uint_as_float(w1 << 16), t1 = __uint_as_float(w1 & 0xffff0000u);
  acc2(s0, t0, badd2(v1.x, v1.y)); acc2(s1, t1, badd2(v1.z, v1.w));
  acc2(s0, t0, badd2(v2.x, v2.y)); acc2(s1, t1, badd2(v2.z, v2.w));
  acc2(s0, t0, badd2(v3.x, v3.y)); acc2(s1, t1, badd2(v3.z, v3.w));
  acc = (s0 + t0) + (s1 + t1);
}
__device__ __forceinline__ float bf_lo(uint32_t w) { return __uint_as_float(w << 16); }
__device__ __forceinline__ float bf_hi(uint32_t w) { return __uint_as_float(w & 0xffff0000u); }
__device__ __forceinline__ float bf_rn(float x) { return __bfloat162float(__float2bfloat16(x)); }
__device__ __forceinline__ void slow_item(const Params& p, int item, int hw) {
  const int blk = item >> 9, h = (item >> 4) & 31, b = item & 15;
#pragma unroll 1
  for (int n = hw; n < SQ; n += 3) {
    float q[6] = {0.f, 0.f, 0.f, 0.f, 0.f, 0.f};
    {
      const uint32_t* xr = (const uint32_t*)(p.xp[blk] + (size_t)(b * SQ + n) * DM);
      const uint32_t* wq = (const uint32_t*)(p.wqp[blk] + h * DH) + (tid_x() & 31);
#pragma unroll 2
      for (int k = 0; k < DM / 2; k++) {
        const uint32_t xv = xr[k];
#pragma unroll
        for (int i = 0; i < 3; i++) {
          const uint32_t w0 = wq[i * 32], w1 = wq[NH * DH / 2 + i * 32];
          q[2 * i] = fmaf(bf_lo(xv), bf_lo(w0), fmaf(bf_hi(xv), bf_lo(w1), q[2 * i]));
          q[2 * i + 1] = fmaf(bf_lo(xv), bf_hi(w0), fmaf(bf_hi(xv), bf_hi(w1), q[2 * i + 1]));
        }
        wq += NH * DH;
      }
    }
    const uint32_t q0 = pack2(q[0], q[1]), q1 = pack2(q[2], q[3]), q2 = pack2(q[4], q[5]);
    float o[6] = {0.f, 0.f, 0.f, 0.f, 0.f, 0.f}, m = -INFINITY, l = 0.f;
    const uint32_t* kg = (const uint32_t*)(p.kp[blk] + (size_t)(b * NH + h) * SK * DH) + (tid_x() & 31);
    const uint32_t* vg = (const uint32_t*)(p.vp[blk] + (size_t)(b * NH + h) * SK * DH) + (tid_x() & 31);
#pragma unroll 1
    for (int k = 0; k < SK; k++) {
      const uint32_t k0 = kg[0], k1 = kg[32], k2 = kg[64], v0 = vg[0], v1 = vg[32], v2 = vg[64];
      kg += DH / 2; vg += DH / 2;
      float sc = fmaf(bf_lo(q0), bf_lo(k0), bf_hi(q0) * bf_hi(k0));
      sc = fmaf(bf_lo(q1), bf_lo(k1), fmaf(bf_hi(q1), bf_hi(k1), sc));
      sc = fmaf(bf_lo(q2), bf_lo(k2), fmaf(bf_hi(q2), bf_hi(k2), sc));
#pragma unroll
      for (int d = 16; d; d >>= 1) sc += __shfl_xor_sync(0xffffffffu, sc, d);
      sc = bf_rn(bf_rn(sc) * 0.07216878364870322f);
      const float mn = fmaxf(m, sc), a = ex2((m - mn) * 1.4426950408889634f), pr = ex2((sc - mn) * 1.4426950408889634f);
      m = mn;
      l = fmaf(l, a, pr);
      o[0] = fmaf(o[0], a, pr * bf_lo(v0)); o[1] = fmaf(o[1], a, pr * bf_hi(v0));
      o[2] = fmaf(o[2], a, pr * bf_lo(v1)); o[3] = fmaf(o[3], a, pr * bf_hi(v1));
      o[4] = fmaf(o[4], a, pr * bf_lo(v2)); o[5] = fmaf(o[5], a, pr * bf_hi(v2));
    }
    float inv;
    asm("rcp.approx.ftz.f32 %0, %1;" : "=f"(inv) : "f"(l));
    const int lane = tid_x() & 31;
    const int r = n & 15, c = 4 * ((r & 7) >> 1) + 2 * (r >> 3) + (r & 1);
    char* on = o_slot(item) + (lane >> 2) * 256 + (lane & 3) * 64 + (n >> 4) * 2048 +
               (((c >> 3) ^ ((lane >> 1) & 1)) << 4) + (c & 7) * 2;
#pragma unroll
    for (int i = 0; i < 3; i++) {
      *(__nv_bfloat16*)(on + i * B_SLOT) = __float2bfloat16(o[2 * i] * inv);
      *(__nv_bfloat16*)(on + i * B_SLOT + 32) = __float2bfloat16(o[2 * i + 1] * inv);
    }
  }
}
__device__ __forceinline__ void attn_helper(const Params& p, int hw, int item, int epoch) {
  int bud = WAIT_BUDGET;
  if (item < PF_N && hw < 2) {
    const char* g = (const char*)(hw ? p.vp[0] : p.kp[0]) + (size_t)(((item & 15) * NH + (item >> 4)) * SK) * DH * 2;
    const long long t0 = clock64();
#pragma unroll 1
    for (int i = 0; i < 32; i++) {
      while (clock64() - t0 < PF_WAIT + i * PF_GAP) __nanosleep(50);
      for (int k = 0; k < 6; k++) asm volatile("prefetch.global.L2 [%0];" ::"l"(g + i * 6144 + k * 1024 + (tid_x() & 31) * 32));
      __syncwarp();
    }
  }
#pragma unroll 1
  for (int it = 0; item < NITEMS; it++) {
    const uint32_t par = it & 1;
    int lane = tid_x() & 31;
    const int r = lane >> 1;
    const uint32_t a0 = B_ADDR(3) + (16 * hw + r) * 128 + (lane & 1) * 16 + ((r & 3) << 5);
    float acc[4] = {0.f, 0.f, 0.f, 0.f};
#pragma unroll 1
    for (int j = 0; j < 8; j++) {
      const uint32_t pb = a0 + (j & 1) * B_SLOT, bfull = BAR_PFULL + (j & 1) * 8, pfull = (j >> 1) & 1;
      mbar_wait(bud, j == 7 ? BAR_PMID : bfull, j == 7 ? par : pfull);
      sum_unit(acc[0], pb);
      if (j == 7) mbar_wait(bud, BAR_PMID + 8, par);
      sum_unit(acc[1], pb + 6144);
      if (j == 7) mbar_wait(bud, bfull, pfull);
      sum_unit(acc[2], pb + 2 * 6144);
      if (hw == 0) sum_unit(acc[3], pb + 3 * 6144);
      __syncwarp();
      mbar_arrive_if0(BAR_PFREE + (j & 1) * 8, lane);
      if (j == 5 && hw == 2) {
        if (lane == 0) TLP(60);
        if (item >= ORING && item < OFRESH) flag_wait(bud, &g_done[item - ORING], (epoch + 1) * 2);
        if (lane == 0) TLP(61);
      }
    }
    bool bad = false;
    const uint32_t la = SB + OFF_L + (((r & 7) >> 1) * 40 + 2 * (r >> 3) + (r & 1) + 4 * hw) * 4;
#pragma unroll
    for (int u = 0; u < 4; u++) {
      const float l = acc[u] + __shfl_xor_sync(0xffffffffu, acc[u], 1);
      if (u < 3 || hw == 0) {
        bad |= !(l >= 8.8817841970012523e-16f && l <= 1.125899906842624e15f);
        float inv;
        asm("rcp.approx.ftz.f32 %0, %1;" : "=f"(inv) : "f"(l));
        asm volatile("st.shared.f32 [%0], %1;" ::"r"(la + u * 48), "f"(inv) : "memory");
      }
    }
    publish_generic(BAR_LFULL, lane);
    if (lane == 0) TLP(40 + hw * 4);
    uint32_t anybad;
    asm volatile("{\n.reg .pred p, q;\nsetp.ne.u32 p, %1, 0;\nbarrier.red.or.pred q, 7, 96, p;\nselp.u32 %0, 1, 0, q;\n}\n"
                 : "=r"(anybad) : "r"((uint32_t)bad) : "memory");
    if (__any_sync(0xffffffffu, anybad)) {
      mbar_wait(bud, BAR_OFULL, par);
      slow_item(p, item, hw);
      bar_sync(7, 96);
    }
    if (hw == 1) {
      mbar_wait(bud, BAR_OFULL, par);
      if ((tid_x() & 31) == 0) {
        TLP(41 + hw * 4);
        asm volatile("red.release.gpu.global.add.s32 [%0], 1;" ::"l"(&g_ready[item]) : "memory");
        TLP(42 + hw * 4);
      }
      __syncwarp();
    }
    item = next_item();
  }
}

__device__ __forceinline__ int attn_producer(const Params& p, int item) {
  int bud = WAIT_BUDGET;
  uint32_t sa = 0, pa = 1;
  const uint64_t pol = evict_first_policy();
  const bool draws = item >= N_OCTA;
  const int delay = start_delay(item);
  {
    const long long t0 = clock64();
    while (clock64() - t0 < delay) __nanosleep(100);
  }
#pragma unroll 1
  for (int it = 0; item < NITEMS; it++) {
    const int blk = item >> 9, h = (item >> 4) & 31, b = item & 15;
    const int row0 = (b * NH + h) * SK;
#pragma unroll
    for (int c = 0; c < 10; c++) {
      if (c >= NSLOT || (it | delay)) {
        mbar_wait(bud, BAR_EMPTYA + sa * 8, pa);
        TLP(c);
        mbar_expect(BAR_FULLA + sa * 8, A_SLOT + B_SLOT);
        tma3d(A_ADDR(sa), &p.wq[blk], BAR_FULLA + sa * 8, 0, c * 64, h * 3);
        mbar_wait(bud, BAR_EMPTYB + xs(c) * 8, c < NSLOT);
        TLP(10 + c);
        tma2d(B_ADDR(xs(c)), &p.x[blk], BAR_FULLA + sa * 8, c * 64, b * SQ);
      }
      if (++sa == NSLOT) { sa = 0; pa ^= 1; }
    }
#pragma unroll
    for (int i = 0; i < 16; i++) {
      const bool isK = (i == 0) || ((i & 1) && i < 15);
      const int j = i == 0 ? 0 : (i == 15 ? 7 : (isK ? (i + 1) >> 1 : (i - 2) >> 1));
      mbar_wait(bud, BAR_EMPTYA + sa * 8, pa);
      TLP(20 + i);
      if (i == 11) item = draws ? NCTA + (int)atomicInc(&g_ticket, NITEMS - NCTA + N_ATT - 1) : NITEMS;
      if (i == 13) asm volatile("st.shared.s32 [%0], %1;" ::"r"(NEXT_ITEM), "r"(item) : "memory");
      mbar_expect(BAR_FULLA + sa * 8, A_SLOT);
      tma3d_hint(A_ADDR(sa), isK ? &p.k[blk] : &p.v[blk], BAR_FULLA + sa * 8, 0, row0 + j * 64, 0, pol);
      if (++sa == NSLOT) { sa = 0; pa ^= 1; }
    }
  }
  return item;
}

struct OJob { int tile, part, c0, n; };
__device__ __forceinline__ OJob get_ojob(int cta, int last) {
  if (cta < N_OCTA) return OJob{O_PAIR ? ((cta & 15) << 1) | (cta >> 4) : cta, 0, 0, CHUNK1};
  const int u = last - NITEMS, part = 1 + (u >> 5), tile = part == 3 ? 95 - u : u & 31;
  const int c1 = CHUNK1, c2 = c1 + LEN1 - ((tile * LSLOPE1 + 16) >> 5), c3 = c2 + LEN2 - ((tile * LSLOPE2 + 16) >> 5);
  return OJob{tile, part, part == 1 ? c1 : part == 2 ? c2 : c3, part == 1 ? c2 - c1 + 1 : part == 2 ? c3 - c2 + 1 : part == 3 ? 189 - c3 + 1 : 0};
}
__device__ __forceinline__ uint32_t first_stage(const OJob& job) { return job.part ? (uint32_t)(300 - job.n) % 3 : 0; }

template <int W>
__device__ __forceinline__ void oproj_consumer(const Params& p, const OJob job) {
  int bud = WAIT_BUDGET;
  const int tid = threadIdx.x & 127, lane = tid & 31, warp = tid >> 5;
  const int qrow = 8 * ((lane >> 1) & 1) + 4 * (lane >> 4) + 2 * ((lane >> 2) & 1) + (lane & 1);
  const uint32_t st_off = qrow * 128 + (((2 * warp + ((lane >> 3) & 1)) ^ (qrow & 7)) << 4);
  float a0[80], a1[80], ah[40];
  zero_regs(a0); zero_regs(a1); zero_regs(ah);
  int left = job.n, step = 0;
  uint32_t st = first_stage(job), ph = 0;
#pragma unroll 1
  while (left) {
    const int nc = left > 3 * NH ? 3 * NH : left;
    left -= nc;
#pragma unroll 1
    for (int c = 0; c < nc; c++) {
      mbar_wait(bud, BAR_GFULL + st * 8, (ph >> st) & 1);
      ph ^= 1 << st;
      wg_fence();
      const uint32_t la = lo_sw(SB + st * O_STAGE), lb = lo_o(SB + st * O_STAGE + O_AB);
#define O_STEP(ks, sc)                                                        \
  mma80r<1, 1, 2 * 8192 + ks * 2048, W * 10240 + ks * 512>(ah, la, lb, sc);   \
  mma160r<1, 1, (W * 3) * 8192 + ks * 2048, ks * 512>(a0, la, lb, sc);        \
  mma160r<1, 1, (W * 3 + 1) * 8192 + ks * 2048, ks * 512>(a1, la, lb, sc);
      O_STEP(0, c != 0) O_STEP(1, 1)
      wg_commit();
      wg_wait<1>();
      mbar_arrive_if0(BAR_GEMPTY + (st == 0 ? 2 : st - 1) * 8, tid | (c == 0));
      wg_fence();
      O_STEP(2, 1) O_STEP(3, 1)
#undef O_STEP
      wg_commit();
      if (++st == 3) {
        st = 0;
        if (W == 0)
          asm volatile("{\n.reg .pred p;\nsetp.eq.u32 p, %1, 0;\n@p red.relaxed.gpu.global.add.s32 [%0], 1;\n}\n"
                       ::"l"(&g_done[step * 16 + (job.tile >> 1)]), "r"(tid | job.part) : "memory");
        TLG(step);
        step++;
      }
    }
    wg_wait<0>();
    reg_fence(a0); reg_fence(a1); reg_fence(ah);
    mbar_arrive_if0(BAR_GEMPTY + (st - 1) * 8, tid | (st == 0));
    const uint32_t sg = SB + O_OUT + st_off;
    if (W == 1) {
      bar_arrive(3, 256);
      store_scaled(sg + 3 * B_SLOT, a0, 1.0f);
      publish(BAR_GOUT + 24, lane);
      bar_sync(9, 256);
      store_scaled(sg + 2 * B_SLOT + 10240, ah, 1.0f);
      publish(BAR_GOUT + 16, lane);
      store_scaled(sg + 4 * B_SLOT, a1, 1.0f);
      publish(BAR_GOUT + 32, lane);
    } else {
      bar_arrive(9, 256);
      bar_sync(3, 256);
      store_scaled(sg, a0, 1.0f);
      publish(BAR_GOUT, lane);
      store_scaled(sg + B_SLOT, a1, 1.0f);
      publish(BAR_GOUT + 8, lane);
      store_scaled(sg + 2 * B_SLOT, ah, 1.0f);
      publish(BAR_GOUT + 16, lane);
    }
  }
  TL_FLUSH();
  TLG(0);
  float acc[7][8];
  uint32_t in[7], blk[7];
#pragma unroll
  for (int i = 0; i < 7; i++) {
    const int e = min(i * 256 + W * 128 + tid, 1599), r = e / 40, cc = e % 40;
    in[i] = r * 128 + (((cc ^ r) & 7) << 4);
    blk[i] = cc >> 3;
#pragma unroll
    for (int k = 0; k < 8; k++) acc[i][k] = 0.f;
  }
  bar_sync(10, 256);
#pragma unroll 1
  for (int q = 0; q < 4; q++) {
    if (q) mbar_wait(bud, BAR_GRED + (q - 1) * 8, 0);
    if (q == 3) TLG(1);
    const uint32_t base = q ? SB + (q - 1) * 25600 : SB + O_OUT + job.part * 5120, bs = q ? 5120 : B_SLOT;
    uint4 v[7];
#pragma unroll
    for (int i = 0; i < 7; i++) v[i] = lds128(base + blk[i] * bs + in[i]);
#pragma unroll
    for (int i = 0; i < 7; i++) {
      acc[i][0] += bf_lo(v[i].x); acc[i][1] += bf_hi(v[i].x); acc[i][2] += bf_lo(v[i].y); acc[i][3] += bf_hi(v[i].y);
      acc[i][4] += bf_lo(v[i].z); acc[i][5] += bf_hi(v[i].z); acc[i][6] += bf_lo(v[i].w); acc[i][7] += bf_hi(v[i].w);
    }
  }
  uint4* go = (uint4*)p.outp + ((job.tile >> 1) * SQ + job.part * 40) * (2 * DM / 8) + DM / 8 + (job.tile & 1) * 40;
#pragma unroll
  for (int i = 0; i < 7; i++) {
    const int r = in[i] >> 7, cc = blk[i] * 8 + (((in[i] >> 4) ^ r) & 7);
    if (i * 256 + W * 128 + tid < 1600)
      go[r * (2 * DM / 8) + cc] = make_uint4(pack2(acc[i][0], acc[i][1]), pack2(acc[i][2], acc[i][3]), pack2(acc[i][4], acc[i][5]), pack2(acc[i][6], acc[i][7]));
  }
  TLG(2);
  TL_FLUSH();
}

__device__ __forceinline__ void oproj_producer(const Params& p, const OJob job, int target) {
  int bud = WAIT_BUDGET;
  const uint64_t polo = evict_first_policy();
  mbar_wait(bud, BAR_FREE, 0);
  uint32_t st = first_stage(job), ph = 7;
  int seen = -1;
#pragma unroll 1
  for (int i = 0; i < job.n; i++) {
    const int c = job.part && i == job.n - 1 ? 188 + job.part : job.c0 + i, step = c / 3, kb = c - 3 * step;
    const int item = step * 16 + (job.tile >> 1);
    if (step != seen) {
      flag_wait(bud, &g_ready[item], target);
      asm volatile("fence.proxy.async.global;" ::: "memory");
      seen = step;
    }
    const uint32_t dst = SB + st * O_STAGE, bar = BAR_GFULL + st * 8;
    const char* og = o_slot(item) + kb * B_SLOT;
    mbar_wait(bud, BAR_GEMPTY + st * 8, (ph >> st) & 1);
    ph ^= 1 << st;
    mbar_expect(bar, O_STAGE);
    tma3d(dst, &p.wo[step >> 5], bar, 0, (c - (step >> 5) * 3 * NH) * 64, (job.tile & 1) * 5);
    bulk_load_hint(dst + O_AB, og, B_SLOT, bar, polo);
    if (++st == 3) st = 0;
  }
  mbar_wait(bud, BAR_GEMPTY, ph & 1);
  mbar_wait(bud, BAR_GEMPTY + 8, (ph >> 1) & 1);
  uint32_t todo = 15 & ~(1 << job.part), dst = SB, bar = BAR_GRED;
  while (todo) {
#pragma unroll 1
    for (int q = 0; q < 4; q++) {
      if (!((todo >> q) & 1)) continue;
      int v;
      asm volatile("ld.acquire.gpu.global.s32 %0, [%1];" : "=r"(v) : "l"(&g_pcnt[job.tile * 4 + q]) : "memory");
      if (v - target < 0 && --bud > 0) continue;
      asm volatile("fence.proxy.async.global;" ::: "memory");
      mbar_expect(bar, 25600);
      for (int k = 0; k < 5; k++)
        tma2d(dst + k * 5120, &p.part, bar, (job.tile & 1) * 320 + k * 64, q * NB * SQ + (job.tile >> 1) * SQ + job.part * 40);
      todo &= ~(1 << q);
      dst += 25600;
      bar += 8;
    }
  }
}

__device__ __forceinline__ void oproj_storer(const Params& p, const OJob job) {
  int bud = WAIT_BUDGET;
  const int col = (job.tile & 1) * 320, row = (job.tile >> 1) * SQ;
  if (job.part == 0) {
    for (int k = 0; k < 3; k++) {
      mbar_wait(bud, BAR_GOUT + k * 8, 0);
      tma_store2d(&p.out, SB + O_OUT + k * B_SLOT, col + k * 64, row);
    }
    asm volatile("cp.async.bulk.commit_group;" ::: "memory");
    asm volatile("cp.async.bulk.wait_group.read 0;" ::: "memory");
    mbar_arrive2_if0(BAR_GEMPTY + 16, 0);
    mbar_wait(bud, BAR_GFULL + 16, 0);
    for (int k = 3; k < 5; k++) {
      mbar_wait(bud, BAR_GOUT + k * 8, 0);
      tma_store2d(&p.out, SB + O_OUT + k * B_SLOT, col + k * 64, row);
      asm volatile("cp.async.bulk.commit_group;" ::: "memory");
      asm volatile("cp.async.bulk.wait_group.read 0;" ::: "memory");
      __nanosleep(1000);
    }
  }
#pragma unroll 1
  for (int i = 0; i < 5; i++) {
    const int k = (0x42103 >> (4 * i)) & 15;
    mbar_wait(bud, BAR_GOUT + k * 8, job.part == 0);
    for (int q = 1; q < 4; q++) {
      const int sh = (job.part + q) & 3;
      tma_store2d(&p.part, SB + O_OUT + k * B_SLOT + sh * 5120, col + k * 64, job.part * NB * SQ + row + sh * 40);
    }
  }
  asm volatile("cp.async.bulk.commit_group;" ::: "memory");
  asm volatile("cp.async.bulk.wait_group 0;" ::: "memory");
  asm volatile("fence.proxy.async.global;" ::: "memory");
  asm volatile("red.release.gpu.global.add.s32 [%0], 1;" ::"l"(&g_pcnt[job.tile * 4 + job.part]) : "memory");
}

__global__ void __launch_bounds__(384, 1) fused_kernel(const __grid_constant__ Params p) {
  extern __shared__ __align__(1024) char smem_raw[];
  if ((smem_u32(smem_raw) & 0xFFFFFFu) != SB) return;
  const int cta = (((blockIdx.x / PERM_G) * PERM_M) % (NCTA / PERM_G)) * PERM_G + (blockIdx.x % PERM_G);
  const int warp = __shfl_sync(0xffffffffu, threadIdx.x >> 5, 0);
  if (threadIdx.x == 0) {
    for (int i = 0; i < NSLOT; i++) { mbar_init(BAR_FULLA + i * 8, 1); mbar_init(BAR_EMPTYA + i * 8, 2); mbar_init(BAR_EMPTYB + i * 8, 2); }
    proxy_fence();
    if (start_delay(cta) == 0) {
#pragma unroll 1
      for (int c = 0; c < NSLOT; c++) {
        mbar_expect(BAR_FULLA + c * 8, A_SLOT + B_SLOT);
        tma3d(A_ADDR(c), &p.wq[0], BAR_FULLA + c * 8, 0, c * 64, (cta >> 4) * 3);
        tma2d(B_ADDR(c), &p.x[0], BAR_FULLA + c * 8, c * 64, (cta & 15) * SQ);
      }
    }
  }
  if (threadIdx.x == 64) {
    mbar_init(BAR_XDONE, 1); mbar_init(BAR_QH, 4); mbar_init(BAR_QM, 4);
    mbar_init(BAR_PFULL, 4); mbar_init(BAR_PFULL + 8, 4); mbar_init(BAR_PFREE, 3); mbar_init(BAR_PFREE + 8, 3);
    mbar_init(BAR_LFULL, 3); mbar_init(BAR_PMID, 4); mbar_init(BAR_PMID + 8, 4); mbar_init(BAR_OFULL, 8);
  }
  if (threadIdx.x == 96) {
    for (int i = 0; i < O_NST; i++) { mbar_init(BAR_GFULL + i * 8, 1); mbar_init(BAR_GEMPTY + i * 8, 2); }
    for (int i = 0; i < 5; i++) mbar_init(BAR_GOUT + i * 8, i == 2 ? 8 : 4);
    mbar_init(BAR_GRED, 1); mbar_init(BAR_GRED + 8, 1); mbar_init(BAR_GRED + 16, 1); mbar_init(BAR_FREE, 2);
    proxy_fence();
  }
  if (warp == 1 && threadIdx.x < 32 + 12) asm volatile("prefetch.tensormap [%0];" ::"l"(&p.x[0] + (threadIdx.x - 32)) : "memory");
  __syncthreads();
  if (warp >= 8) {
    asm volatile("setmaxnreg.dec.sync.aligned.u32 40;");
    if (warp == 8) {
      if (elect_one()) {
        const OJob job = get_ojob(cta, attn_producer(p, cta));
        const int epoch = *(volatile int*)&g_epoch[cta];
        *(volatile int*)&g_epoch[cta] = epoch + 1;
        if (job.n) oproj_producer(p, job, epoch + 1);
      }
    } else {
      const int epoch = __shfl_sync(0xffffffffu, *(volatile int*)&g_epoch[cta], 0);
      attn_helper(p, warp - 9, cta, epoch);
      if (warp == 9) {
        const OJob job = get_ojob(cta, next_item());
        if (job.n && elect_one()) oproj_storer(p, job);
      }
    }
  } else {
    asm volatile("setmaxnreg.inc.sync.aligned.u32 232;");
    if (warp < 4) {
      const OJob job = get_ojob(cta, attn_consumer<0>(cta));
      if (job.n) oproj_consumer<0>(p, job);
    } else {
      const OJob job = get_ojob(cta, attn_consumer<1>(cta));
      if (job.n) oproj_consumer<1>(p, job);
    }
  }
}

typedef CUresult (*EncodeFn)(CUtensorMap*, CUtensorMapDataType, cuuint32_t, void*, const cuuint64_t*, const cuuint64_t*, const cuuint32_t*,
                             const cuuint32_t*, CUtensorMapInterleave, CUtensorMapSwizzle, CUtensorMapL2promotion, CUtensorMapFloatOOBfill);

void make3d(EncodeFn enc, CUtensorMap* m, const void* ptr, uint64_t rows, uint64_t cols, uint32_t box_rows, uint32_t box_blocks,
            CUtensorMapL2promotion promo = CU_TENSOR_MAP_L2_PROMOTION_L2_128B) {
  cuuint64_t gd[3] = {64, rows, cols / 64};
  cuuint64_t gs[2] = {cols * 2, 128};
  cuuint32_t bd[3] = {64, box_rows, box_blocks}, es[3] = {1, 1, 1};
  enc(m, CU_TENSOR_MAP_DATA_TYPE_BFLOAT16, 3, (void*)ptr, gd, gs, bd, es, CU_TENSOR_MAP_INTERLEAVE_NONE, CU_TENSOR_MAP_SWIZZLE_128B,
      promo, CU_TENSOR_MAP_FLOAT_OOB_FILL_NONE);
}
void make2d(EncodeFn enc, CUtensorMap* m, const void* ptr, uint64_t rows, uint64_t cols, uint32_t box_rows) {
  cuuint64_t gd[2] = {cols, rows};
  cuuint64_t gs[1] = {cols * 2};
  cuuint32_t bd[2] = {64, box_rows}, es[2] = {1, 1};
  enc(m, CU_TENSOR_MAP_DATA_TYPE_BFLOAT16, 2, (void*)ptr, gd, gs, bd, es, CU_TENSOR_MAP_INTERLEAVE_NONE, CU_TENSOR_MAP_SWIZZLE_128B,
      CU_TENSOR_MAP_L2_PROMOTION_L2_128B, CU_TENSOR_MAP_FLOAT_OOB_FILL_NONE);
}

}

extern "C" void kernel_launch(void* const* d_in, const int* in_sizes, int n_in, void* d_out, int out_size) {
  static EncodeFn enc = nullptr;
  static void* part = nullptr;
  if (!enc) {
    cudaGetSymbolAddress(&part, g_part);
    cudaDriverEntryPointQueryResult qr;
    cudaGetDriverEntryPoint("cuTensorMapEncodeTiled", (void**)&enc, cudaEnableDefault, &qr);
    cudaFuncSetAttribute(fused_kernel, cudaFuncAttributeMaxDynamicSharedMemorySize, SMEM_BYTES);
  }
  Params p;
  for (int s = 0; s < 2; s++) {
    make2d(enc, &p.x[s], d_in[5 * s + 0], NB * SQ, DM, SQ);
    make3d(enc, &p.k[s], d_in[5 * s + 1], (uint64_t)NB * NH * SK, DH, 64, 3);
    make3d(enc, &p.v[s], d_in[5 * s + 2], (uint64_t)NB * NH * SK, DH, 64, 3);
    make3d(enc, &p.wq[s], d_in[5 * s + 3], DM, NH * DH, 64, 3);
    make3d(enc, &p.wo[s], d_in[5 * s + 4], NH * DH, DM, 64, 5);
    p.xp[s] = (const __nv_bfloat16*)d_in[5 * s + 0];
    p.wqp[s] = (const __nv_bfloat16*)d_in[5 * s + 3];
    p.kp[s] = (const __nv_bfloat16*)d_in[5 * s + 1];
    p.vp[s] = (const __nv_bfloat16*)d_in[5 * s + 2];
  }
  make2d(enc, &p.out, d_out, NB * SQ, 2 * DM, SQ);
  make2d(enc, &p.part, part, 4 * NB * SQ, DM, 40);
  p.outp = (__nv_bfloat16*)d_out;
  fused_kernel<<<NCTA, 384, SMEM_BYTES>>>(p);
}
```

```cpp
#include <cuda_runtime.h>
#include <cuda_bf16.h>
#include <cuda.h>
#include <stdint.h>

#define DEBUG_TIMEOUT 0

namespace {

constexpr int SQ = 160, DM = 640, NH = 32, SK = 512, DH = 192, NB = 16;
constexpr int NITEMS = 2 * NB * NH;
constexpr int NCTA = 132, N_OCTA = 32;
constexpr int ORING = 192, OFRESH = 800, CHUNK1 = 157, LEN1 = 18, LEN2 = 13, LSLOPE1 = 4, LSLOPE2 = 4;
constexpr int STAG_G = 4, PERM_G = 4, STAG_A0 = 19, STAG_SLOPE = 275, PERM_M = 20, PF_N = 32, PF_WAIT = 1500, PF_GAP = 300;
constexpr int OSLOTS = ORING + NITEMS - OFRESH;
constexpr int A_SLOT = 24576, B_SLOT = 20480, NSLOT = 5;
constexpr int OFF_A = 0;
constexpr int OFF_B = NSLOT * A_SLOT;
constexpr int O_STAGE = 61440, O_AB = 40960, O_NST = 3;
constexpr int OFF_L = OFF_B + NSLOT * B_SLOT;
constexpr int OFF_BAR = OFF_L + 160 * 4;
constexpr int SMEM_BYTES = OFF_BAR + 512 + 512;
constexpr int O_OUT = 2 * O_STAGE;
static_assert(O_OUT + 5 * B_SLOT <= OFF_L, "smem layout");
constexpr uint32_t SB = 1024;
constexpr uint32_t BARS = SB + OFF_BAR;
constexpr uint32_t BAR_FULLA = BARS, BAR_EMPTYA = BARS + 40, BAR_PMID = BARS + 80, BAR_EMPTYB = BARS + 120, BAR_XDONE = BARS + 160,
                   BAR_QH = BARS + 168, BAR_QM = BARS + 96, BAR_PFULL = BARS + 184, BAR_PFREE = BARS + 200, BAR_LFULL = BARS + 216,
                   BAR_OFULL = BARS + 224, BAR_GFULL = BARS + 248, BAR_GEMPTY = BARS + 280, BAR_GOUT = BARS + 328, BAR_GRED = BARS + 368,
                   BAR_FREE = BARS + 240, NEXT_ITEM = BARS + 320;
constexpr int O_ITEM_BYTES = SQ * DH * 2;

struct alignas(64) Params {
  CUtensorMap x[2], wq[2], k[2], v[2], wo[2], out, part;
  __nv_bfloat16* outp;
  const __nv_bfloat16 *xp[2], *wqp[2], *kp[2], *vp[2];
};

__device__ uint4 g_o[(size_t)OSLOTS * O_ITEM_BYTES / 16];
__device__ uint4 g_part[4 * NB * SQ * DM / 8];
__device__ __align__(16) int g_pcnt[4 * N_OCTA];
__device__ int g_ready[NITEMS];
__device__ int g_done[NITEMS];
__device__ int g_ticket;
__device__ int g_go;
__device__ int g_epoch[NCTA];

#define TLE(id)
#define TLP(id)
#define TLG(id)
#define TL(id)
#define TL_FLUSH()
__device__ __forceinline__ uint32_t smem_u32(const void* p) { return (uint32_t)__cvta_generic_to_shared(p); }
__device__ __forceinline__ void wg_fence() { asm volatile("wgmma.fence.sync.aligned;" ::: "memory"); }
__device__ __forceinline__ void wg_commit() { asm volatile("wgmma.commit_group.sync.aligned;" ::: "memory"); }
template <int N> __device__ __forceinline__ void wg_wait() { asm volatile("wgmma.wait_group.sync.aligned %0;" ::"n"(N) : "memory"); }
template <int N> __device__ __forceinline__ void reg_fence(float (&d)[N]) {
#pragma unroll
  for (int i = 0; i < N; i++) asm volatile("" : "+f"(d[i])::"memory");
}
template <int N> __device__ __forceinline__ void zero_regs(float (&d)[N]) {
#pragma unroll
  for (int i = 0; i < N; i++) d[i] = 0.f;
}
__device__ __forceinline__ void proxy_fence() { asm volatile("fence.proxy.async.shared::cta;" ::: "memory"); }
__device__ __forceinline__ void mbar_init(uint32_t bar, int cnt) { asm volatile("mbarrier.init.shared::cta.b64 [%0], %1;" ::"r"(bar), "r"(cnt) : "memory"); }
__device__ __forceinline__ void mbar_arrive_if0(uint32_t bar, uint32_t sel) {
  asm volatile("{\n.reg .pred p;\nsetp.eq.u32 p, %1, 0;\n@p mbarrier.arrive.shared::cta.b64 _, [%0];\n}\n" ::"r"(bar), "r"(sel) : "memory");
}
__device__ __forceinline__ void mbar_arrive2_if0(uint32_t bar, uint32_t sel) {
  asm volatile("{\n.reg .pred p;\nsetp.eq.u32 p, %1, 0;\n@p mbarrier.arrive.shared::cta.b64 _, [%0], 2;\n}\n" ::"r"(bar), "r"(sel) : "memory");
}
__device__ __forceinline__ void mbar_expect(uint32_t bar, uint32_t bytes) {
  asm volatile("mbarrier.arrive.expect_tx.shared::cta.b64 _, [%0], %1;" ::"r"(bar), "r"(bytes) : "memory");
}
__device__ __forceinline__ void mbar_wait(int& bud, uint32_t bar, uint32_t parity) {
  asm volatile(
      "{\n.reg .pred p;\n"
      "LW:\n"
      "mbarrier.try_wait.parity.shared::cta.b64 p, [%0], %1;\n"
      "@!p bra LW;\n}\n" ::"r"(bar), "r"(parity) : "memory");
}
constexpr int WAIT_BUDGET = 1 << 22;
__device__ __forceinline__ bool elect_one() {
  uint32_t p;
  asm volatile("{\n.reg .pred p;\nelect.sync _|p, 0xffffffff;\nselp.u32 %0, 1, 0, p;\n}\n" : "=r"(p));
  return p;
}
__device__ __forceinline__ void tma2d(uint32_t dst, const CUtensorMap* m, uint32_t bar, int c0, int c1) {
  asm volatile("cp.async.bulk.tensor.2d.shared::cluster.global.mbarrier::complete_tx::bytes [%0], [%1, {%3, %4}], [%2];"
               ::"r"(dst), "l"(m), "r"(bar), "r"(c0), "r"(c1) : "memory");
}
__device__ __forceinline__ void tma3d(uint32_t dst, const CUtensorMap* m, uint32_t bar, int c0, int c1, int c2) {
  asm volatile("cp.async.bulk.tensor.3d.shared::cluster.global.mbarrier::complete_tx::bytes [%0], [%1, {%3, %4, %5}], [%2];"
               ::"r"(dst), "l"(m), "r"(bar), "r"(c0), "r"(c1), "r"(c2) : "memory");
}
__device__ __forceinline__ void tma3d_hint(uint32_t dst, const CUtensorMap* m, uint32_t bar, int c0, int c1, int c2, uint64_t pol) {
  asm volatile("cp.async.bulk.tensor.3d.shared::cluster.global.mbarrier::complete_tx::bytes.L2::cache_hint [%0], [%1, {%3, %4, %5}], [%2], %6;"
               ::"r"(dst), "l"(m), "r"(bar), "r"(c0), "r"(c1), "r"(c2), "l"(pol) : "memory");
}
__device__ __forceinline__ void tma_store2d(const CUtensorMap* m, uint32_t src, int c0, int c1) {
  asm volatile("cp.async.bulk.tensor.2d.global.shared::cta.bulk_group [%0, {%2, %3}], [%1];" ::"l"(m), "r"(src), "r"(c0), "r"(c1) : "memory");
}
__device__ __forceinline__ void bar_sync(int id, int n) { asm volatile("bar.sync %0, %1;" ::"r"(id), "r"(n) : "memory"); }
__device__ __forceinline__ void bar_arrive(int id, int n) { asm volatile("bar.arrive %0, %1;" ::"r"(id), "r"(n) : "memory"); }
__device__ __forceinline__ float ex2(float x) { float y; asm("ex2.approx.ftz.f32 %0, %1;" : "=f"(y) : "f"(x)); return y; }
__device__ __forceinline__ uint32_t pack2(float lo, float hi) { uint32_t r; asm("cvt.rn.bf16x2.f32 %0, %1, %2;" : "=r"(r) : "f"(hi), "f"(lo)); return r; }
__device__ __forceinline__ void stsm_t(uint32_t a, uint32_t r0, uint32_t r1, uint32_t r2, uint32_t r3) {
  asm volatile("stmatrix.sync.aligned.m8n8.x4.trans.shared.b16 [%0], {%1,%2,%3,%4};" ::"r"(a), "r"(r0), "r"(r1), "r"(r2), "r"(r3) : "memory");
}
__device__ __forceinline__ uint64_t evict_first_policy() {
  uint64_t pol;
  asm volatile("createpolicy.fractional.L2::evict_first.b64 %0, 1.0;" : "=l"(pol));
  return pol;
}
__device__ __forceinline__ void bulk_load_hint(uint32_t dst, const void* src, uint32_t bytes, uint32_t bar, uint64_t pol) {
  asm volatile("cp.async.bulk.shared::cluster.global.mbarrier::complete_tx::bytes.L2::cache_hint [%0], [%1], %2, [%3], %4;"
               ::"r"(dst), "l"(src), "r"(bytes), "r"(bar), "l"(pol) : "memory");
}
__device__ __forceinline__ void flag_wait(int& bud, const int* p, int target) {
  while (true) {
    int v;
    asm volatile("ld.acquire.gpu.global.s32 %0, [%1];" : "=r"(v) : "l"(p) : "memory");
    if (v - target >= 0 || --bud <= 0) break;
    __nanosleep(64);
  }
}
__device__ __forceinline__ uint32_t lo_sw(uint32_t addr) { return (addr >> 4) | (1u << 16); }
__device__ __forceinline__ uint32_t lo_o(uint32_t addr) { return (addr >> 4) | (128u << 16); }
__device__ __forceinline__ uint32_t tid_x() { uint32_t t; asm volatile("mov.u32 %0, %tid.x;" : "=r"(t)); return t; }
__device__ __forceinline__ uint32_t opaque(uint32_t x) { uint32_t y; asm volatile("mov.u32 %0, %1;" : "=r"(y) : "r"(x)); return y; }

template <int TA, int TB, uint32_t OA, uint32_t OB>
__device__ __forceinline__ void mma160(float (&d)[80], uint32_t la, uint32_t lb) {
  asm volatile(
      "{\n.reg .pred p;\n.reg .b32 a, b;\n.reg .b64 da, db;\nsetp.eq.b32 p, 0, 0;\n"
      "add.u32 a, %80, %84;\nadd.u32 b, %81, %85;\nmov.b64 da, {a, 0x40000040};\nmov.b64 db, {b, %86};\n"
      "wgmma.mma_async.sync.aligned.m64n160k16.f32.bf16.bf16 {"
      "%0,%1,%2,%3,%4,%5,%6,%7,%8,%9,%10,%11,%12,%13,%14,%15,%16,%17,%18,%19,%20,%21,%22,%23,%24,%25,%26,%27,%28,%29,%30,%31,%32,%33,%34,%35,%36,"
      "%37,%38,%39,%40,%41,%42,%43,%44,%45,%46,%47,%48,%49,%50,%51,%52,%53,%54,%55,%56,%57,%58,%59,%60,%61,%62,%63,%64,%65,%66,%67,%68,%69,%70,%71,"
      "%72,%73,%74,%75,%76,%77,%78,%79"
      "}, da, db, p, 1, 1, %82, %83;\n}\n"
      :
      "+f"(d[0]),"+f"(d[1]),"+f"(d[2]),"+f"(d[3]),"+f"(d[4]),"+f"(d[5]),"+f"(d[6]),"+f"(d[7]),"+f"(d[8]),"+f"(d[9]),"+f"(d[10]),"+f"(d[11]),
      "+f"(d[12]),"+f"(d[13]),"+f"(d[14]),"+f"(d[15]),"+f"(d[16]),"+f"(d[17]),"+f"(d[18]),"+f"(d[19]),"+f"(d[20]),"+f"(d[21]),"+f"(d[22]),
      "+f"(d[23]),"+f"(d[24]),"+f"(d[25]),"+f"(d[26]),"+f"(d[27]),"+f"(d[28]),"+f"(d[29]),"+f"(d[30]),"+f"(d[31]),"+f"(d[32]),"+f"(d[33]),
      "+f"(d[34]),"+f"(d[35]),"+f"(d[36]),"+f"(d[37]),"+f"(d[38]),"+f"(d[39]),"+f"(d[40]),"+f"(d[41]),"+f"(d[42]),"+f"(d[43]),"+f"(d[44]),
      "+f"(d[45]),"+f"(d[46]),"+f"(d[47]),"+f"(d[48]),"+f"(d[49]),"+f"(d[50]),"+f"(d[51]),"+f"(d[52]),"+f"(d[53]),"+f"(d[54]),"+f"(d[55]),
      "+f"(d[56]),"+f"(d[57]),"+f"(d[58]),"+f"(d[59]),"+f"(d[60]),"+f"(d[61]),"+f"(d[62]),"+f"(d[63]),"+f"(d[64]),"+f"(d[65]),"+f"(d[66]),
      "+f"(d[67]),"+f"(d[68]),"+f"(d[69]),"+f"(d[70]),"+f"(d[71]),"+f"(d[72]),"+f"(d[73]),"+f"(d[74]),"+f"(d[75]),"+f"(d[76]),"+f"(d[77]),
      "+f"(d[78]),"+f"(d[79])
      : "r"(la), "r"(lb), "n"(TA), "n"(TB), "n"(OA >> 4), "n"(OB >> 4), "n"(TB ? 0xC0000010u : 0x40000040u));
}

template <int TA, int TB, uint32_t OA, uint32_t OB>
__device__ __forceinline__ void mma160z(float (&d)[80], uint32_t la, uint32_t lb) {
  asm volatile(
      "{\n.reg .pred p;\n.reg .b32 a, b;\n.reg .b64 da, db;\nsetp.ne.b32 p, 0, 0;\n"
      "add.u32 a, %80, %84;\nadd.u32 b, %81, %85;\nmov.b64 da, {a, 0x40000040};\nmov.b64 db, {b, %86};\n"
      "wgmma.mma_async.sync.aligned.m64n160k16.f32.bf16.bf16 {"
      "%0,%1,%2,%3,%4,%5,%6,%7,%8,%9,%10,%11,%12,%13,%14,%15,%16,%17,%18,%19,%20,%21,%22,%23,%24,%25,%26,%27,%28,%29,%30,%31,%32,%33,%34,%35,%36,"
      "%37,%38,%39,%40,%41,%42,%43,%44,%45,%46,%47,%48,%49,%50,%51,%52,%53,%54,%55,%56,%57,%58,%59,%60,%61,%62,%63,%64,%65,%66,%67,%68,%69,%70,%71,"
      "%72,%73,%74,%75,%76,%77,%78,%79"
      "}, da, db, p, 1, 1, %82, %83;\n}\n"
      :
      "=f"(d[0]),"=f"(d[1]),"=f"(d[2]),"=f"(d[3]),"=f"(d[4]),"=f"(d[5]),"=f"(d[6]),"=f"(d[7]),"=f"(d[8]),"=f"(d[9]),"=f"(d[10]),"=f"(d[11]),
      "=f"(d[12]),"=f"(d[13]),"=f"(d[14]),"=f"(d[15]),"=f"(d[16]),"=f"(d[17]),"=f"(d[18]),"=f"(d[19]),"=f"(d[20]),"=f"(d[21]),"=f"(d[22]),
      "=f"(d[23]),"=f"(d[24]),"=f"(d[25]),"=f"(d[26]),"=f"(d[27]),"=f"(d[28]),"=f"(d[29]),"=f"(d[30]),"=f"(d[31]),"=f"(d[32]),"=f"(d[33]),
      "=f"(d[34]),"=f"(d[35]),"=f"(d[36]),"=f"(d[37]),"=f"(d[38]),"=f"(d[39]),"=f"(d[40]),"=f"(d[41]),"=f"(d[42]),"=f"(d[43]),"=f"(d[44]),
      "=f"(d[45]),"=f"(d[46]),"=f"(d[47]),"=f"(d[48]),"=f"(d[49]),"=f"(d[50]),"=f"(d[51]),"=f"(d[52]),"=f"(d[53]),"=f"(d[54]),"=f"(d[55]),
      "=f"(d[56]),"=f"(d[57]),"=f"(d[58]),"=f"(d[59]),"=f"(d[60]),"=f"(d[61]),"=f"(d[62]),"=f"(d[63]),"=f"(d[64]),"=f"(d[65]),"=f"(d[66]),
      "=f"(d[67]),"=f"(d[68]),"=f"(d[69]),"=f"(d[70]),"=f"(d[71]),"=f"(d[72]),"=f"(d[73]),"=f"(d[74]),"=f"(d[75]),"=f"(d[76]),"=f"(d[77]),
      "=f"(d[78]),"=f"(d[79])
      : "r"(la), "r"(lb), "n"(TA), "n"(TB), "n"(OA >> 4), "n"(OB >> 4), "n"(TB ? 0xC0000010u : 0x40000040u));
}

template <int TA, int TB, uint32_t OA, uint32_t OB>
__device__ __forceinline__ void mma80(float (&d)[40], uint32_t la, uint32_t lb) {
  asm volatile(
      "{\n.reg .pred p;\n.reg .b32 a, b;\n.reg .b64 da, db;\nsetp.eq.b32 p, 0, 0;\n"
      "add.u32 a, %40, %44;\nadd.u32 b, %41, %45;\nmov.b64 da, {a, 0x40000040};\nmov.b64 db, {b, %46};\n"
      "wgmma.mma_async.sync.aligned.m64n80k16.f32.bf16.bf16 {"
      "%0,%1,%2,%3,%4,%5,%6,%7,%8,%9,%10,%11,%12,%13,%14,%15,%16,%17,%18,%19,%20,%21,%22,%23,%24,%25,%26,%27,%28,%29,%30,%31,%32,%33,%34,%35,%36,"
      "%37,%38,%39"
      "}, da, db, p, 1, 1, %42, %43;\n}\n"
      :
      "+f"(d[0]),"+f"(d[1]),"+f"(d[2]),"+f"(d[3]),"+f"(d[4]),"+f"(d[5]),"+f"(d[6]),"+f"(d[7]),"+f"(d[8]),"+f"(d[9]),"+f"(d[10]),"+f"(d[11]),
      "+f"(d[12]),"+f"(d[13]),"+f"(d[14]),"+f"(d[15]),"+f"(d[16]),"+f"(d[17]),"+f"(d[18]),"+f"(d[19]),"+f"(d[20]),"+f"(d[21]),"+f"(d[22]),
      "+f"(d[23]),"+f"(d[24]),"+f"(d[25]),"+f"(d[26]),"+f"(d[27]),"+f"(d[28]),"+f"(d[29]),"+f"(d[30]),"+f"(d[31]),"+f"(d[32]),"+f"(d[33]),
      "+f"(d[34]),"+f"(d[35]),"+f"(d[36]),"+f"(d[37]),"+f"(d[38]),"+f"(d[39])
      : "r"(la), "r"(lb), "n"(TA), "n"(TB), "n"(OA >> 4), "n"(OB >> 4), "n"(TB ? 0xC0000010u : 0x40000040u));
}

template <int TA, int TB, uint32_t OA, uint32_t OB>
__device__ __forceinline__ void mma80z(float (&d)[40], uint32_t la, uint32_t lb) {
  asm volatile(
      "{\n.reg .pred p;\n.reg .b32 a, b;\n.reg .b64 da, db;\nsetp.ne.b32 p, 0, 0;\n"
      "add.u32 a, %40, %44;\nadd.u32 b, %41, %45;\nmov.b64 da, {a, 0x40000040};\nmov.b64 db, {b, %46};\n"
      "wgmma.mma_async.sync.aligned.m64n80k16.f32.bf16.bf16 {"
      "%0,%1,%2,%3,%4,%5,%6,%7,%8,%9,%10,%11,%12,%13,%14,%15,%16,%17,%18,%19,%20,%21,%22,%23,%24,%25,%26,%27,%28,%29,%30,%31,%32,%33,%34,%35,%36,"
      "%37,%38,%39"
      "}, da, db, p, 1, 1, %42, %43;\n}\n"
      :
      "=f"(d[0]),"=f"(d[1]),"=f"(d[2]),"=f"(d[3]),"=f"(d[4]),"=f"(d[5]),"=f"(d[6]),"=f"(d[7]),"=f"(d[8]),"=f"(d[9]),"=f"(d[10]),"=f"(d[11]),
      "=f"(d[12]),"=f"(d[13]),"=f"(d[14]),"=f"(d[15]),"=f"(d[16]),"=f"(d[17]),"=f"(d[18]),"=f"(d[19]),"=f"(d[20]),"=f"(d[21]),"=f"(d[22]),
      "=f"(d[23]),"=f"(d[24]),"=f"(d[25]),"=f"(d[26]),"=f"(d[27]),"=f"(d[28]),"=f"(d[29]),"=f"(d[30]),"=f"(d[31]),"=f"(d[32]),"=f"(d[33]),
      "=f"(d[34]),"=f"(d[35]),"=f"(d[36]),"=f"(d[37]),"=f"(d[38]),"=f"(d[39])
      : "r"(la), "r"(lb), "n"(TA), "n"(TB), "n"(OA >> 4), "n"(OB >> 4), "n"(TB ? 0xC0000010u : 0x40000040u));
}

template <int TA, int TB, uint32_t OA, uint32_t OB>
__device__ __forceinline__ void mma160r(float (&d)[80], uint32_t la, uint32_t lb, int sc) {
  asm volatile(
      "{\n.reg .pred p;\n.reg .b32 a, b;\n.reg .b64 da, db;\nsetp.ne.b32 p, %87, 0;\n"
      "add.u32 a, %80, %84;\nadd.u32 b, %81, %85;\nmov.b64 da, {a, 0x40000040};\nmov.b64 db, {b, %86};\n"
      "wgmma.mma_async.sync.aligned.m64n160k16.f32.bf16.bf16 {"
      "%0,%1,%2,%3,%4,%5,%6,%7,%8,%9,%10,%11,%12,%13,%14,%15,%16,%17,%18,%19,%20,%21,%22,%23,%24,%25,%26,%27,%28,%29,%30,%31,%32,%33,%34,%35,%36,"
      "%37,%38,%39,%40,%41,%42,%43,%44,%45,%46,%47,%48,%49,%50,%51,%52,%53,%54,%55,%56,%57,%58,%59,%60,%61,%62,%63,%64,%65,%66,%67,%68,%69,%70,%71,"
      "%72,%73,%74,%75,%76,%77,%78,%79"
      "}, da, db, p, 1, 1, %82, %83;\n}\n"
      :
      "+f"(d[0]),"+f"(d[1]),"+f"(d[2]),"+f"(d[3]),"+f"(d[4]),"+f"(d[5]),"+f"(d[6]),"+f"(d[7]),"+f"(d[8]),"+f"(d[9]),"+f"(d[10]),"+f"(d[11]),
      "+f"(d[12]),"+f"(d[13]),"+f"(d[14]),"+f"(d[15]),"+f"(d[16]),"+f"(d[17]),"+f"(d[18]),"+f"(d[19]),"+f"(d[20]),"+f"(d[21]),"+f"(d[22]),
      "+f"(d[23]),"+f"(d[24]),"+f"(d[25]),"+f"(d[26]),"+f"(d[27]),"+f"(d[28]),"+f"(d[29]),"+f"(d[30]),"+f"(d[31]),"+f"(d[32]),"+f"(d[33]),
      "+f"(d[34]),"+f"(d[35]),"+f"(d[36]),"+f"(d[37]),"+f"(d[38]),"+f"(d[39]),"+f"(d[40]),"+f"(d[41]),"+f"(d[42]),"+f"(d[43]),"+f"(d[44]),
      "+f"(d[45]),"+f"(d[46]),"+f"(d[47]),"+f"(d[48]),"+f"(d[49]),"+f"(d[50]),"+f"(d[51]),"+f"(d[52]),"+f"(d[53]),"+f"(d[54]),"+f"(d[55]),
      "+f"(d[56]),"+f"(d[57]),"+f"(d[58]),"+f"(d[59]),"+f"(d[60]),"+f"(d[61]),"+f"(d[62]),"+f"(d[63]),"+f"(d[64]),"+f"(d[65]),"+f"(d[66]),
      "+f"(d[67]),"+f"(d[68]),"+f"(d[69]),"+f"(d[70]),"+f"(d[71]),"+f"(d[72]),"+f"(d[73]),"+f"(d[74]),"+f"(d[75]),"+f"(d[76]),"+f"(d[77]),
      "+f"(d[78]),"+f"(d[79])
      : "r"(la), "r"(lb), "n"(TA), "n"(TB), "n"(OA >> 4), "n"(OB >> 4), "n"(TB ? 0xC0000010u : 0x40000040u), "r"(sc));
}

template <int TA, int TB, uint32_t OA, uint32_t OB>
__device__ __forceinline__ void mma80r(float (&d)[40], uint32_t la, uint32_t lb, int sc) {
  asm volatile(
      "{\n.reg .pred p;\n.reg .b32 a, b;\n.reg .b64 da, db;\nsetp.ne.b32 p, %47, 0;\n"
      "add.u32 a, %40, %44;\nadd.u32 b, %41, %45;\nmov.b64 da, {a, 0x40000040};\nmov.b64 db, {b, %46};\n"
      "wgmma.mma_async.sync.aligned.m64n80k16.f32.bf16.bf16 {"
      "%0,%1,%2,%3,%4,%5,%6,%7,%8,%9,%10,%11,%12,%13,%14,%15,%16,%17,%18,%19,%20,%21,%22,%23,%24,%25,%26,%27,%28,%29,%30,%31,%32,%33,%34,%35,%36,"
      "%37,%38,%39"
      "}, da, db, p, 1, 1, %42, %43;\n}\n"
      :
      "+f"(d[0]),"+f"(d[1]),"+f"(d[2]),"+f"(d[3]),"+f"(d[4]),"+f"(d[5]),"+f"(d[6]),"+f"(d[7]),"+f"(d[8]),"+f"(d[9]),"+f"(d[10]),"+f"(d[11]),
      "+f"(d[12]),"+f"(d[13]),"+f"(d[14]),"+f"(d[15]),"+f"(d[16]),"+f"(d[17]),"+f"(d[18]),"+f"(d[19]),"+f"(d[20]),"+f"(d[21]),"+f"(d[22]),
      "+f"(d[23]),"+f"(d[24]),"+f"(d[25]),"+f"(d[26]),"+f"(d[27]),"+f"(d[28]),"+f"(d[29]),"+f"(d[30]),"+f"(d[31]),"+f"(d[32]),"+f"(d[33]),
      "+f"(d[34]),"+f"(d[35]),"+f"(d[36]),"+f"(d[37]),"+f"(d[38]),"+f"(d[39])
      : "r"(la), "r"(lb), "n"(TA), "n"(TB), "n"(OA >> 4), "n"(OB >> 4), "n"(TB ? 0xC0000010u : 0x40000040u), "r"(sc));
}

struct Ring { uint32_t s0, ph0; };
__device__ __forceinline__ void ring_pos(const Ring& r, int i, uint32_t& slot, uint32_t& ph) {
  uint32_t s = opaque(r.s0) + (i % NSLOT);
  uint32_t wrap = s >= NSLOT;
  slot = s - (wrap ? NSLOT : 0);
  ph = r.ph0 ^ ((i / NSLOT) & 1) ^ wrap;
}
__device__ __forceinline__ void ring_advance(Ring& r, int n) {
  uint32_t s, p;
  ring_pos(r, n, s, p);
  r.s0 = s; r.ph0 = p;
}
__host__ __device__ constexpr int idxK(int j) { return j == 0 ? 10 : 9 + 2 * j; }
__host__ __device__ constexpr int idxV(int j) { return j == 7 ? 25 : 12 + 2 * j; }
__host__ __device__ constexpr int xs(int c) { return c % NSLOT; }

__device__ __forceinline__ int start_delay(int cta) {
  return max(0, ((cta - N_OCTA) | (STAG_G - 1)) - STAG_A0) * STAG_SLOPE;
}
__device__ __forceinline__ char* o_slot(int item) {
  return (char*)g_o + (size_t)(item < OFRESH ? item % ORING : item - OFRESH + ORING) * O_ITEM_BYTES;
}
__device__ __forceinline__ int next_item(uint32_t a = NEXT_ITEM) {
  int v;
  asm volatile("ld.shared.s32 %0, [%1];" : "=r"(v) : "r"(a) : "memory");
  return __shfl_sync(0xffffffffu, v, 0);
}

template <int W, bool ACC>
__device__ __forceinline__ void mma_main(float (&d)[80], uint32_t aaddr, uint32_t baddr) {
  const uint32_t la = lo_sw(aaddr), lb = lo_sw(baddr);
  if (ACC) mma160<1, 0, W * 16384, 0>(d, la, lb); else mma160z<1, 0, W * 16384, 0>(d, la, lb);
  mma160<1, 0, W * 16384 + 1 * 2048, 1 * 32>(d, la, lb);
  mma160<1, 0, W * 16384 + 2 * 2048, 2 * 32>(d, la, lb);
  mma160<1, 0, W * 16384 + 3 * 2048, 3 * 32>(d, la, lb);
}
template <int W, bool ACC>
__device__ __forceinline__ void mma_mid(float (&d)[40], uint32_t aaddr, uint32_t baddr) {
  const uint32_t la = lo_sw(aaddr), lb = lo_sw(baddr);
  if (ACC) mma80<1, 0, 8192, W * 10240>(d, la, lb); else mma80z<1, 0, 8192, W * 10240>(d, la, lb);
  mma80<1, 0, 8192 + 1 * 2048, W * 10240 + 1 * 32>(d, la, lb);
  mma80<1, 0, 8192 + 2 * 2048, W * 10240 + 2 * 32>(d, la, lb);
  mma80<1, 0, 8192 + 3 * 2048, W * 10240 + 3 * 32>(d, la, lb);
}
template <int W, bool ACC>
__device__ __forceinline__ void mma_both(float (&dm)[80], float (&dh)[40], uint32_t aaddr, uint32_t baddr) {
  mma_mid<W, ACC>(dh, aaddr, baddr);
  mma_main<W, ACC>(dm, aaddr, baddr);
}
template <int KB, bool ACC>
__device__ __forceinline__ void s_mma(float (&sacc)[80], uint32_t kaddr) {
  const uint32_t la = lo_sw(kaddr), lb = lo_sw(SB + OFF_B);
  if (ACC) mma160<0, 0, KB * 8192, KB * B_SLOT>(sacc, la, lb); else mma160z<0, 0, KB * 8192, KB * B_SLOT>(sacc, la, lb);
  mma160<0, 0, KB * 8192 + 32, KB * B_SLOT + 32>(sacc, la, lb);
  mma160<0, 0, KB * 8192 + 64, KB * B_SLOT + 64>(sacc, la, lb);
  mma160<0, 0, KB * 8192 + 96, KB * B_SLOT + 96>(sacc, la, lb);
}
template <int N>
__device__ __forceinline__ void store_scaled(uint32_t addr, const float (&d)[N], float sc) {
#pragma unroll
  for (int J = 0; J < N / 8; J++)
    stsm_t(addr + J * 2048, pack2(d[8 * J] * sc, d[8 * J + 1] * sc), pack2(d[8 * J + 2] * sc, d[8 * J + 3] * sc),
           pack2(d[8 * J + 4] * sc, d[8 * J + 5] * sc), pack2(d[8 * J + 6] * sc, d[8 * J + 7] * sc));
}
__device__ __forceinline__ float4 lds_f4(uint32_t a) {
  float4 v;
  asm volatile("ld.shared.v4.f32 {%0,%1,%2,%3}, [%4];" : "=f"(v.x), "=f"(v.y), "=f"(v.z), "=f"(v.w) : "r"(a) : "memory");
  return v;
}
__device__ __forceinline__ void norm_pack(uint32_t* p, const float* d, const float4& i) {
  p[0] = pack2(d[0] * i.x, d[1] * i.y); p[1] = pack2(d[4] * i.z, d[5] * i.w);
  p[2] = pack2(d[2] * i.x, d[3] * i.y); p[3] = pack2(d[6] * i.z, d[7] * i.w);
  asm volatile("" : "+r"(p[0]), "+r"(p[1]), "+r"(p[2]), "+r"(p[3])::"memory");
}
template <int W>
__device__ __forceinline__ void pack_first(uint32_t (&pk)[60], const float (&om)[80], const float (&oh)[40], uint32_t laddr) {
  float4 n0 = lds_f4(laddr + W * 80), n1 = lds_f4(laddr + W * 80 + 16);
#pragma unroll
  for (int J = 0; J < 5; J++) {
    const float4 i = n0;
    n0 = n1;
    if (J + 2 < 5) n1 = lds_f4(laddr + W * 80 + (J + 2) * 16);
    norm_pack(&pk[20 + 4 * J], &om[8 * (5 * W + J)], i);
    norm_pack(&pk[4 * J], &oh[8 * J], i);
  }
}
template <int W, int J0, int J1>
__device__ __forceinline__ void pack_second(uint32_t (&pk)[60], const float (&om)[80], uint32_t laddr) {
  float4 n[J1 - J0];
#pragma unroll
  for (int J = J0; J < J1; J++) n[J - J0] = lds_f4(laddr + (1 - W) * 80 + J * 16);
#pragma unroll
  for (int J = J0; J < J1; J++) norm_pack(&pk[40 + 4 * J], &om[8 * (5 * (1 - W) + J)], n[J - J0]);
}
__device__ __forceinline__ char* o_ptr(int item) {
  const uint32_t t = tid_x();
  return o_slot(item) + ((t & 96) * 16 + (t & 28) * 8 + ((((t >> 1) ^ (t >> 4)) & 1) << 4) + (t & 1) * 8);
}
template <int W, int G0, int G1>
__device__ __forceinline__ void store_groups(char* op, const uint32_t (&pk)[60], uint32_t on) {
#pragma unroll
  for (int G = G0; G < G1; G++) {
    const int off = (G < 5 ? 1 : 2 * W) * B_SLOT + (5 * (G < 10 ? W : 1 - W) + G % 5) * 2048;
    asm volatile("{\n.reg .pred p;\nsetp.ne.u32 p, %5, 0;\n@p st.global.v2.b32 [%0], {%1, %2};\n@p st.global.v2.b32 [%0+256], {%3, %4};\n}\n"
                 ::"l"(op + off), "r"(pk[4 * G]), "r"(pk[4 * G + 1]), "r"(pk[4 * G + 2]), "r"(pk[4 * G + 3]), "r"(on) : "memory");
  }
}
__device__ __forceinline__ void publish_generic(uint32_t bar, int lane) {
  __syncwarp();
  mbar_arrive_if0(bar, lane);
}
__device__ __forceinline__ void publish(uint32_t bar, int lane) {
  proxy_fence();
  __syncwarp();
  mbar_arrive_if0(bar, lane);
}

#define A_ADDR(s) (SB + OFF_A + (s) * A_SLOT)
#define B_ADDR(s) (SB + OFF_B + (s) * B_SLOT)
#define WAIT_CHUNK(c, ro, sA)                \
  uint32_t sA;                               \
  {                                          \
    uint32_t pA_;                            \
    ring_pos(ring, (ro) + (c), sA, pA_);     \
    mbar_wait(bud, BAR_FULLA + sA * 8, pA_); \
  }
#define RELEASE_CHUNK(c, sA)                                  \
  mbar_arrive_if0(BAR_EMPTYA + (sA) * 8, tid);                \
  if ((c) < NSLOT) mbar_arrive_if0(BAR_EMPTYB + xs(c) * 8, tid);

template <int W>
__device__ __forceinline__ int attn_consumer(int item) {
  int bud = WAIT_BUDGET;
  const int tid = threadIdx.x & 127, lane = tid & 31, warp = tid >> 5;
  const uint32_t st_off = ((lane & 7) + 8 * (lane >> 4)) * 128 + (((2 * warp + ((lane >> 3) & 1)) ^ (lane & 7)) << 4);
  const uint32_t laddr = SB + OFF_L + (lane & 3) * 160;
  float om[80], oh[40], sacc[80];
  uint32_t pk[60];
#pragma unroll
  for (int i = 0; i < 40; i++) pk[i] = 0;
  zero_regs(om);
  Ring ring{0u, 0u};
  uint32_t par = 0;
  int prev = 0;
  const float qscale = 0.07216878364870322f * 1.4426950408889634f;
  constexpr uint32_t pown = B_ADDR(3 + W), poth = B_ADDR(4 - W);
  TL(0); TLG(62);
  {
    WAIT_CHUNK(0, 0, s0)
    wg_fence();
    mma_both<W, false>(sacc, oh, A_ADDR(s0), B_ADDR(xs(0)));
    wg_commit();
    WAIT_CHUNK(1, 0, s1)
    wg_fence();
    mma_both<W, true>(sacc, oh, A_ADDR(s1), B_ADDR(xs(1)));
    wg_commit();
    wg_wait<1>();
    RELEASE_CHUNK(0, s0)
  }
#pragma unroll 1
  for (int it = 0;; it++) {
    char* op = o_ptr(prev);
#pragma unroll
    for (int c = 2; c < 8 - W; c++) {
      WAIT_CHUNK(c, 0, sA)
      TL(40 + c);
      wg_fence();
      mma_both<W, true>(sacc, oh, A_ADDR(sA), B_ADDR(xs(c)));
      wg_commit();
      wg_wait<1>();
      uint32_t sP, pP;
      ring_pos(ring, c - 1, sP, pP);
      RELEASE_CHUNK(c - 1, sP)
      constexpr int NG = 3;
      if (c == 2) { pack_second<W, 0, 1>(pk, om, laddr); store_groups<W, 0 * NG, 1 * NG>(op, pk, it); }
      if (c == 3) { pack_second<W, 1, 2>(pk, om, laddr); store_groups<W, 1 * NG, 2 * NG>(op, pk, it); }
      if (c == 4) { pack_second<W, 2, 3>(pk, om, laddr); store_groups<W, 2 * NG, 3 * NG>(op, pk, it); }
      if (c == 5) { pack_second<W, 3, 4>(pk, om, laddr); store_groups<W, 3 * NG, 4 * NG>(op, pk, it); }
      if (c == 6) {
        pack_second<W, 4, 5>(pk, om, laddr);
        if (W == 1) {
          wg_wait<0>();
          RELEASE_CHUNK(6, sA)
          mbar_arrive_if0(BAR_XDONE, tid);
        }
        store_groups<W, 4 * NG, 15>(op, pk, it);
        __syncwarp();
        mbar_arrive_if0(BAR_OFULL, lane | (it == 0));
      }
    }
    uint32_t sK0, pK0, s7, p7;
    ring_pos(ring, idxK(W), sK0, pK0);
    ring_pos(ring, 7, s7, p7);
    if (W == 1) mbar_wait(bud, BAR_FULLA + s7 * 8, p7);
    WAIT_CHUNK(8, 0, s8)
    if (W == 0) {
      wg_fence();
      mma_both<W, true>(sacc, oh, A_ADDR(s8), B_ADDR(xs(8)));
      wg_commit();
      wg_wait<1>();
      RELEASE_CHUNK(7, s7)
    }
    WAIT_CHUNK(9, 0, s9)
    TL(48);
    if (W == 0) {
      wg_fence();
      mma_mid<W, true>(oh, A_ADDR(s9), B_ADDR(xs(9)));
      wg_commit();
      mma_main<W, true>(sacc, A_ADDR(s9), B_ADDR(xs(9)));
      wg_commit();
      bar_arrive(5, 256);
      TL(49);
      wg_wait<1>();
      reg_fence(oh);
      mbar_wait(bud, BAR_XDONE, par);
      store_scaled(B_ADDR(1) + st_off, oh, qscale);
    } else {
      bar_sync(5, 256);
      wg_fence();
      mma_mid<W, true>(oh, A_ADDR(s7), B_ADDR(xs(7)));
      mma_mid<W, true>(oh, A_ADDR(s8), B_ADDR(xs(8)));
      mma_mid<W, true>(oh, A_ADDR(s9), B_ADDR(xs(9)));
      wg_commit();
      mma_main<W, true>(sacc, A_ADDR(s7), B_ADDR(xs(7)));
      wg_commit();
      mma_main<W, true>(sacc, A_ADDR(s8), B_ADDR(xs(8)));
      wg_commit();
      wg_wait<2>();
      reg_fence(oh);
      store_scaled(B_ADDR(1) + 10240 + st_off, oh, qscale);
      wg_fence();
      mma_main<W, true>(sacc, A_ADDR(s9), B_ADDR(xs(9)));
      wg_commit();
      bar_arrive(8, 256);
      TL(49);
      wg_wait<2>();
      RELEASE_CHUNK(7, s7)
      publish(BAR_QH, lane);
    }
    wg_wait<0>();
    reg_fence(sacc);
    TL(1);
    RELEASE_CHUNK(8, s8)
    RELEASE_CHUNK(9, s9)
    store_scaled(B_ADDR(2 * W) + st_off, sacc, qscale);
    if (W == 1) publish(BAR_QM, lane); else proxy_fence();
    TL(2);
    uint32_t sK = sK0, sV1 = 0;
    if (W == 0) {
      zero_regs(om); zero_regs(oh);
      reg_fence(om); reg_fence(oh);
      mbar_wait(bud, BAR_FULLA + sK0 * 8, pK0);
      bar_sync(8, 256);
      wg_fence();
      s_mma<0, false>(sacc, A_ADDR(sK));
      mbar_wait(bud, BAR_QH, par);
      TL(3);
      wg_fence();
      s_mma<1, true>(sacc, A_ADDR(sK));
      mbar_wait(bud, BAR_QM, par);
      TL(5);
      wg_fence();
      s_mma<2, true>(sacc, A_ADDR(sK));
      wg_commit();
      wg_commit();
      bar_arrive(2, 256);
    } else {
      uint32_t pV1;
      ring_pos(ring, idxV(0), sV1, pV1);
      mbar_wait(bud, BAR_FULLA + sK * 8, pK0);
      bar_sync(2, 256);
      wg_fence();
      s_mma<0, false>(sacc, A_ADDR(sK));
      s_mma<1, true>(sacc, A_ADDR(sK));
      s_mma<2, true>(sacc, A_ADDR(sK));
      wg_commit();
      TL(6);
      mbar_wait(bud, BAR_FULLA + sV1 * 8, pV1);
      mbar_wait(bud, BAR_PFULL, 0);
      TL(7);
      wg_fence();
      mma_both<W, false>(om, oh, A_ADDR(sV1), poth);
      wg_commit();
      bar_arrive(1, 256);
    }
    Ring rv;
    ring_pos(ring, idxV(W), rv.s0, rv.ph0);
#pragma unroll 1
    for (int jj = 0;; jj++) {
      wg_wait<1>();
      reg_fence(sacc);
      TL(8 + jj * 7);
      mbar_arrive2_if0(BAR_EMPTYA + sK * 8, tid);
      mbar_arrive_if0(BAR_EMPTYB + tid * 8, (tid >= 3) | (jj != 3));
#pragma unroll
      for (int J = 0; J < 10; J++) {
        stsm_t(pown + st_off + J * 2048, pack2(ex2(sacc[8 * J]), ex2(sacc[8 * J + 1])), pack2(ex2(sacc[8 * J + 2]), ex2(sacc[8 * J + 3])),
               pack2(ex2(sacc[8 * J + 4]), ex2(sacc[8 * J + 5])), pack2(ex2(sacc[8 * J + 6]), ex2(sacc[8 * J + 7])));
        if (W == 1 && (J == 2 || J == 5)) publish_generic(BAR_PMID + (J / 3) * 8, lane | (jj != 3));
        if (J == 4) {
          wg_wait<0>();
          mbar_arrive_if0(BAR_EMPTYA + sV1 * 8, tid | (W == 0 && jj == 0));
        }
      }
      publish(BAR_PFULL + W * 8, lane);
      TL(10 + jj * 7);
      if (jj == 3) break;
      uint32_t pK, pV1;
      ring_pos(rv, 1, sK, pK);
      ring_pos(rv, 2, sV1, pV1);
      mbar_wait(bud, BAR_FULLA + rv.s0 * 8, rv.ph0);
      bar_sync(1 + W, 256);
      wg_fence();
      mma_both<W, true>(om, oh, A_ADDR(rv.s0), pown);
      wg_commit();
      mbar_wait(bud, BAR_FULLA + sK * 8, pK);
      TL(11 + jj * 7);
      wg_fence();
      s_mma<0, false>(sacc, A_ADDR(sK));
      s_mma<1, true>(sacc, A_ADDR(sK));
      wg_commit();
      wg_wait<1>();
      mbar_arrive_if0(BAR_EMPTYA + rv.s0 * 8, tid);
      wg_fence();
      s_mma<2, true>(sacc, A_ADDR(sK));
      wg_commit();
      TL(13 + jj * 7);
      mbar_wait(bud, BAR_FULLA + sV1 * 8, pV1);
      mbar_wait(bud, BAR_PFREE + W * 8, jj & 1);
      mbar_wait(bud, BAR_PFULL + (1 - W) * 8, (jj + W) & 1);
      TL(14 + jj * 7);
      wg_fence();
      mma_both<W, true>(om, oh, A_ADDR(sV1), poth);
      wg_commit();
      bar_arrive(2 - W, 256);
      ring_advance(rv, 4);
    }
    uint32_t sV7, pV7;
    ring_pos(ring, idxV(7), sV7, pV7);
    prev = item;
    if (W == 1 && !DEBUG_TIMEOUT) item = next_item();
    if (W == 0) {
      uint32_t sV6, pV6;
      ring_pos(ring, idxV(6), sV6, pV6);
      mbar_wait(bud, BAR_FULLA + sV6 * 8, pV6);
      bar_sync(1, 256);
      wg_fence();
      mma_both<0, true>(om, oh, A_ADDR(sV6), pown);
      wg_commit();
      mbar_wait(bud, BAR_FULLA + sV7 * 8, pV7);
      wg_wait<0>();
      mbar_arrive_if0(BAR_EMPTYA + sV6 * 8, tid);
      mbar_wait(bud, BAR_PFULL + 8, 1);
      wg_fence();
      mma_both<0, true>(om, oh, A_ADDR(sV7), poth);
      wg_commit();
      bar_arrive(6, 256);
    } else {
      mbar_wait(bud, BAR_FULLA + sV7 * 8, pV7);
      bar_sync(6, 256);
    }
    TL(32);
    if (DEBUG_TIMEOUT) item = next_item(NEXT_ITEM + 4);
    else if (W == 0) item = next_item();
    if (item >= NITEMS) {
      if (W == 1) {
        wg_fence();
        mma_both<1, true>(om, oh, A_ADDR(sV7), pown);
        wg_commit();
      }
      wg_wait<0>();
      reg_fence(om); reg_fence(oh);
      TL(33);
      mbar_wait(bud, BAR_LFULL, par);
      mbar_arrive_if0(BAR_FREE, tid);
      TL(34);
      pack_first<W>(pk, om, oh, laddr);
      op = o_ptr(prev);
      store_groups<W, 0, 10>(op, pk, 1);
      pack_second<W, 0, 5>(pk, om, laddr);
      store_groups<W, 10, 15>(op, pk, 1);
      publish_generic(BAR_OFULL, lane);
      TL(35); TLG(63);
      TL_FLUSH();
      return item;
    }
    {
      if (W == 1) {
        wg_fence();
        mma_both<1, true>(om, oh, A_ADDR(sV7), pown);
        wg_commit();
      }
      WAIT_CHUNK(0, 26, s0)
      WAIT_CHUNK(1, 26, s1)
      if (W == 0) {
        wg_wait<0>();
        reg_fence(om); reg_fence(oh);
        TL(33);
        wg_fence();
        mma_main<W, false>(sacc, A_ADDR(s0), B_ADDR(xs(0)));
        wg_commit();
      } else {
        wg_fence();
        mma_main<W, false>(sacc, A_ADDR(s0), B_ADDR(xs(0)));
        mma_main<W, true>(sacc, A_ADDR(s1), B_ADDR(xs(1)));
        wg_commit();
        wg_wait<1>();
        reg_fence(om); reg_fence(oh);
        TL(33);
      }
      mbar_arrive_if0(BAR_EMPTYA + sV7 * 8, tid);
      mbar_wait(bud, BAR_LFULL, par);
      mbar_arrive_if0(BAR_EMPTYB + 24 + tid * 8, tid >= 2);
      TL(34);
      pack_first<W>(pk, om, oh, laddr);
      TL(36);
      wg_fence();
      mma_mid<W, false>(oh, A_ADDR(s0), B_ADDR(xs(0)));
      wg_commit();
      mma_mid<W, true>(oh, A_ADDR(s1), B_ADDR(xs(1)));
      if (W == 0) mma_main<W, true>(sacc, A_ADDR(s1), B_ADDR(xs(1)));
      wg_commit();
      TL(37);
      wg_wait<1>();
      RELEASE_CHUNK(0, s0)
      TL(35); TLG(63);
    }
    TL_FLUSH();
    TL(0); TLG(62);
    ring_advance(ring, 26);
    par ^= 1;
  }
}

__device__ __forceinline__ uint4 lds128(uint32_t a) {
  uint4 v;
  asm volatile("ld.shared.v4.b32 {%0,%1,%2,%3}, [%4];" : "=r"(v.x), "=r"(v.y), "=r"(v.z), "=r"(v.w) : "r"(a) : "memory");
  return v;
}
__device__ __forceinline__ void acc2(float& s, float& t, uint32_t w) {
  s += __uint_as_float(w << 16);
  t += __uint_as_float(w & 0xffff0000u);
}
__device__ __forceinline__ uint32_t badd2(uint32_t a, uint32_t b) { uint32_t r; asm("add.rn.bf16x2 %0, %1, %2;" : "=r"(r) : "r"(a), "r"(b)); return r; }
__device__ __forceinline__ void sum_unit(float& acc, uint32_t pb) {
  const uint4 v0 = lds128(pb), v1 = lds128(pb ^ 32), v2 = lds128(pb ^ 64), v3 = lds128(pb ^ 96);
  const uint32_t w0 = badd2(v0.x, v0.y), w1 = badd2(v0.z, v0.w);
  float s0 = acc + __uint_as_float(w0 << 16), t0 = __uint_as_float(w0 & 0xffff0000u);
  float s1 = __uint_as_float(w1 << 16), t1 = __uint_as_float(w1 & 0xffff0000u);
  acc2(s0, t0, badd2(v1.x, v1.y)); acc2(s1, t1, badd2(v1.z, v1.w));
  acc2(s0, t0, badd2(v2.x, v2.y)); acc2(s1, t1, badd2(v2.z, v2.w));
  acc2(s0, t0, badd2(v3.x, v3.y)); acc2(s1, t1, badd2(v3.z, v3.w));
  acc = (s0 + t0) + (s1 + t1);
}
__device__ __forceinline__ float bf_lo(uint32_t w) { return __uint_as_float(w << 16); }
__device__ __forceinline__ float bf_hi(uint32_t w) { return __uint_as_float(w & 0xffff0000u); }
__device__ __forceinline__ float bf_rn(float x) { return __bfloat162float(__float2bfloat16(x)); }
__device__ __forceinline__ void slow_item(const Params& p, int item, int hw) {
  const int blk = item >> 9, h = (item >> 4) & 31, b = item & 15;
#pragma unroll 1
  for (int n = hw; n < SQ; n += 3) {
    float q[6] = {0.f, 0.f, 0.f, 0.f, 0.f, 0.f};
    {
      const uint32_t* xr = (const uint32_t*)(p.xp[blk] + (size_t)(b * SQ + n) * DM);
      const uint32_t* wq = (const uint32_t*)(p.wqp[blk] + h * DH) + (tid_x() & 31);
#pragma unroll 2
      for (int k = 0; k < DM / 2; k++) {
        const uint32_t xv = xr[k];
#pragma unroll
        for (int i = 0; i < 3; i++) {
          const uint32_t w0 = wq[i * 32], w1 = wq[NH * DH / 2 + i * 32];
          q[2 * i] = fmaf(bf_lo(xv), bf_lo(w0), fmaf(bf_hi(xv), bf_lo(w1), q[2 * i]));
          q[2 * i + 1] = fmaf(bf_lo(xv), bf_hi(w0), fmaf(bf_hi(xv), bf_hi(w1), q[2 * i + 1]));
        }
        wq += NH * DH;
      }
    }
    const uint32_t q0 = pack2(q[0], q[1]), q1 = pack2(q[2], q[3]), q2 = pack2(q[4], q[5]);
    float o[6] = {0.f, 0.f, 0.f, 0.f, 0.f, 0.f}, m = -INFINITY, l = 0.f;
    const uint32_t* kg = (const uint32_t*)(p.kp[blk] + (size_t)(b * NH + h) * SK * DH) + (tid_x() & 31);
    const uint32_t* vg = (const uint32_t*)(p.vp[blk] + (size_t)(b * NH + h) * SK * DH) + (tid_x() & 31);
#pragma unroll 1
    for (int k = 0; k < SK; k++) {
      const uint32_t k0 = kg[0], k1 = kg[32], k2 = kg[64], v0 = vg[0], v1 = vg[32], v2 = vg[64];
      kg += DH / 2; vg += DH / 2;
      float sc = fmaf(bf_lo(q0), bf_lo(k0), bf_hi(q0) * bf_hi(k0));
      sc = fmaf(bf_lo(q1), bf_lo(k1), fmaf(bf_hi(q1), bf_hi(k1), sc));
      sc = fmaf(bf_lo(q2), bf_lo(k2), fmaf(bf_hi(q2), bf_hi(k2), sc));
#pragma unroll
      for (int d = 16; d; d >>= 1) sc += __shfl_xor_sync(0xffffffffu, sc, d);
      sc = bf_rn(bf_rn(sc) * 0.07216878364870322f);
      const float mn = fmaxf(m, sc), a = ex2((m - mn) * 1.4426950408889634f), pr = ex2((sc - mn) * 1.4426950408889634f);
      m = mn;
      l = fmaf(l, a, pr);
      o[0] = fmaf(o[0], a, pr * bf_lo(v0)); o[1] = fmaf(o[1], a, pr * bf_hi(v0));
      o[2] = fmaf(o[2], a, pr * bf_lo(v1)); o[3] = fmaf(o[3], a, pr * bf_hi(v1));
      o[4] = fmaf(o[4], a, pr * bf_lo(v2)); o[5] = fmaf(o[5], a, pr * bf_hi(v2));
    }
    float inv;
    asm("rcp.approx.ftz.f32 %0, %1;" : "=f"(inv) : "f"(l));
    const int lane = tid_x() & 31;
    const int r = n & 15, c = 4 * ((r & 7) >> 1) + 2 * (r >> 3) + (r & 1);
    char* on = o_slot(item) + (lane >> 2) * 256 + (lane & 3) * 64 + (n >> 4) * 2048 +
               (((c >> 3) ^ ((lane >> 1) & 1)) << 4) + (c & 7) * 2;
#pragma unroll
    for (int i = 0; i < 3; i++) {
      *(__nv_bfloat16*)(on + i * B_SLOT) = __float2bfloat16(o[2 * i] * inv);
      *(__nv_bfloat16*)(on + i * B_SLOT + 32) = __float2bfloat16(o[2 * i + 1] * inv);
    }
  }
}
__device__ __forceinline__ void attn_helper(const Params& p, int hw, int item, int epoch) {
  int bud = WAIT_BUDGET;
  if (hw == 2) {
    if (item == 0 && elect_one()) {
      *(volatile int*)&g_ticket = 0;
      asm volatile("red.release.gpu.global.add.s32 [%0], 1;" ::"l"(&g_go) : "memory");
    }
    __syncwarp();
    flag_wait(bud, &g_go, epoch + 1);
  }
  if (item < PF_N && hw < 2) {
    const char* g = (const char*)(hw ? p.vp[0] : p.kp[0]) + (size_t)(((item & 15) * NH + (item >> 4)) * SK) * DH * 2;
    const long long t0 = clock64();
#pragma unroll 1
    for (int i = 0; i < 32; i++) {
      while (clock64() - t0 < PF_WAIT + i * PF_GAP) __nanosleep(50);
      for (int k = 0; k < 6; k++) asm volatile("prefetch.global.L2 [%0];" ::"l"(g + i * 6144 + k * 1024 + (tid_x() & 31) * 32));
      __syncwarp();
    }
  }
#pragma unroll 1
  for (int it = 0; item < NITEMS; it++) {
    const uint32_t par = it & 1;
    int lane = tid_x() & 31;
    const int r = lane >> 1;
    const uint32_t a0 = B_ADDR(3) + (16 * hw + r) * 128 + (lane & 1) * 16 + ((r & 3) << 5);
    float acc[4] = {0.f, 0.f, 0.f, 0.f};
#pragma unroll 1
    for (int j = 0; j < 8; j++) {
      const uint32_t pb = a0 + (j & 1) * B_SLOT, bfull = BAR_PFULL + (j & 1) * 8, pfull = (j >> 1) & 1;
      mbar_wait(bud, j == 7 ? BAR_PMID : bfull, j == 7 ? par : pfull);
      sum_unit(acc[0], pb);
      if (j == 7) mbar_wait(bud, BAR_PMID + 8, par);
      sum_unit(acc[1], pb + 6144);
      if (j == 7) mbar_wait(bud, bfull, pfull);
      sum_unit(acc[2], pb + 2 * 6144);
      if (hw == 0) sum_unit(acc[3], pb + 3 * 6144);
      __syncwarp();
      mbar_arrive_if0(BAR_PFREE + (j & 1) * 8, lane);
      if (j == 5 && hw == 2) {
        if (lane == 0) TLP(60);
        if (item >= ORING && item < OFRESH) flag_wait(bud, &g_done[item - ORING], (epoch + 1) * 2);
        if (lane == 0) TLP(61);
      }
    }
    bool bad = false;
    const uint32_t la = SB + OFF_L + (((r & 7) >> 1) * 40 + 2 * (r >> 3) + (r & 1) + 4 * hw) * 4;
#pragma unroll
    for (int u = 0; u < 4; u++) {
      const float l = acc[u] + __shfl_xor_sync(0xffffffffu, acc[u], 1);
      if (u < 3 || hw == 0) {
        bad |= !(l >= 9.094947017729282e-13f && l <= 1.099511627776e12f);
        float inv;
        asm("rcp.approx.ftz.f32 %0, %1;" : "=f"(inv) : "f"(l));
        asm volatile("st.shared.f32 [%0], %1;" ::"r"(la + u * 48), "f"(inv) : "memory");
      }
    }
    publish_generic(BAR_LFULL, lane);
    if (lane == 0) TLP(40 + hw * 4);
    uint32_t anybad;
    asm volatile("{\n.reg .pred p, q;\nsetp.ne.u32 p, %1, 0;\nbarrier.red.or.pred q, 7, 96, p;\nselp.u32 %0, 1, 0, q;\n}\n"
                 : "=r"(anybad) : "r"((uint32_t)bad) : "memory");
    if (__any_sync(0xffffffffu, anybad)) {
      mbar_wait(bud, BAR_OFULL, par);
      slow_item(p, item, hw);
      bar_sync(7, 96);
    }
    if (hw == 1) {
      mbar_wait(bud, BAR_OFULL, par);
      if ((tid_x() & 31) == 0) {
        TLP(41 + hw * 4);
        asm volatile("red.release.gpu.global.add.s32 [%0], 1;" ::"l"(&g_ready[item]) : "memory");
        TLP(42 + hw * 4);
      }
      __syncwarp();
    }
    item = next_item();
  }
}

__device__ __forceinline__ int attn_producer(const Params& p, int item) {
  int bud = WAIT_BUDGET;
  uint32_t sa = 0, pa = 1;
  const uint64_t pol = evict_first_policy();
  const bool draws = item >= N_OCTA;
  const int delay = start_delay(item);
  {
    const long long t0 = clock64();
    while (clock64() - t0 < delay) __nanosleep(100);
  }
#pragma unroll 1
  for (int it = 0; item < NITEMS; it++) {
    const int blk = item >> 9, h = (item >> 4) & 31, b = item & 15;
    const int row0 = (b * NH + h) * SK;
#pragma unroll
    for (int c = 0; c < 10; c++) {
      if (c >= NSLOT || (it | delay)) {
        mbar_wait(bud, BAR_EMPTYA + sa * 8, pa);
        TLP(c);
        mbar_expect(BAR_FULLA + sa * 8, A_SLOT + B_SLOT);
        tma3d(A_ADDR(sa), &p.wq[blk], BAR_FULLA + sa * 8, 0, c * 64, h * 3);
        mbar_wait(bud, BAR_EMPTYB + xs(c) * 8, c < NSLOT);
        TLP(10 + c);
        tma2d(B_ADDR(xs(c)), &p.x[blk], BAR_FULLA + sa * 8, c * 64, b * SQ);
      }
      if (++sa == NSLOT) { sa = 0; pa ^= 1; }
    }
#pragma unroll
    for (int i = 0; i < 16; i++) {
      const bool isK = (i == 0) || ((i & 1) && i < 15);
      const int j = i == 0 ? 0 : (i == 15 ? 7 : (isK ? (i + 1) >> 1 : (i - 2) >> 1));
      mbar_wait(bud, BAR_EMPTYA + sa * 8, pa);
      TLP(20 + i);
      if (i == 11) item = draws ? NCTA + atomicAdd(&g_ticket, 1) : NITEMS;
      if (i == 13) asm volatile("st.shared.s32 [%0], %1;" ::"r"(NEXT_ITEM), "r"(item) : "memory");
      mbar_expect(BAR_FULLA + sa * 8, A_SLOT);
      tma3d_hint(A_ADDR(sa), isK ? &p.k[blk] : &p.v[blk], BAR_FULLA + sa * 8, 0, row0 + j * 64, 0, pol);
      if (++sa == NSLOT) { sa = 0; pa ^= 1; }
    }
  }
  return item;
}

struct OJob { int tile, part, c0, n; };
__device__ __forceinline__ OJob get_ojob(int cta, int last) {
  if (cta < N_OCTA) return OJob{cta, 0, 0, CHUNK1};
  const int u = last - NITEMS, part = 1 + (u >> 5), tile = part == 3 ? 95 - u : u & 31;
  const int c1 = CHUNK1, c2 = c1 + LEN1 - ((tile * LSLOPE1 + 16) >> 5), c3 = c2 + LEN2 - ((tile * LSLOPE2 + 16) >> 5);
  return OJob{tile, part, part == 1 ? c1 : part == 2 ? c2 : c3, part == 1 ? c2 - c1 + 1 : part == 2 ? c3 - c2 + 1 : part == 3 ? 189 - c3 + 1 : 0};
}
__device__ __forceinline__ int unperm(int c) { return 8 * ((c >> 1) & 1) + 4 * (c >> 3) + 2 * ((c >> 2) & 1) + (c & 1); }
__device__ __forceinline__ uint32_t first_stage(const OJob& job) { return job.part ? (uint32_t)(300 - job.n) % 3 : 0; }

template <int W>
__device__ __forceinline__ void oproj_consumer(const Params& p, const OJob job) {
  int bud = WAIT_BUDGET;
  const int tid = threadIdx.x & 127, lane = tid & 31, warp = tid >> 5;
  float a0[80], a1[80], ah[40];
  zero_regs(a0); zero_regs(a1); zero_regs(ah);
  int left = job.n, step = 0;
  uint32_t st = first_stage(job), ph = 0;
#pragma unroll 1
  while (left) {
    const int nc = left > 3 * NH ? 3 * NH : left;
    left -= nc;
#pragma unroll 1
    for (int c = 0; c < nc; c++) {
      mbar_wait(bud, BAR_GFULL + st * 8, (ph >> st) & 1);
      ph ^= 1 << st;
      if (W == 0) asm volatile("{\n.reg .pred p;\nsetp.eq.s32 p, %0, %1;\n@p bar.sync 11, 256;\n}\n" ::"r"(c + 1), "r"(nc) : "memory");
      wg_fence();
      const uint32_t la = lo_sw(SB + st * O_STAGE), lb = lo_o(SB + st * O_STAGE + O_AB);
#define O_STEP(ks, sc)                                                        \
  mma80r<1, 1, 2 * 8192 + ks * 2048, W * 10240 + ks * 512>(ah, la, lb, sc);   \
  mma160r<1, 1, (W * 3) * 8192 + ks * 2048, ks * 512>(a0, la, lb, sc);        \
  mma160r<1, 1, (W * 3 + 1) * 8192 + ks * 2048, ks * 512>(a1, la, lb, sc);
      O_STEP(0, c != 0) O_STEP(1, 1)
      wg_commit();
      wg_wait<1>();
      mbar_arrive_if0(BAR_GEMPTY + (st == 0 ? 2 : st - 1) * 8, tid | (c == 0));
      wg_fence();
      O_STEP(2, 1) O_STEP(3, 1)
#undef O_STEP
      wg_commit();
      if (++st == 3) {
        st = 0;
        if (W == 0)
          asm volatile("{\n.reg .pred p;\nsetp.eq.u32 p, %1, 0;\n@p red.relaxed.gpu.global.add.s32 [%0], 1;\n}\n"
                       ::"l"(&g_done[step * 16 + (job.tile >> 1)]), "r"(tid | job.part) : "memory");
        TLG(step);
        step++;
      }
    }
    if (W == 1) bar_arrive(11, 256);
    wg_wait<0>();
    reg_fence(a0); reg_fence(a1); reg_fence(ah);
    mbar_arrive_if0(BAR_GEMPTY + (st - 1) * 8, tid | (st == 0));
    TLG(63);
    const int prow = (lane & 7) + 8 * (lane >> 4), qrow = left ? unperm(prow) : prow;
    const uint32_t sg = SB + O_OUT + qrow * 128 + (((2 * warp + ((lane >> 3) & 1)) ^ (qrow & 7)) << 4);
    if (W == 1) {
      bar_arrive(3, 256);
      store_scaled(sg + 3 * B_SLOT, a0, 1.0f);
      publish(BAR_GOUT + 24, lane);
      store_scaled(sg + 4 * B_SLOT, a1, 1.0f);
      publish(BAR_GOUT + 32, lane);
      bar_sync(9, 256);
      store_scaled(sg + 2 * B_SLOT + 10240, ah, 1.0f);
      publish(BAR_GOUT + 16, lane);
    } else {
      bar_arrive(9, 256);
      bar_sync(3, 256);
      store_scaled(sg, a0, 1.0f);
      publish(BAR_GOUT, lane);
      store_scaled(sg + B_SLOT, a1, 1.0f);
      publish(BAR_GOUT + 8, lane);
      store_scaled(sg + 2 * B_SLOT, ah, 1.0f);
      publish(BAR_GOUT + 16, lane);
    }
  }
  TL_FLUSH();
  TLG(0);
  float acc[7][8];
  uint32_t in[7], blk[7], oo[7];
#pragma unroll
  for (int i = 0; i < 7; i++) {
    const int e = min(i * 256 + W * 128 + tid, 1599), r = e / 40, cc = e % 40, R = job.part * 40 + r;
    in[i] = r * 128 + (((cc ^ r) & 7) << 4);
    blk[i] = cc >> 3;
    oo[i] = ((R & ~15) + unperm(R & 15)) * (2 * DM / 8) + cc;
    asm volatile("" : "+r"(oo[i]));
#pragma unroll
    for (int k = 0; k < 8; k++) acc[i][k] = 0.f;
  }
  bar_sync(10, 256);
#pragma unroll 1
  for (int q = 0; q < 4; q++) {
    if (q) mbar_wait(bud, BAR_GRED + (q - 1) * 8, 0);
    if (q == 3) TLG(1);
    const uint32_t base = q ? SB + (q - 1) * 25600 : SB + O_OUT + job.part * 5120, bs = q ? 5120 : B_SLOT;
    uint4 v[7];
#pragma unroll
    for (int i = 0; i < 7; i++) v[i] = lds128(base + blk[i] * bs + in[i]);
#pragma unroll
    for (int i = 0; i < 7; i++) {
      acc[i][0] += bf_lo(v[i].x); acc[i][1] += bf_hi(v[i].x); acc[i][2] += bf_lo(v[i].y); acc[i][3] += bf_hi(v[i].y);
      acc[i][4] += bf_lo(v[i].z); acc[i][5] += bf_hi(v[i].z); acc[i][6] += bf_lo(v[i].w); acc[i][7] += bf_hi(v[i].w);
    }
  }
  uint4* go = (uint4*)p.outp + (job.tile >> 1) * SQ * (2 * DM / 8) + DM / 8 + (job.tile & 1) * 40;
#pragma unroll
  for (int i = 0; i < 7; i++) {
    if (i * 256 + W * 128 + tid < 1600)
      go[oo[i]] = make_uint4(pack2(acc[i][0], acc[i][1]), pack2(acc[i][2], acc[i][3]), pack2(acc[i][4], acc[i][5]), pack2(acc[i][6], acc[i][7]));
  }
  TLG(2);
  TL_FLUSH();
}

__device__ __forceinline__ void oproj_producer(const Params& p, const OJob job, int target) {
  int bud = WAIT_BUDGET;
  const uint64_t polo = evict_first_policy();
  mbar_wait(bud, BAR_FREE, 0);
  uint32_t st = first_stage(job), ph = 7;
  int seen = -1;
#pragma unroll 1
  for (int i = 0; i < job.n; i++) {
    const int c = job.part && i == job.n - 1 ? 188 + job.part : job.c0 + i, step = c / 3, kb = c - 3 * step;
    const int item = step * 16 + (job.tile >> 1);
    if (step != seen) {
      flag_wait(bud, &g_ready[item], target);
      asm volatile("fence.proxy.async.global;" ::: "memory");
      seen = step;
    }
    const uint32_t dst = SB + st * O_STAGE, bar = BAR_GFULL + st * 8;
    const char* og = o_slot(item) + kb * B_SLOT;
    mbar_wait(bud, BAR_GEMPTY + st * 8, (ph >> st) & 1);
    ph ^= 1 << st;
    mbar_expect(bar, O_STAGE);
    tma3d(dst, &p.wo[step >> 5], bar, 0, (c - (step >> 5) * 3 * NH) * 64, (job.tile & 1) * 5);
    bulk_load_hint(dst + O_AB, og, B_SLOT, bar, polo);
    if (++st == 3) st = 0;
  }
  mbar_wait(bud, BAR_GEMPTY, ph & 1);
  mbar_wait(bud, BAR_GEMPTY + 8, (ph >> 1) & 1);
  uint32_t todo = 15 & ~(1 << job.part), dst = SB, bar = BAR_GRED;
  while (todo) {
    int v0, v1, v2, v3;
    asm volatile("ld.acquire.gpu.global.v4.s32 {%0, %1, %2, %3}, [%4];" : "=r"(v0), "=r"(v1), "=r"(v2), "=r"(v3) : "l"(&g_pcnt[job.tile * 4]) : "memory");
    const uint32_t rdy = --bud > 0 ? (v0 - target >= 0) | (v1 - target >= 0) << 1 | (v2 - target >= 0) << 2 | (v3 - target >= 0) << 3 : 15;
    if (!(rdy & todo)) continue;
    asm volatile("fence.proxy.async.global;" ::: "memory");
#pragma unroll 1
    for (int q = 0; q < 4; q++) {
      if (!(((rdy & todo) >> q) & 1)) continue;
      TLE(4 + q);
      mbar_expect(bar, 25600);
      for (int k = 0; k < 5; k++)
        tma2d(dst + k * 5120, &p.part, bar, (job.tile & 1) * 320 + k * 64, q * NB * SQ + (job.tile >> 1) * SQ + job.part * 40);
      todo &= ~(1 << q);
      dst += 25600;
      bar += 8;
    }
  }
}

__device__ __forceinline__ void oproj_storer(const Params& p, const OJob job) {
  int bud = WAIT_BUDGET;
  const int col = (job.tile & 1) * 320, row = (job.tile >> 1) * SQ;
  if (job.part == 0) {
    for (int k = 0; k < 3; k++) {
      mbar_wait(bud, BAR_GOUT + k * 8, 0);
      tma_store2d(&p.out, SB + O_OUT + k * B_SLOT, col + k * 64, row);
    }
    asm volatile("cp.async.bulk.commit_group;" ::: "memory");
    asm volatile("cp.async.bulk.wait_group.read 0;" ::: "memory");
    mbar_arrive2_if0(BAR_GEMPTY + 16, 0);
    mbar_wait(bud, BAR_GFULL + 16, 0);
    for (int k = 3; k < 5; k++) {
      mbar_wait(bud, BAR_GOUT + k * 8, 0);
      tma_store2d(&p.out, SB + O_OUT + k * B_SLOT, col + k * 64, row);
      asm volatile("cp.async.bulk.commit_group;" ::: "memory");
      asm volatile("cp.async.bulk.wait_group.read 0;" ::: "memory");
      __nanosleep(1000);
    }
  }
#pragma unroll 1
  for (int i = 0; i < 5; i++) {
    const int k = (0x21043 >> (4 * i)) & 15;
    mbar_wait(bud, BAR_GOUT + k * 8, job.part == 0);
    if (i == 0) TLE(0);
    for (int q = 1; q < 4; q++) {
      const int sh = (job.part + q) & 3;
      tma_store2d(&p.part, SB + O_OUT + k * B_SLOT + sh * 5120, col + k * 64, job.part * NB * SQ + row + sh * 40);
    }
  }
  asm volatile("cp.async.bulk.commit_group;" ::: "memory");
  TLE(1);
  asm volatile("cp.async.bulk.wait_group 0;" ::: "memory");
  TLE(2);
  asm volatile("fence.proxy.async.global;" ::: "memory");
  asm volatile("red.release.gpu.global.add.s32 [%0], 1;" ::"l"(&g_pcnt[job.tile * 4 + job.part]) : "memory");
  TLE(3);
}

__global__ void __launch_bounds__(384, 1) fused_kernel(const __grid_constant__ Params p) {
  extern __shared__ __align__(1024) char smem_raw[];
  if ((smem_u32(smem_raw) & 0xFFFFFFu) != SB) return;
  const int cta = (((blockIdx.x / PERM_G) * PERM_M) % (NCTA / PERM_G)) * PERM_G + (blockIdx.x % PERM_G);
  const int warp = __shfl_sync(0xffffffffu, threadIdx.x >> 5, 0);
  if (threadIdx.x == 0) {
    for (int i = 0; i < NSLOT; i++) { mbar_init(BAR_FULLA + i * 8, 1); mbar_init(BAR_EMPTYA + i * 8, 2); mbar_init(BAR_EMPTYB + i * 8, 2); }
    proxy_fence();
    if (start_delay(cta) == 0) {
#pragma unroll 1
      for (int c = 0; c < NSLOT; c++) {
        mbar_expect(BAR_FULLA + c * 8, A_SLOT + B_SLOT);
        tma3d(A_ADDR(c), &p.wq[0], BAR_FULLA + c * 8, 0, c * 64, (cta >> 4) * 3);
        tma2d(B_ADDR(c), &p.x[0], BAR_FULLA + c * 8, c * 64, (cta & 15) * SQ);
      }
    }
  }
  if (threadIdx.x == 64) {
    mbar_init(BAR_XDONE, 1); mbar_init(BAR_QH, 4); mbar_init(BAR_QM, 4);
    mbar_init(BAR_PFULL, 4); mbar_init(BAR_PFULL + 8, 4); mbar_init(BAR_PFREE, 3); mbar_init(BAR_PFREE + 8, 3);
    mbar_init(BAR_LFULL, 3); mbar_init(BAR_PMID, 4); mbar_init(BAR_PMID + 8, 4); mbar_init(BAR_OFULL, 8);
  }
  if (threadIdx.x == 96) {
    for (int i = 0; i < O_NST; i++) { mbar_init(BAR_GFULL + i * 8, 1); mbar_init(BAR_GEMPTY + i * 8, 2); }
    for (int i = 0; i < 5; i++) mbar_init(BAR_GOUT + i * 8, i == 2 ? 8 : 4);
    mbar_init(BAR_GRED, 1); mbar_init(BAR_GRED + 8, 1); mbar_init(BAR_GRED + 16, 1); mbar_init(BAR_FREE, 2);
    proxy_fence();
  }
  if (warp == 1 && threadIdx.x < 32 + 12) asm volatile("prefetch.tensormap [%0];" ::"l"(&p.x[0] + (threadIdx.x - 32)) : "memory");
  __syncthreads();
  if (warp >= 8) {
    asm volatile("setmaxnreg.dec.sync.aligned.u32 40;");
    if (warp == 8) {
      if (elect_one()) {
        const OJob job = get_ojob(cta, attn_producer(p, cta));
        const int epoch = *(volatile int*)&g_epoch[cta];
        *(volatile int*)&g_epoch[cta] = epoch + 1;
        if (job.n) oproj_producer(p, job, epoch + 1);
      }
    } else {
      const int epoch = __shfl_sync(0xffffffffu, *(volatile int*)&g_epoch[cta], 0);
      attn_helper(p, warp - 9, cta, epoch);
      if (warp == 9) {
        const OJob job = get_ojob(cta, next_item());
        if (job.n && elect_one()) oproj_storer(p, job);
      }
    }
  } else {
    asm volatile("setmaxnreg.inc.sync.aligned.u32 232;");
    if (warp < 4) {
      const OJob job = get_ojob(cta, attn_consumer<0>(cta));
      if (job.n) oproj_consumer<0>(p, job);
    } else {
      const OJob job = get_ojob(cta, attn_consumer<1>(cta));
      if (job.n) oproj_consumer<1>(p, job);
    }
  }
}

typedef CUresult (*EncodeFn)(CUtensorMap*, CUtensorMapDataType, cuuint32_t, void*, const cuuint64_t*, const cuuint64_t*, const cuuint32_t*,
                             const cuuint32_t*, CUtensorMapInterleave, CUtensorMapSwizzle, CUtensorMapL2promotion, CUtensorMapFloatOOBfill);

void make3d(EncodeFn enc, CUtensorMap* m, const void* ptr, uint64_t rows, uint64_t cols, uint32_t box_rows, uint32_t box_blocks,
            CUtensorMapL2promotion promo = CU_TENSOR_MAP_L2_PROMOTION_L2_128B) {
  cuuint64_t gd[3] = {64, rows, cols / 64};
  cuuint64_t gs[2] = {cols * 2, 128};
  cuuint32_t bd[3] = {64, box_rows, box_blocks}, es[3] = {1, 1, 1};
  enc(m, CU_TENSOR_MAP_DATA_TYPE_BFLOAT16, 3, (void*)ptr, gd, gs, bd, es, CU_TENSOR_MAP_INTERLEAVE_NONE, CU_TENSOR_MAP_SWIZZLE_128B,
      promo, CU_TENSOR_MAP_FLOAT_OOB_FILL_NONE);
}
void make2d(EncodeFn enc, CUtensorMap* m, const void* ptr, uint64_t rows, uint64_t cols, uint32_t box_rows) {
  cuuint64_t gd[2] = {cols, rows};
  cuuint64_t gs[1] = {cols * 2};
  cuuint32_t bd[2] = {64, box_rows}, es[2] = {1, 1};
  enc(m, CU_TENSOR_MAP_DATA_TYPE_BFLOAT16, 2, (void*)ptr, gd, gs, bd, es, CU_TENSOR_MAP_INTERLEAVE_NONE, CU_TENSOR_MAP_SWIZZLE_128B,
      CU_TENSOR_MAP_L2_PROMOTION_L2_128B, CU_TENSOR_MAP_FLOAT_OOB_FILL_NONE);
}

}

extern "C" void kernel_launch(void* const* d_in, const int* in_sizes, int n_in, void* d_out, int out_size) {
  static EncodeFn enc = nullptr;
  static void* part = nullptr;
  if (!enc) {
    cudaGetSymbolAddress(&part, g_part);
    cudaDriverEntryPointQueryResult qr;
    cudaGetDriverEntryPoint("cuTensorMapEncodeTiled", (void**)&enc, cudaEnableDefault, &qr);
    cudaFuncSetAttribute(fused_kernel, cudaFuncAttributeMaxDynamicSharedMemorySize, SMEM_BYTES);
  }
  Params p;
  for (int s = 0; s < 2; s++) {
    make2d(enc, &p.x[s], d_in[5 * s + 0], NB * SQ, DM, SQ);
    make3d(enc, &p.k[s], d_in[5 * s + 1], (uint64_t)NB * NH * SK, DH, 64, 3);
    make3d(enc, &p.v[s], d_in[5 * s + 2], (uint64_t)NB * NH * SK, DH, 64, 3);
    make3d(enc, &p.wq[s], d_in[5 * s + 3], DM, NH * DH, 64, 3);
    make3d(enc, &p.wo[s], d_in[5 * s + 4], NH * DH, DM, 64, 5);
    p.xp[s] = (const __nv_bfloat16*)d_in[5 * s + 0];
    p.wqp[s] = (const __nv_bfloat16*)d_in[5 * s + 3];
    p.kp[s] = (const __nv_bfloat16*)d_in[5 * s + 1];
    p.vp[s] = (const __nv_bfloat16*)d_in[5 * s + 2];
  }
  make2d(enc, &p.out, d_out, NB * SQ, 2 * DM, SQ);
  make2d(enc, &p.part, part, 4 * NB * SQ, DM, 40);
  p.outp = (__nv_bfloat16*)d_out;
  fused_kernel<<<NCTA, 384, SMEM_BYTES>>>(p);
}
```

```cpp
#include <cuda_runtime.h>
#include <cuda_bf16.h>
#include <cuda.h>
#include <stdint.h>

#define DEBUG_TIMEOUT 0

namespace {

constexpr int SQ = 160, DM = 640, NH = 32, SK = 512, DH = 192, NB = 16;
constexpr int NITEMS = 2 * NB * NH;
constexpr int NCTA = 132, N_OCTA = 32;
constexpr int ORING = 192, OFRESH = 800, CHUNK1 = 157, LEN1 = 18, LEN2 = 13, LSLOPE1 = 4, LSLOPE2 = 4;
constexpr int STAG_G = 4, PERM_G = 4, STAG_A0 = 19, STAG_SLOPE = 275, PERM_M = 20, PF_N = 32, PF_WAIT = 1500, PF_GAP = 300;
constexpr int OSLOTS = ORING + NITEMS - OFRESH;
constexpr int A_SLOT = 24576, B_SLOT = 20480, NSLOT = 5;
constexpr int OFF_A = 0;
constexpr int OFF_B = NSLOT * A_SLOT;
constexpr int O_STAGE = 61440, O_AB = 40960, O_NST = 3;
constexpr int OFF_L = OFF_B + NSLOT * B_SLOT;
constexpr int OFF_BAR = OFF_L + 160 * 4;
constexpr int SMEM_BYTES = OFF_BAR + 512 + 512;
constexpr int O_OUT = 2 * O_STAGE;
static_assert(O_OUT + 5 * B_SLOT <= OFF_L, "smem layout");
constexpr uint32_t SB = 1024;
constexpr uint32_t BARS = SB + OFF_BAR;
constexpr uint32_t BAR_FULLA = BARS, BAR_EMPTYA = BARS + 40, BAR_PMID = BARS + 80, BAR_EMPTYB = BARS + 120, BAR_XDONE = BARS + 160,
                   BAR_QH = BARS + 168, BAR_QM = BARS + 96, BAR_PFULL = BARS + 184, BAR_PFREE = BARS + 200, BAR_LFULL = BARS + 216,
                   BAR_OFULL = BARS + 224, BAR_GFULL = BARS + 248, BAR_GEMPTY = BARS + 280, BAR_GOUT = BARS + 328, BAR_GRED = BARS + 368,
                   BAR_FREE = BARS + 240, NEXT_ITEM = BARS + 320;
constexpr int O_ITEM_BYTES = SQ * DH * 2;

struct alignas(64) Params {
  CUtensorMap x[2], wq[2], k[2], v[2], wo[2], out, part;
  __nv_bfloat16* outp;
  const __nv_bfloat16 *xp[2], *wqp[2], *kp[2], *vp[2];
};

__device__ uint4 g_o[(size_t)OSLOTS * O_ITEM_BYTES / 16];
__device__ uint4 g_part[4 * NB * SQ * DM / 8];
__device__ __align__(16) int g_pcnt[4 * N_OCTA];
__device__ int g_ready[NITEMS];
__device__ int g_done[NITEMS];
__device__ int g_ticket;
__device__ int g_go;
__device__ int g_epoch[NCTA];

#define TLE(id)
#define TLP(id)
#define TLG(id)
#define TL(id)
#define TL_FLUSH()
__device__ __forceinline__ uint32_t smem_u32(const void* p) { return (uint32_t)__cvta_generic_to_shared(p); }
__device__ __forceinline__ void wg_fence() { asm volatile("wgmma.fence.sync.aligned;" ::: "memory"); }
__device__ __forceinline__ void wg_commit() { asm volatile("wgmma.commit_group.sync.aligned;" ::: "memory"); }
template <int N> __device__ __forceinline__ void wg_wait() { asm volatile("wgmma.wait_group.sync.aligned %0;" ::"n"(N) : "memory"); }
template <int N> __device__ __forceinline__ void reg_fence(float (&d)[N]) {
#pragma unroll
  for (int i = 0; i < N; i++) asm volatile("" : "+f"(d[i])::"memory");
}
template <int N> __device__ __forceinline__ void zero_regs(float (&d)[N]) {
#pragma unroll
  for (int i = 0; i < N; i++) d[i] = 0.f;
}
__device__ __forceinline__ void proxy_fence() { asm volatile("fence.proxy.async.shared::cta;" ::: "memory"); }
__device__ __forceinline__ void mbar_init(uint32_t bar, int cnt) { asm volatile("mbarrier.init.shared::cta.b64 [%0], %1;" ::"r"(bar), "r"(cnt) : "memory"); }
__device__ __forceinline__ void mbar_arrive_if0(uint32_t bar, uint32_t sel) {
  asm volatile("{\n.reg .pred p;\nsetp.eq.u32 p, %1, 0;\n@p mbarrier.arrive.shared::cta.b64 _, [%0];\n}\n" ::"r"(bar), "r"(sel) : "memory");
}
__device__ __forceinline__ void mbar_arrive2_if0(uint32_t bar, uint32_t sel) {
  asm volatile("{\n.reg .pred p;\nsetp.eq.u32 p, %1, 0;\n@p mbarrier.arrive.shared::cta.b64 _, [%0], 2;\n}\n" ::"r"(bar), "r"(sel) : "memory");
}
__device__ __forceinline__ void mbar_expect(uint32_t bar, uint32_t bytes) {
  asm volatile("mbarrier.arrive.expect_tx.shared::cta.b64 _, [%0], %1;" ::"r"(bar), "r"(bytes) : "memory");
}
__device__ __forceinline__ void mbar_wait(int& bud, uint32_t bar, uint32_t parity) {
  asm volatile(
      "{\n.reg .pred p;\n"
      "LW:\n"
      "mbarrier.try_wait.parity.shared::cta.b64 p, [%0], %1;\n"
      "@!p bra LW;\n}\n" ::"r"(bar), "r"(parity) : "memory");
}
constexpr int WAIT_BUDGET = 1 << 22;
__device__ __forceinline__ bool elect_one() {
  uint32_t p;
  asm volatile("{\n.reg .pred p;\nelect.sync _|p, 0xffffffff;\nselp.u32 %0, 1, 0, p;\n}\n" : "=r"(p));
  return p;
}
__device__ __forceinline__ void tma2d(uint32_t dst, const CUtensorMap* m, uint32_t bar, int c0, int c1) {
  asm volatile("cp.async.bulk.tensor.2d.shared::cluster.global.mbarrier::complete_tx::bytes [%0], [%1, {%3, %4}], [%2];"
               ::"r"(dst), "l"(m), "r"(bar), "r"(c0), "r"(c1) : "memory");
}
__device__ __forceinline__ void tma3d(uint32_t dst, const CUtensorMap* m, uint32_t bar, int c0, int c1, int c2) {
  asm volatile("cp.async.bulk.tensor.3d.shared::cluster.global.mbarrier::complete_tx::bytes [%0], [%1, {%3, %4, %5}], [%2];"
               ::"r"(dst), "l"(m), "r"(bar), "r"(c0), "r"(c1), "r"(c2) : "memory");
}
__device__ __forceinline__ void tma3d_hint(uint32_t dst, const CUtensorMap* m, uint32_t bar, int c0, int c1, int c2, uint64_t pol) {
  asm volatile("cp.async.bulk.tensor.3d.shared::cluster.global.mbarrier::complete_tx::bytes.L2::cache_hint [%0], [%1, {%3, %4, %5}], [%2], %6;"
               ::"r"(dst), "l"(m), "r"(bar), "r"(c0), "r"(c1), "r"(c2), "l"(pol) : "memory");
}
__device__ __forceinline__ void tma_store2d(const CUtensorMap* m, uint32_t src, int c0, int c1) {
  asm volatile("cp.async.bulk.tensor.2d.global.shared::cta.bulk_group [%0, {%2, %3}], [%1];" ::"l"(m), "r"(src), "r"(c0), "r"(c1) : "memory");
}
__device__ __forceinline__ void bar_sync(int id, int n) { asm volatile("bar.sync %0, %1;" ::"r"(id), "r"(n) : "memory"); }
__device__ __forceinline__ void bar_arrive(int id, int n) { asm volatile("bar.arrive %0, %1;" ::"r"(id), "r"(n) : "memory"); }
__device__ __forceinline__ float ex2(float x) { float y; asm("ex2.approx.ftz.f32 %0, %1;" : "=f"(y) : "f"(x)); return y; }
__device__ __forceinline__ uint32_t pack2(float lo, float hi) { uint32_t r; asm("cvt.rn.bf16x2.f32 %0, %1, %2;" : "=r"(r) : "f"(hi), "f"(lo)); return r; }
__device__ __forceinline__ void stsm_t(uint32_t a, uint32_t r0, uint32_t r1, uint32_t r2, uint32_t r3) {
  asm volatile("stmatrix.sync.aligned.m8n8.x4.trans.shared.b16 [%0], {%1,%2,%3,%4};" ::"r"(a), "r"(r0), "r"(r1), "r"(r2), "r"(r3) : "memory");
}
__device__ __forceinline__ uint64_t evict_first_policy() {
  uint64_t pol;
  asm volatile("createpolicy.fractional.L2::evict_first.b64 %0, 1.0;" : "=l"(pol));
  return pol;
}
__device__ __forceinline__ void bulk_load_hint(uint32_t dst, const void* src, uint32_t bytes, uint32_t bar, uint64_t pol) {
  asm volatile("cp.async.bulk.shared::cluster.global.mbarrier::complete_tx::bytes.L2::cache_hint [%0], [%1], %2, [%3], %4;"
               ::"r"(dst), "l"(src), "r"(bytes), "r"(bar), "l"(pol) : "memory");
}
__device__ __forceinline__ void flag_wait(int& bud, const int* p, int target) {
  while (true) {
    int v;
    asm volatile("ld.acquire.gpu.global.s32 %0, [%1];" : "=r"(v) : "l"(p) : "memory");
    if (v - target >= 0 || --bud <= 0) break;
    __nanosleep(64);
  }
}
__device__ __forceinline__ uint32_t lo_sw(uint32_t addr) { return (addr >> 4) | (1u << 16); }
__device__ __forceinline__ uint32_t lo_o(uint32_t addr) { return (addr >> 4) | (128u << 16); }
__device__ __forceinline__ uint32_t tid_x() { uint32_t t; asm volatile("mov.u32 %0, %tid.x;" : "=r"(t)); return t; }
__device__ __forceinline__ uint32_t opaque(uint32_t x) { uint32_t y; asm volatile("mov.u32 %0, %1;" : "=r"(y) : "r"(x)); return y; }

template <int TA, int TB, uint32_t OA, uint32_t OB>
__device__ __forceinline__ void mma160(float (&d)[80], uint32_t la, uint32_t lb) {
  asm volatile(
      "{\n.reg .pred p;\n.reg .b32 a, b;\n.reg .b64 da, db;\nsetp.eq.b32 p, 0, 0;\n"
      "add.u32 a, %80, %84;\nadd.u32 b, %81, %85;\nmov.b64 da, {a, 0x40000040};\nmov.b64 db, {b, %86};\n"
      "wgmma.mma_async.sync.aligned.m64n160k16.f32.bf16.bf16 {"
      "%0,%1,%2,%3,%4,%5,%6,%7,%8,%9,%10,%11,%12,%13,%14,%15,%16,%17,%18,%19,%20,%21,%22,%23,%24,%25,%26,%27,%28,%29,%30,%31,%32,%33,%34,%35,%36,"
      "%37,%38,%39,%40,%41,%42,%43,%44,%45,%46,%47,%48,%49,%50,%51,%52,%53,%54,%55,%56,%57,%58,%59,%60,%61,%62,%63,%64,%65,%66,%67,%68,%69,%70,%71,"
      "%72,%73,%74,%75,%76,%77,%78,%79"
      "}, da, db, p, 1, 1, %82, %83;\n}\n"
      :
      "+f"(d[0]),"+f"(d[1]),"+f"(d[2]),"+f"(d[3]),"+f"(d[4]),"+f"(d[5]),"+f"(d[6]),"+f"(d[7]),"+f"(d[8]),"+f"(d[9]),"+f"(d[10]),"+f"(d[11]),
      "+f"(d[12]),"+f"(d[13]),"+f"(d[14]),"+f"(d[15]),"+f"(d[16]),"+f"(d[17]),"+f"(d[18]),"+f"(d[19]),"+f"(d[20]),"+f"(d[21]),"+f"(d[22]),
      "+f"(d[23]),"+f"(d[24]),"+f"(d[25]),"+f"(d[26]),"+f"(d[27]),"+f"(d[28]),"+f"(d[29]),"+f"(d[30]),"+f"(d[31]),"+f"(d[32]),"+f"(d[33]),
      "+f"(d[34]),"+f"(d[35]),"+f"(d[36]),"+f"(d[37]),"+f"(d[38]),"+f"(d[39]),"+f"(d[40]),"+f"(d[41]),"+f"(d[42]),"+f"(d[43]),"+f"(d[44]),
      "+f"(d[45]),"+f"(d[46]),"+f"(d[47]),"+f"(d[48]),"+f"(d[49]),"+f"(d[50]),"+f"(d[51]),"+f"(d[52]),"+f"(d[53]),"+f"(d[54]),"+f"(d[55]),
      "+f"(d[56]),"+f"(d[57]),"+f"(d[58]),"+f"(d[59]),"+f"(d[60]),"+f"(d[61]),"+f"(d[62]),"+f"(d[63]),"+f"(d[64]),"+f"(d[65]),"+f"(d[66]),
      "+f"(d[67]),"+f"(d[68]),"+f"(d[69]),"+f"(d[70]),"+f"(d[71]),"+f"(d[72]),"+f"(d[73]),"+f"(d[74]),"+f"(d[75]),"+f"(d[76]),"+f"(d[77]),
      "+f"(d[78]),"+f"(d[79])
      : "r"(la), "r"(lb), "n"(TA), "n"(TB), "n"(OA >> 4), "n"(OB >> 4), "n"(TB ? 0xC0000010u : 0x40000040u));
}

template <int TA, int TB, uint32_t OA, uint32_t OB>
__device__ __forceinline__ void mma160z(float (&d)[80], uint32_t la, uint32_t lb) {
  asm volatile(
      "{\n.reg .pred p;\n.reg .b32 a, b;\n.reg .b64 da, db;\nsetp.ne.b32 p, 0, 0;\n"
      "add.u32 a, %80, %84;\nadd.u32 b, %81, %85;\nmov.b64 da, {a, 0x40000040};\nmov.b64 db, {b, %86};\n"
      "wgmma.mma_async.sync.aligned.m64n160k16.f32.bf16.bf16 {"
      "%0,%1,%2,%3,%4,%5,%6,%7,%8,%9,%10,%11,%12,%13,%14,%15,%16,%17,%18,%19,%20,%21,%22,%23,%24,%25,%26,%27,%28,%29,%30,%31,%32,%33,%34,%35,%36,"
      "%37,%38,%39,%40,%41,%42,%43,%44,%45,%46,%47,%48,%49,%50,%51,%52,%53,%54,%55,%56,%57,%58,%59,%60,%61,%62,%63,%64,%65,%66,%67,%68,%69,%70,%71,"
      "%72,%73,%74,%75,%76,%77,%78,%79"
      "}, da, db, p, 1, 1, %82, %83;\n}\n"
      :
      "=f"(d[0]),"=f"(d[1]),"=f"(d[2]),"=f"(d[3]),"=f"(d[4]),"=f"(d[5]),"=f"(d[6]),"=f"(d[7]),"=f"(d[8]),"=f"(d[9]),"=f"(d[10]),"=f"(d[11]),
      "=f"(d[12]),"=f"(d[13]),"=f"(d[14]),"=f"(d[15]),"=f"(d[16]),"=f"(d[17]),"=f"(d[18]),"=f"(d[19]),"=f"(d[20]),"=f"(d[21]),"=f"(d[22]),
      "=f"(d[23]),"=f"(d[24]),"=f"(d[25]),"=f"(d[26]),"=f"(d[27]),"=f"(d[28]),"=f"(d[29]),"=f"(d[30]),"=f"(d[31]),"=f"(d[32]),"=f"(d[33]),
      "=f"(d[34]),"=f"(d[35]),"=f"(d[36]),"=f"(d[37]),"=f"(d[38]),"=f"(d[39]),"=f"(d[40]),"=f"(d[41]),"=f"(d[42]),"=f"(d[43]),"=f"(d[44]),
      "=f"(d[45]),"=f"(d[46]),"=f"(d[47]),"=f"(d[48]),"=f"(d[49]),"=f"(d[50]),"=f"(d[51]),"=f"(d[52]),"=f"(d[53]),"=f"(d[54]),"=f"(d[55]),
      "=f"(d[56]),"=f"(d[57]),"=f"(d[58]),"=f"(d[59]),"=f"(d[60]),"=f"(d[61]),"=f"(d[62]),"=f"(d[63]),"=f"(d[64]),"=f"(d[65]),"=f"(d[66]),
      "=f"(d[67]),"=f"(d[68]),"=f"(d[69]),"=f"(d[70]),"=f"(d[71]),"=f"(d[72]),"=f"(d[73]),"=f"(d[74]),"=f"(d[75]),"=f"(d[76]),"=f"(d[77]),
      "=f"(d[78]),"=f"(d[79])
      : "r"(la), "r"(lb), "n"(TA), "n"(TB), "n"(OA >> 4), "n"(OB >> 4), "n"(TB ? 0xC0000010u : 0x40000040u));
}

template <int TA, int TB, uint32_t OA, uint32_t OB>
__device__ __forceinline__ void mma80(float (&d)[40], uint32_t la, uint32_t lb) {
  asm volatile(
      "{\n.reg .pred p;\n.reg .b32 a, b;\n.reg .b64 da, db;\nsetp.eq.b32 p, 0, 0;\n"
      "add.u32 a, %40, %44;\nadd.u32 b, %41, %45;\nmov.b64 da, {a, 0x40000040};\nmov.b64 db, {b, %46};\n"
      "wgmma.mma_async.sync.aligned.m64n80k16.f32.bf16.bf16 {"
      "%0,%1,%2,%3,%4,%5,%6,%7,%8,%9,%10,%11,%12,%13,%14,%15,%16,%17,%18,%19,%20,%21,%22,%23,%24,%25,%26,%27,%28,%29,%30,%31,%32,%33,%34,%35,%36,"
      "%37,%38,%39"
      "}, da, db, p, 1, 1, %42, %43;\n}\n"
      :
      "+f"(d[0]),"+f"(d[1]),"+f"(d[2]),"+f"(d[3]),"+f"(d[4]),"+f"(d[5]),"+f"(d[6]),"+f"(d[7]),"+f"(d[8]),"+f"(d[9]),"+f"(d[10]),"+f"(d[11]),
      "+f"(d[12]),"+f"(d[13]),"+f"(d[14]),"+f"(d[15]),"+f"(d[16]),"+f"(d[17]),"+f"(d[18]),"+f"(d[19]),"+f"(d[20]),"+f"(d[21]),"+f"(d[22]),
      "+f"(d[23]),"+f"(d[24]),"+f"(d[25]),"+f"(d[26]),"+f"(d[27]),"+f"(d[28]),"+f"(d[29]),"+f"(d[30]),"+f"(d[31]),"+f"(d[32]),"+f"(d[33]),
      "+f"(d[34]),"+f"(d[35]),"+f"(d[36]),"+f"(d[37]),"+f"(d[38]),"+f"(d[39])
      : "r"(la), "r"(lb), "n"(TA), "n"(TB), "n"(OA >> 4), "n"(OB >> 4), "n"(TB ? 0xC0000010u : 0x40000040u));
}

template <int TA, int TB, uint32_t OA, uint32_t OB>
__device__ __forceinline__ void mma80z(float (&d)[40], uint32_t la, uint32_t lb) {
  asm volatile(
      "{\n.reg .pred p;\n.reg .b32 a, b;\n.reg .b64 da, db;\nsetp.ne.b32 p, 0, 0;\n"
      "add.u32 a, %40, %44;\nadd.u32 b, %41, %45;\nmov.b64 da, {a, 0x40000040};\nmov.b64 db, {b, %46};\n"
      "wgmma.mma_async.sync.aligned.m64n80k16.f32.bf16.bf16 {"
      "%0,%1,%2,%3,%4,%5,%6,%7,%8,%9,%10,%11,%12,%13,%14,%15,%16,%17,%18,%19,%20,%21,%22,%23,%24,%25,%26,%27,%28,%29,%30,%31,%32,%33,%34,%35,%36,"
      "%37,%38,%39"
      "}, da, db, p, 1, 1, %42, %43;\n}\n"
      :
      "=f"(d[0]),"=f"(d[1]),"=f"(d[2]),"=f"(d[3]),"=f"(d[4]),"=f"(d[5]),"=f"(d[6]),"=f"(d[7]),"=f"(d[8]),"=f"(d[9]),"=f"(d[10]),"=f"(d[11]),
      "=f"(d[12]),"=f"(d[13]),"=f"(d[14]),"=f"(d[15]),"=f"(d[16]),"=f"(d[17]),"=f"(d[18]),"=f"(d[19]),"=f"(d[20]),"=f"(d[21]),"=f"(d[22]),
      "=f"(d[23]),"=f"(d[24]),"=f"(d[25]),"=f"(d[26]),"=f"(d[27]),"=f"(d[28]),"=f"(d[29]),"=f"(d[30]),"=f"(d[31]),"=f"(d[32]),"=f"(d[33]),
      "=f"(d[34]),"=f"(d[35]),"=f"(d[36]),"=f"(d[37]),"=f"(d[38]),"=f"(d[39])
      : "r"(la), "r"(lb), "n"(TA), "n"(TB), "n"(OA >> 4), "n"(OB >> 4), "n"(TB ? 0xC0000010u : 0x40000040u));
}

template <int TA, int TB, uint32_t OA, uint32_t OB>
__device__ __forceinline__ void mma160r(float (&d)[80], uint32_t la, uint32_t lb, int sc) {
  asm volatile(
      "{\n.reg .pred p;\n.reg .b32 a, b;\n.reg .b64 da, db;\nsetp.ne.b32 p, %87, 0;\n"
      "add.u32 a, %80, %84;\nadd.u32 b, %81, %85;\nmov.b64 da, {a, 0x40000040};\nmov.b64 db, {b, %86};\n"
      "wgmma.mma_async.sync.aligned.m64n160k16.f32.bf16.bf16 {"
      "%0,%1,%2,%3,%4,%5,%6,%7,%8,%9,%10,%11,%12,%13,%14,%15,%16,%17,%18,%19,%20,%21,%22,%23,%24,%25,%26,%27,%28,%29,%30,%31,%32,%33,%34,%35,%36,"
      "%37,%38,%39,%40,%41,%42,%43,%44,%45,%46,%47,%48,%49,%50,%51,%52,%53,%54,%55,%56,%57,%58,%59,%60,%61,%62,%63,%64,%65,%66,%67,%68,%69,%70,%71,"
      "%72,%73,%74,%75,%76,%77,%78,%79"
      "}, da, db, p, 1, 1, %82, %83;\n}\n"
      :
      "+f"(d[0]),"+f"(d[1]),"+f"(d[2]),"+f"(d[3]),"+f"(d[4]),"+f"(d[5]),"+f"(d[6]),"+f"(d[7]),"+f"(d[8]),"+f"(d[9]),"+f"(d[10]),"+f"(d[11]),
      "+f"(d[12]),"+f"(d[13]),"+f"(d[14]),"+f"(d[15]),"+f"(d[16]),"+f"(d[17]),"+f"(d[18]),"+f"(d[19]),"+f"(d[20]),"+f"(d[21]),"+f"(d[22]),
      "+f"(d[23]),"+f"(d[24]),"+f"(d[25]),"+f"(d[26]),"+f"(d[27]),"+f"(d[28]),"+f"(d[29]),"+f"(d[30]),"+f"(d[31]),"+f"(d[32]),"+f"(d[33]),
      "+f"(d[34]),"+f"(d[35]),"+f"(d[36]),"+f"(d[37]),"+f"(d[38]),"+f"(d[39]),"+f"(d[40]),"+f"(d[41]),"+f"(d[42]),"+f"(d[43]),"+f"(d[44]),
      "+f"(d[45]),"+f"(d[46]),"+f"(d[47]),"+f"(d[48]),"+f"(d[49]),"+f"(d[50]),"+f"(d[51]),"+f"(d[52]),"+f"(d[53]),"+f"(d[54]),"+f"(d[55]),
      "+f"(d[56]),"+f"(d[57]),"+f"(d[58]),"+f"(d[59]),"+f"(d[60]),"+f"(d[61]),"+f"(d[62]),"+f"(d[63]),"+f"(d[64]),"+f"(d[65]),"+f"(d[66]),
      "+f"(d[67]),"+f"(d[68]),"+f"(d[69]),"+f"(d[70]),"+f"(d[71]),"+f"(d[72]),"+f"(d[73]),"+f"(d[74]),"+f"(d[75]),"+f"(d[76]),"+f"(d[77]),
      "+f"(d[78]),"+f"(d[79])
      : "r"(la), "r"(lb), "n"(TA), "n"(TB), "n"(OA >> 4), "n"(OB >> 4), "n"(TB ? 0xC0000010u : 0x40000040u), "r"(sc));
}

template <int TA, int TB, uint32_t OA, uint32_t OB>
__device__ __forceinline__ void mma80r(float (&d)[40], uint32_t la, uint32_t lb, int sc) {
  asm volatile(
      "{\n.reg .pred p;\n.reg .b32 a, b;\n.reg .b64 da, db;\nsetp.ne.b32 p, %47, 0;\n"
      "add.u32 a, %40, %44;\nadd.u32 b, %41, %45;\nmov.b64 da, {a, 0x40000040};\nmov.b64 db, {b, %46};\n"
      "wgmma.mma_async.sync.aligned.m64n80k16.f32.bf16.bf16 {"
      "%0,%1,%2,%3,%4,%5,%6,%7,%8,%9,%10,%11,%12,%13,%14,%15,%16,%17,%18,%19,%20,%21,%22,%23,%24,%25,%26,%27,%28,%29,%30,%31,%32,%33,%34,%35,%36,"
      "%37,%38,%39"
      "}, da, db, p, 1, 1, %42, %43;\n}\n"
      :
      "+f"(d[0]),"+f"(d[1]),"+f"(d[2]),"+f"(d[3]),"+f"(d[4]),"+f"(d[5]),"+f"(d[6]),"+f"(d[7]),"+f"(d[8]),"+f"(d[9]),"+f"(d[10]),"+f"(d[11]),
      "+f"(d[12]),"+f"(d[13]),"+f"(d[14]),"+f"(d[15]),"+f"(d[16]),"+f"(d[17]),"+f"(d[18]),"+f"(d[19]),"+f"(d[20]),"+f"(d[21]),"+f"(d[22]),
      "+f"(d[23]),"+f"(d[24]),"+f"(d[25]),"+f"(d[26]),"+f"(d[27]),"+f"(d[28]),"+f"(d[29]),"+f"(d[30]),"+f"(d[31]),"+f"(d[32]),"+f"(d[33]),
      "+f"(d[34]),"+f"(d[35]),"+f"(d[36]),"+f"(d[37]),"+f"(d[38]),"+f"(d[39])
      : "r"(la), "r"(lb), "n"(TA), "n"(TB), "n"(OA >> 4), "n"(OB >> 4), "n"(TB ? 0xC0000010u : 0x40000040u), "r"(sc));
}

struct Ring { uint32_t s0, ph0; };
__device__ __forceinline__ void ring_pos(const Ring& r, int i, uint32_t& slot, uint32_t& ph) {
  uint32_t s = opaque(r.s0) + (i % NSLOT);
  uint32_t wrap = s >= NSLOT;
  slot = s - (wrap ? NSLOT : 0);
  ph = r.ph0 ^ ((i / NSLOT) & 1) ^ wrap;
}
__device__ __forceinline__ void ring_advance(Ring& r, int n) {
  uint32_t s, p;
  ring_pos(r, n, s, p);
  r.s0 = s; r.ph0 = p;
}
__host__ __device__ constexpr int idxK(int j) { return j == 0 ? 10 : 9 + 2 * j; }
__host__ __device__ constexpr int idxV(int j) { return j == 7 ? 25 : 12 + 2 * j; }
__host__ __device__ constexpr int xs(int c) { return c % NSLOT; }

__device__ __forceinline__ int start_delay(int cta) {
  return max(0, ((cta - N_OCTA) | (STAG_G - 1)) - STAG_A0) * STAG_SLOPE;
}
__device__ __forceinline__ char* o_slot(int item) {
  return (char*)g_o + (size_t)(item < OFRESH ? item % ORING : item - OFRESH + ORING) * O_ITEM_BYTES;
}
__device__ __forceinline__ int next_item(uint32_t a = NEXT_ITEM) {
  int v;
  asm volatile("ld.shared.s32 %0, [%1];" : "=r"(v) : "r"(a) : "memory");
  return __shfl_sync(0xffffffffu, v, 0);
}

template <int W, bool ACC>
__device__ __forceinline__ void mma_main(float (&d)[80], uint32_t aaddr, uint32_t baddr) {
  const uint32_t la = lo_sw(aaddr), lb = lo_sw(baddr);
  if (ACC) mma160<1, 0, W * 16384, 0>(d, la, lb); else mma160z<1, 0, W * 16384, 0>(d, la, lb);
  mma160<1, 0, W * 16384 + 1 * 2048, 1 * 32>(d, la, lb);
  mma160<1, 0, W * 16384 + 2 * 2048, 2 * 32>(d, la, lb);
  mma160<1, 0, W * 16384 + 3 * 2048, 3 * 32>(d, la, lb);
}
template <int W, bool ACC>
__device__ __forceinline__ void mma_mid(float (&d)[40], uint32_t aaddr, uint32_t baddr) {
  const uint32_t la = lo_sw(aaddr), lb = lo_sw(baddr);
  if (ACC) mma80<1, 0, 8192, W * 10240>(d, la, lb); else mma80z<1, 0, 8192, W * 10240>(d, la, lb);
  mma80<1, 0, 8192 + 1 * 2048, W * 10240 + 1 * 32>(d, la, lb);
  mma80<1, 0, 8192 + 2 * 2048, W * 10240 + 2 * 32>(d, la, lb);
  mma80<1, 0, 8192 + 3 * 2048, W * 10240 + 3 * 32>(d, la, lb);
}
template <int W, bool ACC>
__device__ __forceinline__ void mma_both(float (&dm)[80], float (&dh)[40], uint32_t aaddr, uint32_t baddr) {
  mma_mid<W, ACC>(dh, aaddr, baddr);
  mma_main<W, ACC>(dm, aaddr, baddr);
}
template <int KB, bool ACC>
__device__ __forceinline__ void s_mma(float (&sacc)[80], uint32_t kaddr) {
  const uint32_t la = lo_sw(kaddr), lb = lo_sw(SB + OFF_B);
  if (ACC) mma160<0, 0, KB * 8192, KB * B_SLOT>(sacc, la, lb); else mma160z<0, 0, KB * 8192, KB * B_SLOT>(sacc, la, lb);
  mma160<0, 0, KB * 8192 + 32, KB * B_SLOT + 32>(sacc, la, lb);
  mma160<0, 0, KB * 8192 + 64, KB * B_SLOT + 64>(sacc, la, lb);
  mma160<0, 0, KB * 8192 + 96, KB * B_SLOT + 96>(sacc, la, lb);
}
template <int N>
__device__ __forceinline__ void store_scaled(uint32_t addr, const float (&d)[N], float sc) {
#pragma unroll
  for (int J = 0; J < N / 8; J++)
    stsm_t(addr + J * 2048, pack2(d[8 * J] * sc, d[8 * J + 1] * sc), pack2(d[8 * J + 2] * sc, d[8 * J + 3] * sc),
           pack2(d[8 * J + 4] * sc, d[8 * J + 5] * sc), pack2(d[8 * J + 6] * sc, d[8 * J + 7] * sc));
}
__device__ __forceinline__ float4 lds_f4(uint32_t a) {
  float4 v;
  asm volatile("ld.shared.v4.f32 {%0,%1,%2,%3}, [%4];" : "=f"(v.x), "=f"(v.y), "=f"(v.z), "=f"(v.w) : "r"(a) : "memory");
  return v;
}
__device__ __forceinline__ void norm_pack(uint32_t* p, const float* d, const float4& i) {
  p[0] = pack2(d[0] * i.x, d[1] * i.y); p[1] = pack2(d[4] * i.z, d[5] * i.w);
  p[2] = pack2(d[2] * i.x, d[3] * i.y); p[3] = pack2(d[6] * i.z, d[7] * i.w);
  asm volatile("" : "+r"(p[0]), "+r"(p[1]), "+r"(p[2]), "+r"(p[3])::"memory");
}
template <int W>
__device__ __forceinline__ void pack_first(uint32_t (&pk)[60], const float (&om)[80], const float (&oh)[40], uint32_t laddr) {
  float4 n0 = lds_f4(laddr + W * 80), n1 = lds_f4(laddr + W * 80 + 16);
#pragma unroll
  for (int J = 0; J < 5; J++) {
    const float4 i = n0;
    n0 = n1;
    if (J + 2 < 5) n1 = lds_f4(laddr + W * 80 + (J + 2) * 16);
    norm_pack(&pk[20 + 4 * J], &om[8 * (5 * W + J)], i);
    norm_pack(&pk[4 * J], &oh[8 * J], i);
  }
}
template <int W, int J0, int J1>
__device__ __forceinline__ void pack_second(uint32_t (&pk)[60], const float (&om)[80], uint32_t laddr) {
  float4 n[J1 - J0];
#pragma unroll
  for (int J = J0; J < J1; J++) n[J - J0] = lds_f4(laddr + (1 - W) * 80 + J * 16);
#pragma unroll
  for (int J = J0; J < J1; J++) norm_pack(&pk[40 + 4 * J], &om[8 * (5 * (1 - W) + J)], n[J - J0]);
}
__device__ __forceinline__ char* o_ptr(int item) {
  const uint32_t t = tid_x();
  return o_slot(item) + ((t & 96) * 16 + (t & 28) * 8 + ((((t >> 1) ^ (t >> 4)) & 1) << 4) + (t & 1) * 8);
}
template <int W, int G0, int G1>
__device__ __forceinline__ void store_groups(char* op, const uint32_t (&pk)[60], uint32_t on) {
#pragma unroll
  for (int G = G0; G < G1; G++) {
    const int off = (G < 5 ? 1 : 2 * W) * B_SLOT + (5 * (G < 10 ? W : 1 - W) + G % 5) * 2048;
    asm volatile("{\n.reg .pred p;\nsetp.ne.u32 p, %5, 0;\n@p st.global.v2.b32 [%0], {%1, %2};\n@p st.global.v2.b32 [%0+256], {%3, %4};\n}\n"
                 ::"l"(op + off), "r"(pk[4 * G]), "r"(pk[4 * G + 1]), "r"(pk[4 * G + 2]), "r"(pk[4 * G + 3]), "r"(on) : "memory");
  }
}
__device__ __forceinline__ void publish_generic(uint32_t bar, int lane) {
  __syncwarp();
  mbar_arrive_if0(bar, lane);
}
__device__ __forceinline__ void publish(uint32_t bar, int lane) {
  proxy_fence();
  __syncwarp();
  mbar_arrive_if0(bar, lane);
}

#define A_ADDR(s) (SB + OFF_A + (s) * A_SLOT)
#define B_ADDR(s) (SB + OFF_B + (s) * B_SLOT)
#define WAIT_CHUNK(c, ro, sA)                \
  uint32_t sA;                               \
  {                                          \
    uint32_t pA_;                            \
    ring_pos(ring, (ro) + (c), sA, pA_);     \
    mbar_wait(bud, BAR_FULLA + sA * 8, pA_); \
  }
#define RELEASE_CHUNK(c, sA)                                  \
  mbar_arrive_if0(BAR_EMPTYA + (sA) * 8, tid);                \
  if ((c) < NSLOT) mbar_arrive_if0(BAR_EMPTYB + xs(c) * 8, tid);

template <int W>
__device__ __forceinline__ int attn_consumer(int item) {
  int bud = WAIT_BUDGET;
  const int tid = threadIdx.x & 127, lane = tid & 31, warp = tid >> 5;
  const uint32_t st_off = ((lane & 7) + 8 * (lane >> 4)) * 128 + (((2 * warp + ((lane >> 3) & 1)) ^ (lane & 7)) << 4);
  const uint32_t laddr = SB + OFF_L + (lane & 3) * 160;
  float om[80], oh[40], sacc[80];
  uint32_t pk[60];
#pragma unroll
  for (int i = 0; i < 40; i++) pk[i] = 0;
  zero_regs(om);
  Ring ring{0u, 0u};
  uint32_t par = 0;
  int prev = 0;
  const float qscale = 0.07216878364870322f * 1.4426950408889634f;
  constexpr uint32_t pown = B_ADDR(3 + W), poth = B_ADDR(4 - W);
  TL(0); TLG(62);
  {
    WAIT_CHUNK(0, 0, s0)
    wg_fence();
    mma_both<W, false>(sacc, oh, A_ADDR(s0), B_ADDR(xs(0)));
    wg_commit();
    WAIT_CHUNK(1, 0, s1)
    wg_fence();
    mma_both<W, true>(sacc, oh, A_ADDR(s1), B_ADDR(xs(1)));
    wg_commit();
    wg_wait<1>();
    RELEASE_CHUNK(0, s0)
  }
#pragma unroll 1
  for (int it = 0;; it++) {
    char* op = o_ptr(prev);
#pragma unroll
    for (int c = 2; c < 8 - W; c++) {
      WAIT_CHUNK(c, 0, sA)
      TL(40 + c);
      wg_fence();
      mma_both<W, true>(sacc, oh, A_ADDR(sA), B_ADDR(xs(c)));
      wg_commit();
      wg_wait<1>();
      uint32_t sP, pP;
      ring_pos(ring, c - 1, sP, pP);
      RELEASE_CHUNK(c - 1, sP)
      constexpr int NG = 3;
      if (c == 2) { pack_second<W, 0, 1>(pk, om, laddr); store_groups<W, 0 * NG, 1 * NG>(op, pk, it); }
      if (c == 3) { pack_second<W, 1, 2>(pk, om, laddr); store_groups<W, 1 * NG, 2 * NG>(op, pk, it); }
      if (c == 4) { pack_second<W, 2, 3>(pk, om, laddr); store_groups<W, 2 * NG, 3 * NG>(op, pk, it); }
      if (c == 5) { pack_second<W, 3, 4>(pk, om, laddr); store_groups<W, 3 * NG, 4 * NG>(op, pk, it); }
      if (c == 6) {
        pack_second<W, 4, 5>(pk, om, laddr);
        if (W == 1) {
          wg_wait<0>();
          RELEASE_CHUNK(6, sA)
          mbar_arrive_if0(BAR_XDONE, tid);
        }
        store_groups<W, 4 * NG, 15>(op, pk, it);
        __syncwarp();
        mbar_arrive_if0(BAR_OFULL, lane | (it == 0));
      }
    }
    uint32_t sK0, pK0, s7, p7;
    ring_pos(ring, idxK(W), sK0, pK0);
    ring_pos(ring, 7, s7, p7);
    if (W == 1) mbar_wait(bud, BAR_FULLA + s7 * 8, p7);
    WAIT_CHUNK(8, 0, s8)
    if (W == 0) {
      wg_fence();
      mma_both<W, true>(sacc, oh, A_ADDR(s8), B_ADDR(xs(8)));
      wg_commit();
      wg_wait<1>();
      RELEASE_CHUNK(7, s7)
    }
    WAIT_CHUNK(9, 0, s9)
    TL(48);
    if (W == 0) {
      wg_fence();
      mma_mid<W, true>(oh, A_ADDR(s9), B_ADDR(xs(9)));
      wg_commit();
      mma_main<W, true>(sacc, A_ADDR(s9), B_ADDR(xs(9)));
      wg_commit();
      bar_arrive(5, 256);
      TL(49);
      wg_wait<1>();
      reg_fence(oh);
      mbar_wait(bud, BAR_XDONE, par);
      store_scaled(B_ADDR(1) + st_off, oh, qscale);
    } else {
      bar_sync(5, 256);
      wg_fence();
      mma_mid<W, true>(oh, A_ADDR(s7), B_ADDR(xs(7)));
      mma_mid<W, true>(oh, A_ADDR(s8), B_ADDR(xs(8)));
      mma_mid<W, true>(oh, A_ADDR(s9), B_ADDR(xs(9)));
      wg_commit();
      mma_main<W, true>(sacc, A_ADDR(s7), B_ADDR(xs(7)));
      wg_commit();
      mma_main<W, true>(sacc, A_ADDR(s8), B_ADDR(xs(8)));
      wg_commit();
      wg_wait<2>();
      reg_fence(oh);
      store_scaled(B_ADDR(1) + 10240 + st_off, oh, qscale);
      wg_fence();
      mma_main<W, true>(sacc, A_ADDR(s9), B_ADDR(xs(9)));
      wg_commit();
      bar_arrive(8, 256);
      TL(49);
      wg_wait<2>();
      RELEASE_CHUNK(7, s7)
      publish(BAR_QH, lane);
    }
    wg_wait<0>();
    reg_fence(sacc);
    TL(1);
    RELEASE_CHUNK(8, s8)
    RELEASE_CHUNK(9, s9)
    store_scaled(B_ADDR(2 * W) + st_off, sacc, qscale);
    if (W == 1) publish(BAR_QM, lane); else proxy_fence();
    TL(2);
    uint32_t sK = sK0, sV1 = 0;
    if (W == 0) {
      zero_regs(om); zero_regs(oh);
      reg_fence(om); reg_fence(oh);
      mbar_wait(bud, BAR_FULLA + sK0 * 8, pK0);
      bar_sync(8, 256);
      wg_fence();
      s_mma<0, false>(sacc, A_ADDR(sK));
      mbar_wait(bud, BAR_QH, par);
      TL(3);
      wg_fence();
      s_mma<1, true>(sacc, A_ADDR(sK));
      mbar_wait(bud, BAR_QM, par);
      TL(5);
      wg_fence();
      s_mma<2, true>(sacc, A_ADDR(sK));
      wg_commit();
      wg_commit();
      bar_arrive(2, 256);
    } else {
      uint32_t pV1;
      ring_pos(ring, idxV(0), sV1, pV1);
      mbar_wait(bud, BAR_FULLA + sK * 8, pK0);
      bar_sync(2, 256);
      wg_fence();
      s_mma<0, false>(sacc, A_ADDR(sK));
      s_mma<1, true>(sacc, A_ADDR(sK));
      s_mma<2, true>(sacc, A_ADDR(sK));
      wg_commit();
      TL(6);
      mbar_wait(bud, BAR_FULLA + sV1 * 8, pV1);
      mbar_wait(bud, BAR_PFULL, 0);
      TL(7);
      wg_fence();
      mma_both<W, false>(om, oh, A_ADDR(sV1), poth);
      wg_commit();
      bar_arrive(1, 256);
    }
    Ring rv;
    ring_pos(ring, idxV(W), rv.s0, rv.ph0);
#pragma unroll 1
    for (int jj = 0;; jj++) {
      wg_wait<1>();
      reg_fence(sacc);
      TL(8 + jj * 7);
      mbar_arrive2_if0(BAR_EMPTYA + sK * 8, tid);
      mbar_arrive_if0(BAR_EMPTYB + tid * 8, (tid >= 3) | (jj != 3));
#pragma unroll
      for (int J = 0; J < 10; J++) {
        stsm_t(pown + st_off + J * 2048, pack2(ex2(sacc[8 * J]), ex2(sacc[8 * J + 1])), pack2(ex2(sacc[8 * J + 2]), ex2(sacc[8 * J + 3])),
               pack2(ex2(sacc[8 * J + 4]), ex2(sacc[8 * J + 5])), pack2(ex2(sacc[8 * J + 6]), ex2(sacc[8 * J + 7])));
        if (W == 1 && (J == 2 || J == 5)) publish_generic(BAR_PMID + (J / 3) * 8, lane | (jj != 3));
        if (J == 4) {
          wg_wait<0>();
          mbar_arrive_if0(BAR_EMPTYA + sV1 * 8, tid | (W == 0 && jj == 0));
        }
      }
      publish(BAR_PFULL + W * 8, lane);
      TL(10 + jj * 7);
      if (jj == 3) break;
      uint32_t pK, pV1;
      ring_pos(rv, 1, sK, pK);
      ring_pos(rv, 2, sV1, pV1);
      mbar_wait(bud, BAR_FULLA + rv.s0 * 8, rv.ph0);
      bar_sync(1 + W, 256);
      wg_fence();
      mma_both<W, true>(om, oh, A_ADDR(rv.s0), pown);
      wg_commit();
      mbar_wait(bud, BAR_FULLA + sK * 8, pK);
      TL(11 + jj * 7);
      wg_fence();
      s_mma<0, false>(sacc, A_ADDR(sK));
      s_mma<1, true>(sacc, A_ADDR(sK));
      wg_commit();
      wg_wait<1>();
      mbar_arrive_if0(BAR_EMPTYA + rv.s0 * 8, tid);
      wg_fence();
      s_mma<2, true>(sacc, A_ADDR(sK));
      wg_commit();
      TL(13 + jj * 7);
      mbar_wait(bud, BAR_FULLA + sV1 * 8, pV1);
      mbar_wait(bud, BAR_PFREE + W * 8, jj & 1);
      mbar_wait(bud, BAR_PFULL + (1 - W) * 8, (jj + W) & 1);
      TL(14 + jj * 7);
      wg_fence();
      mma_both<W, true>(om, oh, A_ADDR(sV1), poth);
      wg_commit();
      bar_arrive(2 - W, 256);
      ring_advance(rv, 4);
    }
    uint32_t sV7, pV7;
    ring_pos(ring, idxV(7), sV7, pV7);
    prev = item;
    if (W == 1 && !DEBUG_TIMEOUT) item = next_item();
    if (W == 0) {
      uint32_t sV6, pV6;
      ring_pos(ring, idxV(6), sV6, pV6);
      mbar_wait(bud, BAR_FULLA + sV6 * 8, pV6);
      bar_sync(1, 256);
      wg_fence();
      mma_both<0, true>(om, oh, A_ADDR(sV6), pown);
      wg_commit();
      mbar_wait(bud, BAR_FULLA + sV7 * 8, pV7);
      wg_wait<0>();
      mbar_arrive_if0(BAR_EMPTYA + sV6 * 8, tid);
      mbar_wait(bud, BAR_PFULL + 8, 1);
      wg_fence();
      mma_both<0, true>(om, oh, A_ADDR(sV7), poth);
      wg_commit();
      bar_arrive(6, 256);
    } else {
      mbar_wait(bud, BAR_FULLA + sV7 * 8, pV7);
      bar_sync(6, 256);
    }
    TL(32);
    if (DEBUG_TIMEOUT) item = next_item(NEXT_ITEM + 4);
    else if (W == 0) item = next_item();
    if (item >= NITEMS) {
      if (W == 1) {
        wg_fence();
        mma_both<1, true>(om, oh, A_ADDR(sV7), pown);
        wg_commit();
      }
      wg_wait<0>();
      reg_fence(om); reg_fence(oh);
      TL(33);
      mbar_wait(bud, BAR_LFULL, par);
      mbar_arrive_if0(BAR_FREE, tid);
      TL(34);
      pack_first<W>(pk, om, oh, laddr);
      op = o_ptr(prev);
      store_groups<W, 0, 10>(op, pk, 1);
      pack_second<W, 0, 5>(pk, om, laddr);
      store_groups<W, 10, 15>(op, pk, 1);
      publish_generic(BAR_OFULL, lane);
      TL(35); TLG(63);
      TL_FLUSH();
      return item;
    }
    {
      if (W == 1) {
        wg_fence();
        mma_both<1, true>(om, oh, A_ADDR(sV7), pown);
        wg_commit();
      }
      WAIT_CHUNK(0, 26, s0)
      WAIT_CHUNK(1, 26, s1)
      if (W == 0) {
        wg_wait<0>();
        reg_fence(om); reg_fence(oh);
        TL(33);
        wg_fence();
        mma_main<W, false>(sacc, A_ADDR(s0), B_ADDR(xs(0)));
        wg_commit();
      } else {
        wg_fence();
        mma_main<W, false>(sacc, A_ADDR(s0), B_ADDR(xs(0)));
        mma_main<W, true>(sacc, A_ADDR(s1), B_ADDR(xs(1)));
        wg_commit();
        wg_wait<1>();
        reg_fence(om); reg_fence(oh);
        TL(33);
      }
      mbar_arrive_if0(BAR_EMPTYA + sV7 * 8, tid);
      mbar_wait(bud, BAR_LFULL, par);
      mbar_arrive_if0(BAR_EMPTYB + 24 + tid * 8, tid >= 2);
      TL(34);
      pack_first<W>(pk, om, oh, laddr);
      TL(36);
      wg_fence();
      mma_mid<W, false>(oh, A_ADDR(s0), B_ADDR(xs(0)));
      wg_commit();
      mma_mid<W, true>(oh, A_ADDR(s1), B_ADDR(xs(1)));
      if (W == 0) mma_main<W, true>(sacc, A_ADDR(s1), B_ADDR(xs(1)));
      wg_commit();
      TL(37);
      wg_wait<1>();
      RELEASE_CHUNK(0, s0)
      TL(35); TLG(63);
    }
    TL_FLUSH();
    TL(0); TLG(62);
    ring_advance(ring, 26);
    par ^= 1;
  }
}

__device__ __forceinline__ uint4 lds128(uint32_t a) {
  uint4 v;
  asm volatile("ld.shared.v4.b32 {%0,%1,%2,%3}, [%4];" : "=r"(v.x), "=r"(v.y), "=r"(v.z), "=r"(v.w) : "r"(a) : "memory");
  return v;
}
__device__ __forceinline__ void acc2(float& s, float& t, uint32_t w) {
  s += __uint_as_float(w << 16);
  t += __uint_as_float(w & 0xffff0000u);
}
__device__ __forceinline__ uint32_t badd2(uint32_t a, uint32_t b) { uint32_t r; asm("add.rn.bf16x2 %0, %1, %2;" : "=r"(r) : "r"(a), "r"(b)); return r; }
__device__ __forceinline__ void sum_unit(float& acc, uint32_t pb) {
  const uint4 v0 = lds128(pb), v1 = lds128(pb ^ 32), v2 = lds128(pb ^ 64), v3 = lds128(pb ^ 96);
  const uint32_t w0 = badd2(badd2(v0.x, v0.y), badd2(v0.z, v0.w));
  float s = acc + __uint_as_float(w0 << 16), t = __uint_as_float(w0 & 0xffff0000u);
  acc2(s, t, badd2(badd2(v1.x, v1.y), badd2(v1.z, v1.w)));
  acc2(s, t, badd2(badd2(v2.x, v2.y), badd2(v2.z, v2.w)));
  acc2(s, t, badd2(badd2(v3.x, v3.y), badd2(v3.z, v3.w)));
  acc = s + t;
}
__device__ __forceinline__ float bf_lo(uint32_t w) { return __uint_as_float(w << 16); }
__device__ __forceinline__ float bf_hi(uint32_t w) { return __uint_as_float(w & 0xffff0000u); }
__device__ __forceinline__ float bf_rn(float x) { return __bfloat162float(__float2bfloat16(x)); }
__device__ __forceinline__ void slow_item(const Params& p, int item, int hw) {
  const int blk = item >> 9, h = (item >> 4) & 31, b = item & 15;
#pragma unroll 1
  for (int n = hw; n < SQ; n += 3) {
    float q[6] = {0.f, 0.f, 0.f, 0.f, 0.f, 0.f};
    {
      const uint32_t* xr = (const uint32_t*)(p.xp[blk] + (size_t)(b * SQ + n) * DM);
      const uint32_t* wq = (const uint32_t*)(p.wqp[blk] + h * DH) + (tid_x() & 31);
#pragma unroll 2
      for (int k = 0; k < DM / 2; k++) {
        const uint32_t xv = xr[k];
#pragma unroll
        for (int i = 0; i < 3; i++) {
          const uint32_t w0 = wq[i * 32], w1 = wq[NH * DH / 2 + i * 32];
          q[2 * i] = fmaf(bf_lo(xv), bf_lo(w0), fmaf(bf_hi(xv), bf_lo(w1), q[2 * i]));
          q[2 * i + 1] = fmaf(bf_lo(xv), bf_hi(w0), fmaf(bf_hi(xv), bf_hi(w1), q[2 * i + 1]));
        }
        wq += NH * DH;
      }
    }
    const uint32_t q0 = pack2(q[0], q[1]), q1 = pack2(q[2], q[3]), q2 = pack2(q[4], q[5]);
    float o[6] = {0.f, 0.f, 0.f, 0.f, 0.f, 0.f}, m = -INFINITY, l = 0.f;
    const uint32_t* kg = (const uint32_t*)(p.kp[blk] + (size_t)(b * NH + h) * SK * DH) + (tid_x() & 31);
    const uint32_t* vg = (const uint32_t*)(p.vp[blk] + (size_t)(b * NH + h) * SK * DH) + (tid_x() & 31);
#pragma unroll 1
    for (int k = 0; k < SK; k++) {
      const uint32_t k0 = kg[0], k1 = kg[32], k2 = kg[64], v0 = vg[0], v1 = vg[32], v2 = vg[64];
      kg += DH / 2; vg += DH / 2;
      float sc = fmaf(bf_lo(q0), bf_lo(k0), bf_hi(q0) * bf_hi(k0));
      sc = fmaf(bf_lo(q1), bf_lo(k1), fmaf(bf_hi(q1), bf_hi(k1), sc));
      sc = fmaf(bf_lo(q2), bf_lo(k2), fmaf(bf_hi(q2), bf_hi(k2), sc));
#pragma unroll
      for (int d = 16; d; d >>= 1) sc += __shfl_xor_sync(0xffffffffu, sc, d);
      sc = bf_rn(bf_rn(sc) * 0.07216878364870322f);
      const float mn = fmaxf(m, sc), a = ex2((m - mn) * 1.4426950408889634f), pr = ex2((sc - mn) * 1.4426950408889634f);
      m = mn;
      l = fmaf(l, a, pr);
      o[0] = fmaf(o[0], a, pr * bf_lo(v0)); o[1] = fmaf(o[1], a, pr * bf_hi(v0));
      o[2] = fmaf(o[2], a, pr * bf_lo(v1)); o[3] = fmaf(o[3], a, pr * bf_hi(v1));
      o[4] = fmaf(o[4], a, pr * bf_lo(v2)); o[5] = fmaf(o[5], a, pr * bf_hi(v2));
    }
    float inv;
    asm("rcp.approx.ftz.f32 %0, %1;" : "=f"(inv) : "f"(l));
    const int lane = tid_x() & 31;
    const int r = n & 15, c = 4 * ((r & 7) >> 1) + 2 * (r >> 3) + (r & 1);
    char* on = o_slot(item) + (lane >> 2) * 256 + (lane & 3) * 64 + (n >> 4) * 2048 +
               (((c >> 3) ^ ((lane >> 1) & 1)) << 4) + (c & 7) * 2;
#pragma unroll
    for (int i = 0; i < 3; i++) {
      *(__nv_bfloat16*)(on + i * B_SLOT) = __float2bfloat16(o[2 * i] * inv);
      *(__nv_bfloat16*)(on + i * B_SLOT + 32) = __float2bfloat16(o[2 * i + 1] * inv);
    }
  }
}
__device__ __forceinline__ void attn_helper(const Params& p, int hw, int item, int epoch) {
  int bud = WAIT_BUDGET;
  if (hw == 2) {
    if (item == 0 && elect_one()) {
      *(volatile int*)&g_ticket = 0;
      asm volatile("red.release.gpu.global.add.s32 [%0], 1;" ::"l"(&g_go) : "memory");
    }
    __syncwarp();
    flag_wait(bud, &g_go, epoch + 1);
  }
  if (item < PF_N && hw < 2) {
    const char* g = (const char*)(hw ? p.vp[0] : p.kp[0]) + (size_t)(((item & 15) * NH + (item >> 4)) * SK) * DH * 2;
    const long long t0 = clock64();
#pragma unroll 1
    for (int i = 0; i < 32; i++) {
      while (clock64() - t0 < PF_WAIT + i * PF_GAP) __nanosleep(50);
      for (int k = 0; k < 6; k++) asm volatile("prefetch.global.L2 [%0];" ::"l"(g + i * 6144 + k * 1024 + (tid_x() & 31) * 32));
      __syncwarp();
    }
  }
#pragma unroll 1
  for (int it = 0; item < NITEMS; it++) {
    const uint32_t par = it & 1;
    int lane = tid_x() & 31;
    const int r = lane >> 1;
    const uint32_t a0 = B_ADDR(3) + (16 * hw + r) * 128 + (lane & 1) * 16 + ((r & 3) << 5);
    float acc[4] = {0.f, 0.f, 0.f, 0.f};
#pragma unroll 1
    for (int j = 0; j < 8; j++) {
      const uint32_t pb = a0 + (j & 1) * B_SLOT, bfull = BAR_PFULL + (j & 1) * 8, pfull = (j >> 1) & 1;
      mbar_wait(bud, j == 7 ? BAR_PMID : bfull, j == 7 ? par : pfull);
      sum_unit(acc[0], pb);
      if (j == 7) mbar_wait(bud, BAR_PMID + 8, par);
      sum_unit(acc[1], pb + 6144);
      if (j == 7) mbar_wait(bud, bfull, pfull);
      sum_unit(acc[2], pb + 2 * 6144);
      if (hw == 0) sum_unit(acc[3], pb + 3 * 6144);
      __syncwarp();
      mbar_arrive_if0(BAR_PFREE + (j & 1) * 8, lane);
      if (j == 5 && hw == 2) {
        if (lane == 0) TLP(60);
        if (item >= ORING && item < OFRESH) flag_wait(bud, &g_done[item - ORING], (epoch + 1) * 2);
        if (lane == 0) TLP(61);
      }
    }
    bool bad = false;
    const uint32_t la = SB + OFF_L + (((r & 7) >> 1) * 40 + 2 * (r >> 3) + (r & 1) + 4 * hw) * 4;
#pragma unroll
    for (int u = 0; u < 4; u++) {
      const float l = acc[u] + __shfl_xor_sync(0xffffffffu, acc[u], 1);
      if (u < 3 || hw == 0) {
        bad |= !(l >= 9.094947017729282e-13f && l <= 1.099511627776e12f);
        float inv;
        asm("rcp.approx.ftz.f32 %0, %1;" : "=f"(inv) : "f"(l));
        asm volatile("st.shared.f32 [%0], %1;" ::"r"(la + u * 48), "f"(inv) : "memory");
      }
    }
    publish_generic(BAR_LFULL, lane);
    if (lane == 0) TLP(40 + hw * 4);
    uint32_t anybad;
    asm volatile("{\n.reg .pred p, q;\nsetp.ne.u32 p, %1, 0;\nbarrier.red.or.pred q, 7, 96, p;\nselp.u32 %0, 1, 0, q;\n}\n"
                 : "=r"(anybad) : "r"((uint32_t)bad) : "memory");
    if (__any_sync(0xffffffffu, anybad)) {
      mbar_wait(bud, BAR_OFULL, par);
      slow_item(p, item, hw);
      bar_sync(7, 96);
    }
    if (hw == 1) {
      mbar_wait(bud, BAR_OFULL, par);
      if ((tid_x() & 31) == 0) {
        TLP(41 + hw * 4);
        asm volatile("red.release.gpu.global.add.s32 [%0], 1;" ::"l"(&g_ready[item]) : "memory");
        TLP(42 + hw * 4);
      }
      __syncwarp();
    }
    item = next_item();
  }
}

__device__ __forceinline__ int attn_producer(const Params& p, int item) {
  int bud = WAIT_BUDGET;
  uint32_t sa = 0, pa = 1;
  const uint64_t pol = evict_first_policy();
  const bool draws = item >= N_OCTA;
  const int delay = start_delay(item);
  {
    const long long t0 = clock64();
    while (clock64() - t0 < delay) __nanosleep(100);
  }
#pragma unroll 1
  for (int it = 0; item < NITEMS; it++) {
    const int blk = item >> 9, h = (item >> 4) & 31, b = item & 15;
    const int row0 = (b * NH + h) * SK;
#pragma unroll
    for (int c = 0; c < 10; c++) {
      if (c >= NSLOT || (it | delay)) {
        mbar_wait(bud, BAR_EMPTYA + sa * 8, pa);
        TLP(c);
        mbar_expect(BAR_FULLA + sa * 8, A_SLOT + B_SLOT);
        tma3d(A_ADDR(sa), &p.wq[blk], BAR_FULLA + sa * 8, 0, c * 64, h * 3);
        mbar_wait(bud, BAR_EMPTYB + xs(c) * 8, c < NSLOT);
        TLP(10 + c);
        tma2d(B_ADDR(xs(c)), &p.x[blk], BAR_FULLA + sa * 8, c * 64, b * SQ);
      }
      if (++sa == NSLOT) { sa = 0; pa ^= 1; }
    }
#pragma unroll
    for (int i = 0; i < 16; i++) {
      const bool isK = (i == 0) || ((i & 1) && i < 15);
      const int j = i == 0 ? 0 : (i == 15 ? 7 : (isK ? (i + 1) >> 1 : (i - 2) >> 1));
      mbar_wait(bud, BAR_EMPTYA + sa * 8, pa);
      TLP(20 + i);
      if (i == 11) item = draws ? NCTA + atomicAdd(&g_ticket, 1) : NITEMS;
      if (i == 13) asm volatile("st.shared.s32 [%0], %1;" ::"r"(NEXT_ITEM), "r"(item) : "memory");
      mbar_expect(BAR_FULLA + sa * 8, A_SLOT);
      tma3d_hint(A_ADDR(sa), isK ? &p.k[blk] : &p.v[blk], BAR_FULLA + sa * 8, 0, row0 + j * 64, 0, pol);
      if (++sa == NSLOT) { sa = 0; pa ^= 1; }
    }
  }
  return item;
}

struct OJob { int tile, part, c0, n; };
__device__ __forceinline__ OJob get_ojob(int cta, int last) {
  if (cta < N_OCTA) return OJob{cta, 0, 0, CHUNK1};
  const int u = last - NITEMS, part = 1 + (u >> 5), tile = part == 3 ? 95 - u : u & 31;
  const int c1 = CHUNK1, c2 = c1 + LEN1 - ((tile * LSLOPE1 + 16) >> 5), c3 = c2 + LEN2 - ((tile * LSLOPE2 + 16) >> 5);
  return OJob{tile, part, part == 1 ? c1 : part == 2 ? c2 : c3, part == 1 ? c2 - c1 + 1 : part == 2 ? c3 - c2 + 1 : part == 3 ? 189 - c3 + 1 : 0};
}
__device__ __forceinline__ int unperm(int c) { return 8 * ((c >> 1) & 1) + 4 * (c >> 3) + 2 * ((c >> 2) & 1) + (c & 1); }
__device__ __forceinline__ uint32_t first_stage(const OJob& job) { return job.part ? (uint32_t)(300 - job.n) % 3 : 0; }

template <int W>
__device__ __forceinline__ void oproj_consumer(const Params& p, const OJob job) {
  int bud = WAIT_BUDGET;
  const int tid = threadIdx.x & 127, lane = tid & 31, warp = tid >> 5;
  float a0[80], a1[80], ah[40];
  zero_regs(a0); zero_regs(a1); zero_regs(ah);
  int left = job.n, step = 0;
  uint32_t st = first_stage(job), ph = 0;
#pragma unroll 1
  while (left) {
    const int nc = left > 3 * NH ? 3 * NH : left;
    left -= nc;
#pragma unroll 1
    for (int c = 0; c < nc; c++) {
      mbar_wait(bud, BAR_GFULL + st * 8, (ph >> st) & 1);
      ph ^= 1 << st;
      if (W == 0) asm volatile("{\n.reg .pred p;\nsetp.eq.s32 p, %0, %1;\n@p bar.sync 11, 256;\n}\n" ::"r"(c + 1), "r"(nc) : "memory");
      wg_fence();
      const uint32_t la = lo_sw(SB + st * O_STAGE), lb = lo_o(SB + st * O_STAGE + O_AB);
#define O_STEP(ks, sc)                                                        \
  mma80r<1, 1, 2 * 8192 + ks * 2048, W * 10240 + ks * 512>(ah, la, lb, sc);   \
  mma160r<1, 1, (W * 3) * 8192 + ks * 2048, ks * 512>(a0, la, lb, sc);        \
  mma160r<1, 1, (W * 3 + 1) * 8192 + ks * 2048, ks * 512>(a1, la, lb, sc);
      O_STEP(0, c != 0) O_STEP(1, 1)
      wg_commit();
      wg_wait<1>();
      mbar_arrive_if0(BAR_GEMPTY + (st == 0 ? 2 : st - 1) * 8, tid | (c == 0));
      wg_fence();
      O_STEP(2, 1) O_STEP(3, 1)
#undef O_STEP
      wg_commit();
      if (++st == 3) {
        st = 0;
        if (W == 0)
          asm volatile("{\n.reg .pred p;\nsetp.eq.u32 p, %1, 0;\n@p red.relaxed.gpu.global.add.s32 [%0], 1;\n}\n"
                       ::"l"(&g_done[step * 16 + (job.tile >> 1)]), "r"(tid | job.part) : "memory");
        TLG(step);
        step++;
      }
    }
    if (W == 1) bar_arrive(11, 256);
    wg_wait<0>();
    reg_fence(a0); reg_fence(a1); reg_fence(ah);
    mbar_arrive_if0(BAR_GEMPTY + (st - 1) * 8, tid | (st == 0));
    TLG(63);
    const int prow = (lane & 7) + 8 * (lane >> 4), qrow = left ? unperm(prow) : prow;
    const uint32_t sg = SB + O_OUT + qrow * 128 + (((2 * warp + ((lane >> 3) & 1)) ^ (qrow & 7)) << 4);
    if (W == 1) {
      bar_arrive(3, 256);
      store_scaled(sg + 3 * B_SLOT, a0, 1.0f);
      publish(BAR_GOUT + 24, lane);
      store_scaled(sg + 4 * B_SLOT, a1, 1.0f);
      publish(BAR_GOUT + 32, lane);
      bar_sync(9, 256);
      store_scaled(sg + 2 * B_SLOT + 10240, ah, 1.0f);
      publish(BAR_GOUT + 16, lane);
    } else {
      bar_arrive(9, 256);
      bar_sync(3, 256);
      store_scaled(sg, a0, 1.0f);
      publish(BAR_GOUT, lane);
      store_scaled(sg + B_SLOT, a1, 1.0f);
      publish(BAR_GOUT + 8, lane);
      store_scaled(sg + 2 * B_SLOT, ah, 1.0f);
      publish(BAR_GOUT + 16, lane);
    }
  }
  TL_FLUSH();
  TLG(0);
  float acc[7][8];
  uint32_t in[7], blk[7], oo[7];
#pragma unroll
  for (int i = 0; i < 7; i++) {
    const int e = min(i * 256 + W * 128 + tid, 1599), r = e / 40, cc = e % 40, R = job.part * 40 + r;
    in[i] = r * 128 + (((cc ^ r) & 7) << 4);
    blk[i] = cc >> 3;
    oo[i] = ((R & ~15) + unperm(R & 15)) * (2 * DM / 8) + cc;
    asm volatile("" : "+r"(oo[i]));
#pragma unroll
    for (int k = 0; k < 8; k++) acc[i][k] = 0.f;
  }
  bar_sync(10, 256);
#pragma unroll 1
  for (int q = 0; q < 4; q++) {
    if (q) mbar_wait(bud, BAR_GRED + (q - 1) * 8, 0);
    if (q == 3) TLG(1);
    const uint32_t base = q ? SB + (q - 1) * 25600 : SB + O_OUT + job.part * 5120, bs = q ? 5120 : B_SLOT;
    uint4 v[7];
#pragma unroll
    for (int i = 0; i < 7; i++) v[i] = lds128(base + blk[i] * bs + in[i]);
#pragma unroll
    for (int i = 0; i < 7; i++) {
      acc[i][0] += bf_lo(v[i].x); acc[i][1] += bf_hi(v[i].x); acc[i][2] += bf_lo(v[i].y); acc[i][3] += bf_hi(v[i].y);
      acc[i][4] += bf_lo(v[i].z); acc[i][5] += bf_hi(v[i].z); acc[i][6] += bf_lo(v[i].w); acc[i][7] += bf_hi(v[i].w);
    }
  }
  uint4* go = (uint4*)p.outp + (job.tile >> 1) * SQ * (2 * DM / 8) + DM / 8 + (job.tile & 1) * 40;
#pragma unroll
  for (int i = 0; i < 7; i++) {
    if (i * 256 + W * 128 + tid < 1600)
      go[oo[i]] = make_uint4(pack2(acc[i][0], acc[i][1]), pack2(acc[i][2], acc[i][3]), pack2(acc[i][4], acc[i][5]), pack2(acc[i][6], acc[i][7]));
  }
  TLG(2);
  TL_FLUSH();
}

__device__ __forceinline__ void oproj_producer(const Params& p, const OJob job, int target) {
  int bud = WAIT_BUDGET;
  const uint64_t polo = evict_first_policy();
  mbar_wait(bud, BAR_FREE, 0);
  uint32_t st = first_stage(job), ph = 7;
  int seen = -1;
#pragma unroll 1
  for (int i = 0; i < job.n; i++) {
    const int c = job.part && i == job.n - 1 ? 188 + job.part : job.c0 + i, step = c / 3, kb = c - 3 * step;
    const int item = step * 16 + (job.tile >> 1);
    if (step != seen) {
      flag_wait(bud, &g_ready[item], target);
      asm volatile("fence.proxy.async.global;" ::: "memory");
      seen = step;
    }
    const uint32_t dst = SB + st * O_STAGE, bar = BAR_GFULL + st * 8;
    const char* og = o_slot(item) + kb * B_SLOT;
    mbar_wait(bud, BAR_GEMPTY + st * 8, (ph >> st) & 1);
    ph ^= 1 << st;
    mbar_expect(bar, O_STAGE);
    tma3d(dst, &p.wo[step >> 5], bar, 0, (c - (step >> 5) * 3 * NH) * 64, (job.tile & 1) * 5);
    bulk_load_hint(dst + O_AB, og, B_SLOT, bar, polo);
    if (++st == 3) st = 0;
  }
  mbar_wait(bud, BAR_GEMPTY, ph & 1);
  mbar_wait(bud, BAR_GEMPTY + 8, (ph >> 1) & 1);
  uint32_t todo = 15 & ~(1 << job.part), dst = SB, bar = BAR_GRED;
  while (todo) {
    int v0, v1, v2, v3;
    asm volatile("ld.acquire.gpu.global.v4.s32 {%0, %1, %2, %3}, [%4];" : "=r"(v0), "=r"(v1), "=r"(v2), "=r"(v3) : "l"(&g_pcnt[job.tile * 4]) : "memory");
    const uint32_t rdy = --bud > 0 ? (v0 - target >= 0) | (v1 - target >= 0) << 1 | (v2 - target >= 0) << 2 | (v3 - target >= 0) << 3 : 15;
    if (!(rdy & todo)) continue;
    asm volatile("fence.proxy.async.global;" ::: "memory");
#pragma unroll 1
    for (int q = 0; q < 4; q++) {
      if (!(((rdy & todo) >> q) & 1)) continue;
      TLE(4 + q);
      mbar_expect(bar, 25600);
      for (int k = 0; k < 5; k++)
        tma2d(dst + k * 5120, &p.part, bar, (job.tile & 1) * 320 + k * 64, q * NB * SQ + (job.tile >> 1) * SQ + job.part * 40);
      todo &= ~(1 << q);
      dst += 25600;
      bar += 8;
    }
  }
}

__device__ __forceinline__ void oproj_storer(const Params& p, const OJob job) {
  int bud = WAIT_BUDGET;
  const int col = (job.tile & 1) * 320, row = (job.tile >> 1) * SQ;
  if (job.part == 0) {
    for (int k = 0; k < 3; k++) {
      mbar_wait(bud, BAR_GOUT + k * 8, 0);
      tma_store2d(&p.out, SB + O_OUT + k * B_SLOT, col + k * 64, row);
    }
    asm volatile("cp.async.bulk.commit_group;" ::: "memory");
    asm volatile("cp.async.bulk.wait_group.read 0;" ::: "memory");
    mbar_arrive2_if0(BAR_GEMPTY + 16, 0);
    mbar_wait(bud, BAR_GFULL + 16, 0);
    for (int k = 3; k < 5; k++) {
      mbar_wait(bud, BAR_GOUT + k * 8, 0);
      tma_store2d(&p.out, SB + O_OUT + k * B_SLOT, col + k * 64, row);
      asm volatile("cp.async.bulk.commit_group;" ::: "memory");
      asm volatile("cp.async.bulk.wait_group.read 0;" ::: "memory");
      __nanosleep(1000);
    }
  }
#pragma unroll 1
  for (int i = 0; i < 5; i++) {
    const int k = (0x21043 >> (4 * i)) & 15;
    mbar_wait(bud, BAR_GOUT + k * 8, job.part == 0);
    if (i == 0) TLE(0);
    for (int q = 1; q < 4; q++) {
      const int sh = (job.part + q) & 3;
      tma_store2d(&p.part, SB + O_OUT + k * B_SLOT + sh * 5120, col + k * 64, job.part * NB * SQ + row + sh * 40);
    }
  }
  asm volatile("cp.async.bulk.commit_group;" ::: "memory");
  TLE(1);
  asm volatile("cp.async.bulk.wait_group 0;" ::: "memory");
  TLE(2);
  asm volatile("fence.proxy.async.global;" ::: "memory");
  asm volatile("red.release.gpu.global.add.s32 [%0], 1;" ::"l"(&g_pcnt[job.tile * 4 + job.part]) : "memory");
  TLE(3);
}

__global__ void __launch_bounds__(384, 1) fused_kernel(const __grid_constant__ Params p) {
  extern __shared__ __align__(1024) char smem_raw[];
  if ((smem_u32(smem_raw) & 0xFFFFFFu) != SB) return;
  const int cta = (((blockIdx.x / PERM_G) * PERM_M) % (NCTA / PERM_G)) * PERM_G + (blockIdx.x % PERM_G);
  const int warp = __shfl_sync(0xffffffffu, threadIdx.x >> 5, 0);
  if (threadIdx.x == 0) {
    for (int i = 0; i < NSLOT; i++) { mbar_init(BAR_FULLA + i * 8, 1); mbar_init(BAR_EMPTYA + i * 8, 2); mbar_init(BAR_EMPTYB + i * 8, 2); }
    proxy_fence();
    if (start_delay(cta) == 0) {
#pragma unroll 1
      for (int c = 0; c < NSLOT; c++) {
        mbar_expect(BAR_FULLA + c * 8, A_SLOT + B_SLOT);
        tma3d(A_ADDR(c), &p.wq[0], BAR_FULLA + c * 8, 0, c * 64, (cta >> 4) * 3);
        tma2d(B_ADDR(c), &p.x[0], BAR_FULLA + c * 8, c * 64, (cta & 15) * SQ);
      }
    }
  }
  if (threadIdx.x == 64) {
    mbar_init(BAR_XDONE, 1); mbar_init(BAR_QH, 4); mbar_init(BAR_QM, 4);
    mbar_init(BAR_PFULL, 4); mbar_init(BAR_PFULL + 8, 4); mbar_init(BAR_PFREE, 3); mbar_init(BAR_PFREE + 8, 3);
    mbar_init(BAR_LFULL, 3); mbar_init(BAR_PMID, 4); mbar_init(BAR_PMID + 8, 4); mbar_init(BAR_OFULL, 8);
  }
  if (threadIdx.x == 96) {
    for (int i = 0; i < O_NST; i++) { mbar_init(BAR_GFULL + i * 8, 1); mbar_init(BAR_GEMPTY + i * 8, 2); }
    for (int i = 0; i < 5; i++) mbar_init(BAR_GOUT + i * 8, i == 2 ? 8 : 4);
    mbar_init(BAR_GRED, 1); mbar_init(BAR_GRED + 8, 1); mbar_init(BAR_GRED + 16, 1); mbar_init(BAR_FREE, 2);
    proxy_fence();
  }
  if (warp == 1 && threadIdx.x < 32 + 12) asm volatile("prefetch.tensormap [%0];" ::"l"(&p.x[0] + (threadIdx.x - 32)) : "memory");
  __syncthreads();
  if (warp >= 8) {
    asm volatile("setmaxnreg.dec.sync.aligned.u32 40;");
    if (warp == 8) {
      if (elect_one()) {
        const OJob job = get_ojob(cta, attn_producer(p, cta));
        const int epoch = *(volatile int*)&g_epoch[cta];
        *(volatile int*)&g_epoch[cta] = epoch + 1;
        if (job.n) oproj_producer(p, job, epoch + 1);
      }
    } else {
      const int epoch = __shfl_sync(0xffffffffu, *(volatile int*)&g_epoch[cta], 0);
      attn_helper(p, warp - 9, cta, epoch);
      if (warp == 9) {
        const OJob job = get_ojob(cta, next_item());
        if (job.n && elect_one()) oproj_storer(p, job);
      }
    }
  } else {
    asm volatile("setmaxnreg.inc.sync.aligned.u32 232;");
    if (warp < 4) {
      const OJob job = get_ojob(cta, attn_consumer<0>(cta));
      if (job.n) oproj_consumer<0>(p, job);
    } else {
      const OJob job = get_ojob(cta, attn_consumer<1>(cta));
      if (job.n) oproj_consumer<1>(p, job);
    }
  }
}

typedef CUresult (*EncodeFn)(CUtensorMap*, CUtensorMapDataType, cuuint32_t, void*, const cuuint64_t*, const cuuint64_t*, const cuuint32_t*,
                             const cuuint32_t*, CUtensorMapInterleave, CUtensorMapSwizzle, CUtensorMapL2promotion, CUtensorMapFloatOOBfill);

void make3d(EncodeFn enc, CUtensorMap* m, const void* ptr, uint64_t rows, uint64_t cols, uint32_t box_rows, uint32_t box_blocks,
            CUtensorMapL2promotion promo = CU_TENSOR_MAP_L2_PROMOTION_L2_128B) {
  cuuint64_t gd[3] = {64, rows, cols / 64};
  cuuint64_t gs[2] = {cols * 2, 128};
  cuuint32_t bd[3] = {64, box_rows, box_blocks}, es[3] = {1, 1, 1};
  enc(m, CU_TENSOR_MAP_DATA_TYPE_BFLOAT16, 3, (void*)ptr, gd, gs, bd, es, CU_TENSOR_MAP_INTERLEAVE_NONE, CU_TENSOR_MAP_SWIZZLE_128B,
      promo, CU_TENSOR_MAP_FLOAT_OOB_FILL_NONE);
}
void make2d(EncodeFn enc, CUtensorMap* m, const void* ptr, uint64_t rows, uint64_t cols, uint32_t box_rows) {
  cuuint64_t gd[2] = {cols, rows};
  cuuint64_t gs[1] = {cols * 2};
  cuuint32_t bd[2] = {64, box_rows}, es[2] = {1, 1};
  enc(m, CU_TENSOR_MAP_DATA_TYPE_BFLOAT16, 2, (void*)ptr, gd, gs, bd, es, CU_TENSOR_MAP_INTERLEAVE_NONE, CU_TENSOR_MAP_SWIZZLE_128B,
      CU_TENSOR_MAP_L2_PROMOTION_L2_128B, CU_TENSOR_MAP_FLOAT_OOB_FILL_NONE);
}

}

extern "C" void kernel_launch(void* const* d_in, const int* in_sizes, int n_in, void* d_out, int out_size) {
  static EncodeFn enc = nullptr;
  static void* part = nullptr;
  if (!enc) {
    cudaGetSymbolAddress(&part, g_part);
    cudaDriverEntryPointQueryResult qr;
    cudaGetDriverEntryPoint("cuTensorMapEncodeTiled", (void**)&enc, cudaEnableDefault, &qr);
    cudaFuncSetAttribute(fused_kernel, cudaFuncAttributeMaxDynamicSharedMemorySize, SMEM_BYTES);
  }
  Params p;
  for (int s = 0; s < 2; s++) {
    make2d(enc, &p.x[s], d_in[5 * s + 0], NB * SQ, DM, SQ);
    make3d(enc, &p.k[s], d_in[5 * s + 1], (uint64_t)NB * NH * SK, DH, 64, 3);
    make3d(enc, &p.v[s], d_in[5 * s + 2], (uint64_t)NB * NH * SK, DH, 64, 3);
    make3d(enc, &p.wq[s], d_in[5 * s + 3], DM, NH * DH, 64, 3);
    make3d(enc, &p.wo[s], d_in[5 * s + 4], NH * DH, DM, 64, 5);
    p.xp[s] = (const __nv_bfloat16*)d_in[5 * s + 0];
    p.wqp[s] = (const __nv_bfloat16*)d_in[5 * s + 3];
    p.kp[s] = (const __nv_bfloat16*)d_in[5 * s + 1];
    p.vp[s] = (const __nv_bfloat16*)d_in[5 * s + 2];
  }
  make2d(enc, &p.out, d_out, NB * SQ, 2 * DM, SQ);
  make2d(enc, &p.part, part, 4 * NB * SQ, DM, 40);
  p.outp = (__nv_bfloat16*)d_out;
  fused_kernel<<<NCTA, 384, SMEM_BYTES>>>(p);
}
```

```cpp
#include <cuda_runtime.h>
#include <cuda_bf16.h>
#include <cuda.h>
#include <stdint.h>

#define DEBUG_TIMEOUT 0

namespace {

constexpr int SQ = 160, DM = 640, NH = 32, SK = 512, DH = 192, NB = 16;
constexpr int NITEMS = 2 * NB * NH;
constexpr int NCTA = 132, N_OCTA = 32;
constexpr int ORING = 192, OFRESH = 800, CHUNK1 = 157, LEN1 = 18, LEN2 = 13, LSLOPE1 = 4, LSLOPE2 = 4;
constexpr int STAG_G = 4, PERM_G = 4, STAG_A0 = 19, STAG_SLOPE = 275, PERM_M = 20, PF_N = 32, PF_WAIT = 1500, PF_GAP = 300;
constexpr int OSLOTS = ORING + NITEMS - OFRESH;
constexpr int A_SLOT = 24576, B_SLOT = 20480, NSLOT = 5;
constexpr int OFF_A = 0;
constexpr int OFF_B = NSLOT * A_SLOT;
constexpr int O_STAGE = 61440, O_AB = 40960, O_NST = 3;
constexpr int OFF_L = OFF_B + NSLOT * B_SLOT;
constexpr int OFF_BAR = OFF_L + 160 * 4;
constexpr int SMEM_BYTES = OFF_BAR + 512 + 512;
constexpr int O_OUT = 2 * O_STAGE;
static_assert(O_OUT + 5 * B_SLOT <= OFF_L, "smem layout");
constexpr uint32_t SB = 1024;
constexpr uint32_t BARS = SB + OFF_BAR;
constexpr uint32_t BAR_FULLA = BARS, BAR_EMPTYA = BARS + 40, BAR_PMID = BARS + 80, BAR_EMPTYB = BARS + 120, BAR_XDONE = BARS + 160,
                   BAR_QH = BARS + 168, BAR_QM = BARS + 96, BAR_PFULL = BARS + 184, BAR_PFREE = BARS + 200, BAR_LFULL = BARS + 216,
                   BAR_OFULL = BARS + 224, BAR_GFULL = BARS + 248, BAR_GEMPTY = BARS + 280, BAR_GOUT = BARS + 328, BAR_GRED = BARS + 368,
                   BAR_FREE = BARS + 240, NEXT_ITEM = BARS + 320;
constexpr int O_ITEM_BYTES = SQ * DH * 2;

struct alignas(64) Params {
  CUtensorMap x[2], wq[2], k[2], v[2], wo[2], out, part;
  uint64_t dsw, dso;
  __nv_bfloat16* outp;
  const __nv_bfloat16 *xp[2], *wqp[2], *kp[2], *vp[2];
};

__device__ uint4 g_o[(size_t)OSLOTS * O_ITEM_BYTES / 16];
__device__ uint4 g_part[4 * NB * SQ * DM / 8];
__device__ __align__(16) int g_pcnt[4 * N_OCTA];
__device__ int g_ready[NITEMS];
__device__ int g_done[NITEMS];
__device__ int g_ticket;
__device__ int g_go;
__device__ int g_epoch[NCTA];

#define TLE(id)
#define TLP(id)
#define TLG(id)
#define TL(id)
#define TL_FLUSH()
__device__ __forceinline__ uint32_t smem_u32(const void* p) { return (uint32_t)__cvta_generic_to_shared(p); }
__device__ __forceinline__ void wg_fence() { asm volatile("wgmma.fence.sync.aligned;" ::: "memory"); }
__device__ __forceinline__ void wg_commit() { asm volatile("wgmma.commit_group.sync.aligned;" ::: "memory"); }
template <int N> __device__ __forceinline__ void wg_wait() { asm volatile("wgmma.wait_group.sync.aligned %0;" ::"n"(N) : "memory"); }
template <int N> __device__ __forceinline__ void reg_fence(float (&d)[N]) {
#pragma unroll
  for (int i = 0; i < N; i++) asm volatile("" : "+f"(d[i])::"memory");
}
template <int N> __device__ __forceinline__ void zero_regs(float (&d)[N]) {
#pragma unroll
  for (int i = 0; i < N; i++) d[i] = 0.f;
}
__device__ __forceinline__ void proxy_fence() { asm volatile("fence.proxy.async.shared::cta;" ::: "memory"); }
__device__ __forceinline__ void mbar_init(uint32_t bar, int cnt) { asm volatile("mbarrier.init.shared::cta.b64 [%0], %1;" ::"r"(bar), "r"(cnt) : "memory"); }
__device__ __forceinline__ void mbar_arrive_if0(uint32_t bar, uint32_t sel) {
  asm volatile("{\n.reg .pred p;\nsetp.eq.u32 p, %1, 0;\n@p mbarrier.arrive.shared::cta.b64 _, [%0];\n}\n" ::"r"(bar), "r"(sel) : "memory");
}
__device__ __forceinline__ void mbar_arrive2_if0(uint32_t bar, uint32_t sel) {
  asm volatile("{\n.reg .pred p;\nsetp.eq.u32 p, %1, 0;\n@p mbarrier.arrive.shared::cta.b64 _, [%0], 2;\n}\n" ::"r"(bar), "r"(sel) : "memory");
}
__device__ __forceinline__ void mbar_expect(uint32_t bar, uint32_t bytes) {
  asm volatile("mbarrier.arrive.expect_tx.shared::cta.b64 _, [%0], %1;" ::"r"(bar), "r"(bytes) : "memory");
}
__device__ __forceinline__ void mbar_wait(int& bud, uint32_t bar, uint32_t parity) {
  asm volatile(
      "{\n.reg .pred p;\n"
      "LW:\n"
      "mbarrier.try_wait.parity.shared::cta.b64 p, [%0], %1;\n"
      "@!p bra LW;\n}\n" ::"r"(bar), "r"(parity) : "memory");
}
constexpr int WAIT_BUDGET = 1 << 22;
__device__ __forceinline__ bool elect_one() {
  uint32_t p;
  asm volatile("{\n.reg .pred p;\nelect.sync _|p, 0xffffffff;\nselp.u32 %0, 1, 0, p;\n}\n" : "=r"(p));
  return p;
}
__device__ __forceinline__ void tma2d(uint32_t dst, const CUtensorMap* m, uint32_t bar, int c0, int c1) {
  asm volatile("cp.async.bulk.tensor.2d.shared::cluster.global.mbarrier::complete_tx::bytes [%0], [%1, {%3, %4}], [%2];"
               ::"r"(dst), "l"(m), "r"(bar), "r"(c0), "r"(c1) : "memory");
}
__device__ __forceinline__ void tma3d(uint32_t dst, const CUtensorMap* m, uint32_t bar, int c0, int c1, int c2) {
  asm volatile("cp.async.bulk.tensor.3d.shared::cluster.global.mbarrier::complete_tx::bytes [%0], [%1, {%3, %4, %5}], [%2];"
               ::"r"(dst), "l"(m), "r"(bar), "r"(c0), "r"(c1), "r"(c2) : "memory");
}
__device__ __forceinline__ void tma3d_hint(uint32_t dst, const CUtensorMap* m, uint32_t bar, int c0, int c1, int c2, uint64_t pol) {
  asm volatile("cp.async.bulk.tensor.3d.shared::cluster.global.mbarrier::complete_tx::bytes.L2::cache_hint [%0], [%1, {%3, %4, %5}], [%2], %6;"
               ::"r"(dst), "l"(m), "r"(bar), "r"(c0), "r"(c1), "r"(c2), "l"(pol) : "memory");
}
__device__ __forceinline__ void tma_store2d(const CUtensorMap* m, uint32_t src, int c0, int c1) {
  asm volatile("cp.async.bulk.tensor.2d.global.shared::cta.bulk_group [%0, {%2, %3}], [%1];" ::"l"(m), "r"(src), "r"(c0), "r"(c1) : "memory");
}
__device__ __forceinline__ void bar_sync(int id, int n) { asm volatile("bar.sync %0, %1;" ::"r"(id), "r"(n) : "memory"); }
__device__ __forceinline__ void bar_arrive(int id, int n) { asm volatile("bar.arrive %0, %1;" ::"r"(id), "r"(n) : "memory"); }
__device__ __forceinline__ float ex2(float x) { float y; asm("ex2.approx.ftz.f32 %0, %1;" : "=f"(y) : "f"(x)); return y; }
__device__ __forceinline__ uint32_t pack2(float lo, float hi) { uint32_t r; asm("cvt.rn.bf16x2.f32 %0, %1, %2;" : "=r"(r) : "f"(hi), "f"(lo)); return r; }
__device__ __forceinline__ void stsm_t(uint32_t a, uint32_t r0, uint32_t r1, uint32_t r2, uint32_t r3) {
  asm volatile("stmatrix.sync.aligned.m8n8.x4.trans.shared.b16 [%0], {%1,%2,%3,%4};" ::"r"(a), "r"(r0), "r"(r1), "r"(r2), "r"(r3) : "memory");
}
__device__ __forceinline__ uint64_t evict_first_policy() {
  uint64_t pol;
  asm volatile("createpolicy.fractional.L2::evict_first.b64 %0, 1.0;" : "=l"(pol));
  return pol;
}
__device__ __forceinline__ void bulk_load_hint(uint32_t dst, const void* src, uint32_t bytes, uint32_t bar, uint64_t pol) {
  asm volatile("cp.async.bulk.shared::cluster.global.mbarrier::complete_tx::bytes.L2::cache_hint [%0], [%1], %2, [%3], %4;"
               ::"r"(dst), "l"(src), "r"(bytes), "r"(bar), "l"(pol) : "memory");
}
__device__ __forceinline__ void flag_wait(int& bud, const int* p, int target) {
  while (true) {
    int v;
    asm volatile("ld.acquire.gpu.global.s32 %0, [%1];" : "=r"(v) : "l"(p) : "memory");
    if (v - target >= 0 || --bud <= 0) break;
    __nanosleep(64);
  }
}
constexpr uint64_t DESC_SW = 0x4000004000010000ull, DESC_O = 0xC000001000800000ull;
__device__ __forceinline__ uint32_t tid_x() { uint32_t t; asm volatile("mov.u32 %0, %tid.x;" : "=r"(t)); return t; }
__device__ __forceinline__ uint32_t opaque(uint32_t x) { uint32_t y; asm volatile("mov.u32 %0, %1;" : "=r"(y) : "r"(x)); return y; }

template <int TA, int TB, uint32_t OA, uint32_t OB>
__device__ __forceinline__ void mma160(float (&d)[80], uint64_t ba, uint32_t la, uint64_t bb, uint32_t lb) {
  asm volatile(
      "{\n.reg .pred p;\n.reg .b64 da, db;\nsetp.eq.b32 p, 0, 0;\n"
      "cvt.u64.u32 da, %80;\nadd.s64 da, da, %86;\nadd.s64 da, da, %84;\ncvt.u64.u32 db, %81;\nadd.s64 db, db, %87;\nadd.s64 db, db, %85;\n"
      "wgmma.mma_async.sync.aligned.m64n160k16.f32.bf16.bf16 {"
      "%0,%1,%2,%3,%4,%5,%6,%7,%8,%9,%10,%11,%12,%13,%14,%15,%16,%17,%18,%19,%20,%21,%22,%23,%24,%25,%26,%27,%28,%29,%30,%31,%32,%33,%34,%35,%36,"
      "%37,%38,%39,%40,%41,%42,%43,%44,%45,%46,%47,%48,%49,%50,%51,%52,%53,%54,%55,%56,%57,%58,%59,%60,%61,%62,%63,%64,%65,%66,%67,%68,%69,%70,%71,"
      "%72,%73,%74,%75,%76,%77,%78,%79"
      "}, da, db, p, 1, 1, %82, %83;\n}\n"
      :
      "+f"(d[0]),"+f"(d[1]),"+f"(d[2]),"+f"(d[3]),"+f"(d[4]),"+f"(d[5]),"+f"(d[6]),"+f"(d[7]),"+f"(d[8]),"+f"(d[9]),"+f"(d[10]),"+f"(d[11]),
      "+f"(d[12]),"+f"(d[13]),"+f"(d[14]),"+f"(d[15]),"+f"(d[16]),"+f"(d[17]),"+f"(d[18]),"+f"(d[19]),"+f"(d[20]),"+f"(d[21]),"+f"(d[22]),
      "+f"(d[23]),"+f"(d[24]),"+f"(d[25]),"+f"(d[26]),"+f"(d[27]),"+f"(d[28]),"+f"(d[29]),"+f"(d[30]),"+f"(d[31]),"+f"(d[32]),"+f"(d[33]),
      "+f"(d[34]),"+f"(d[35]),"+f"(d[36]),"+f"(d[37]),"+f"(d[38]),"+f"(d[39]),"+f"(d[40]),"+f"(d[41]),"+f"(d[42]),"+f"(d[43]),"+f"(d[44]),
      "+f"(d[45]),"+f"(d[46]),"+f"(d[47]),"+f"(d[48]),"+f"(d[49]),"+f"(d[50]),"+f"(d[51]),"+f"(d[52]),"+f"(d[53]),"+f"(d[54]),"+f"(d[55]),
      "+f"(d[56]),"+f"(d[57]),"+f"(d[58]),"+f"(d[59]),"+f"(d[60]),"+f"(d[61]),"+f"(d[62]),"+f"(d[63]),"+f"(d[64]),"+f"(d[65]),"+f"(d[66]),
      "+f"(d[67]),"+f"(d[68]),"+f"(d[69]),"+f"(d[70]),"+f"(d[71]),"+f"(d[72]),"+f"(d[73]),"+f"(d[74]),"+f"(d[75]),"+f"(d[76]),"+f"(d[77]),
      "+f"(d[78]),"+f"(d[79])
      : "r"(la), "r"(lb), "n"(TA), "n"(TB), "n"(OA >> 4), "n"(OB >> 4), "l"(ba), "l"(bb));
}

template <int TA, int TB, uint32_t OA, uint32_t OB>
__device__ __forceinline__ void mma160z(float (&d)[80], uint64_t ba, uint32_t la, uint64_t bb, uint32_t lb) {
  asm volatile(
      "{\n.reg .pred p;\n.reg .b64 da, db;\nsetp.ne.b32 p, 0, 0;\n"
      "cvt.u64.u32 da, %80;\nadd.s64 da, da, %86;\nadd.s64 da, da, %84;\ncvt.u64.u32 db, %81;\nadd.s64 db, db, %87;\nadd.s64 db, db, %85;\n"
      "wgmma.mma_async.sync.aligned.m64n160k16.f32.bf16.bf16 {"
      "%0,%1,%2,%3,%4,%5,%6,%7,%8,%9,%10,%11,%12,%13,%14,%15,%16,%17,%18,%19,%20,%21,%22,%23,%24,%25,%26,%27,%28,%29,%30,%31,%32,%33,%34,%35,%36,"
      "%37,%38,%39,%40,%41,%42,%43,%44,%45,%46,%47,%48,%49,%50,%51,%52,%53,%54,%55,%56,%57,%58,%59,%60,%61,%62,%63,%64,%65,%66,%67,%68,%69,%70,%71,"
      "%72,%73,%74,%75,%76,%77,%78,%79"
      "}, da, db, p, 1, 1, %82, %83;\n}\n"
      :
      "=f"(d[0]),"=f"(d[1]),"=f"(d[2]),"=f"(d[3]),"=f"(d[4]),"=f"(d[5]),"=f"(d[6]),"=f"(d[7]),"=f"(d[8]),"=f"(d[9]),"=f"(d[10]),"=f"(d[11]),
      "=f"(d[12]),"=f"(d[13]),"=f"(d[14]),"=f"(d[15]),"=f"(d[16]),"=f"(d[17]),"=f"(d[18]),"=f"(d[19]),"=f"(d[20]),"=f"(d[21]),"=f"(d[22]),
      "=f"(d[23]),"=f"(d[24]),"=f"(d[25]),"=f"(d[26]),"=f"(d[27]),"=f"(d[28]),"=f"(d[29]),"=f"(d[30]),"=f"(d[31]),"=f"(d[32]),"=f"(d[33]),
      "=f"(d[34]),"=f"(d[35]),"=f"(d[36]),"=f"(d[37]),"=f"(d[38]),"=f"(d[39]),"=f"(d[40]),"=f"(d[41]),"=f"(d[42]),"=f"(d[43]),"=f"(d[44]),
      "=f"(d[45]),"=f"(d[46]),"=f"(d[47]),"=f"(d[48]),"=f"(d[49]),"=f"(d[50]),"=f"(d[51]),"=f"(d[52]),"=f"(d[53]),"=f"(d[54]),"=f"(d[55]),
      "=f"(d[56]),"=f"(d[57]),"=f"(d[58]),"=f"(d[59]),"=f"(d[60]),"=f"(d[61]),"=f"(d[62]),"=f"(d[63]),"=f"(d[64]),"=f"(d[65]),"=f"(d[66]),
      "=f"(d[67]),"=f"(d[68]),"=f"(d[69]),"=f"(d[70]),"=f"(d[71]),"=f"(d[72]),"=f"(d[73]),"=f"(d[74]),"=f"(d[75]),"=f"(d[76]),"=f"(d[77]),
      "=f"(d[78]),"=f"(d[79])
      : "r"(la), "r"(lb), "n"(TA), "n"(TB), "n"(OA >> 4), "n"(OB >> 4), "l"(ba), "l"(bb));
}

template <int TA, int TB, uint32_t OA, uint32_t OB>
__device__ __forceinline__ void mma80(float (&d)[40], uint64_t ba, uint32_t la, uint64_t bb, uint32_t lb) {
  asm volatile(
      "{\n.reg .pred p;\n.reg .b64 da, db;\nsetp.eq.b32 p, 0, 0;\n"
      "cvt.u64.u32 da, %40;\nadd.s64 da, da, %46;\nadd.s64 da, da, %44;\ncvt.u64.u32 db, %41;\nadd.s64 db, db, %47;\nadd.s64 db, db, %45;\n"
      "wgmma.mma_async.sync.aligned.m64n80k16.f32.bf16.bf16 {"
      "%0,%1,%2,%3,%4,%5,%6,%7,%8,%9,%10,%11,%12,%13,%14,%15,%16,%17,%18,%19,%20,%21,%22,%23,%24,%25,%26,%27,%28,%29,%30,%31,%32,%33,%34,%35,%36,"
      "%37,%38,%39"
      "}, da, db, p, 1, 1, %42, %43;\n}\n"
      :
      "+f"(d[0]),"+f"(d[1]),"+f"(d[2]),"+f"(d[3]),"+f"(d[4]),"+f"(d[5]),"+f"(d[6]),"+f"(d[7]),"+f"(d[8]),"+f"(d[9]),"+f"(d[10]),"+f"(d[11]),
      "+f"(d[12]),"+f"(d[13]),"+f"(d[14]),"+f"(d[15]),"+f"(d[16]),"+f"(d[17]),"+f"(d[18]),"+f"(d[19]),"+f"(d[20]),"+f"(d[21]),"+f"(d[22]),
      "+f"(d[23]),"+f"(d[24]),"+f"(d[25]),"+f"(d[26]),"+f"(d[27]),"+f"(d[28]),"+f"(d[29]),"+f"(d[30]),"+f"(d[31]),"+f"(d[32]),"+f"(d[33]),
      "+f"(d[34]),"+f"(d[35]),"+f"(d[36]),"+f"(d[37]),"+f"(d[38]),"+f"(d[39])
      : "r"(la), "r"(lb), "n"(TA), "n"(TB), "n"(OA >> 4), "n"(OB >> 4), "l"(ba), "l"(bb));
}

template <int TA, int TB, uint32_t OA, uint32_t OB>
__device__ __forceinline__ void mma80z(float (&d)[40], uint64_t ba, uint32_t la, uint64_t bb, uint32_t lb) {
  asm volatile(
      "{\n.reg .pred p;\n.reg .b64 da, db;\nsetp.ne.b32 p, 0, 0;\n"
      "cvt.u64.u32 da, %40;\nadd.s64 da, da, %46;\nadd.s64 da, da, %44;\ncvt.u64.u32 db, %41;\nadd.s64 db, db, %47;\nadd.s64 db, db, %45;\n"
      "wgmma.mma_async.sync.aligned.m64n80k16.f32.bf16.bf16 {"
      "%0,%1,%2,%3,%4,%5,%6,%7,%8,%9,%10,%11,%12,%13,%14,%15,%16,%17,%18,%19,%20,%21,%22,%23,%24,%25,%26,%27,%28,%29,%30,%31,%32,%33,%34,%35,%36,"
      "%37,%38,%39"
      "}, da, db, p, 1, 1, %42, %43;\n}\n"
      :
      "=f"(d[0]),"=f"(d[1]),"=f"(d[2]),"=f"(d[3]),"=f"(d[4]),"=f"(d[5]),"=f"(d[6]),"=f"(d[7]),"=f"(d[8]),"=f"(d[9]),"=f"(d[10]),"=f"(d[11]),
      "=f"(d[12]),"=f"(d[13]),"=f"(d[14]),"=f"(d[15]),"=f"(d[16]),"=f"(d[17]),"=f"(d[18]),"=f"(d[19]),"=f"(d[20]),"=f"(d[21]),"=f"(d[22]),
      "=f"(d[23]),"=f"(d[24]),"=f"(d[25]),"=f"(d[26]),"=f"(d[27]),"=f"(d[28]),"=f"(d[29]),"=f"(d[30]),"=f"(d[31]),"=f"(d[32]),"=f"(d[33]),
      "=f"(d[34]),"=f"(d[35]),"=f"(d[36]),"=f"(d[37]),"=f"(d[38]),"=f"(d[39])
      : "r"(la), "r"(lb), "n"(TA), "n"(TB), "n"(OA >> 4), "n"(OB >> 4), "l"(ba), "l"(bb));
}

template <int TA, int TB, uint32_t OA, uint32_t OB>
__device__ __forceinline__ void mma160r(float (&d)[80], uint64_t ba, uint32_t la, uint64_t bb, uint32_t lb, int sc) {
  asm volatile(
      "{\n.reg .pred p;\n.reg .b64 da, db;\nsetp.ne.b32 p, %88, 0;\n"
      "cvt.u64.u32 da, %80;\nadd.s64 da, da, %86;\nadd.s64 da, da, %84;\ncvt.u64.u32 db, %81;\nadd.s64 db, db, %87;\nadd.s64 db, db, %85;\n"
      "wgmma.mma_async.sync.aligned.m64n160k16.f32.bf16.bf16 {"
      "%0,%1,%2,%3,%4,%5,%6,%7,%8,%9,%10,%11,%12,%13,%14,%15,%16,%17,%18,%19,%20,%21,%22,%23,%24,%25,%26,%27,%28,%29,%30,%31,%32,%33,%34,%35,%36,"
      "%37,%38,%39,%40,%41,%42,%43,%44,%45,%46,%47,%48,%49,%50,%51,%52,%53,%54,%55,%56,%57,%58,%59,%60,%61,%62,%63,%64,%65,%66,%67,%68,%69,%70,%71,"
      "%72,%73,%74,%75,%76,%77,%78,%79"
      "}, da, db, p, 1, 1, %82, %83;\n}\n"
      :
      "+f"(d[0]),"+f"(d[1]),"+f"(d[2]),"+f"(d[3]),"+f"(d[4]),"+f"(d[5]),"+f"(d[6]),"+f"(d[7]),"+f"(d[8]),"+f"(d[9]),"+f"(d[10]),"+f"(d[11]),
      "+f"(d[12]),"+f"(d[13]),"+f"(d[14]),"+f"(d[15]),"+f"(d[16]),"+f"(d[17]),"+f"(d[18]),"+f"(d[19]),"+f"(d[20]),"+f"(d[21]),"+f"(d[22]),
      "+f"(d[23]),"+f"(d[24]),"+f"(d[25]),"+f"(d[26]),"+f"(d[27]),"+f"(d[28]),"+f"(d[29]),"+f"(d[30]),"+f"(d[31]),"+f"(d[32]),"+f"(d[33]),
      "+f"(d[34]),"+f"(d[35]),"+f"(d[36]),"+f"(d[37]),"+f"(d[38]),"+f"(d[39]),"+f"(d[40]),"+f"(d[41]),"+f"(d[42]),"+f"(d[43]),"+f"(d[44]),
      "+f"(d[45]),"+f"(d[46]),"+f"(d[47]),"+f"(d[48]),"+f"(d[49]),"+f"(d[50]),"+f"(d[51]),"+f"(d[52]),"+f"(d[53]),"+f"(d[54]),"+f"(d[55]),
      "+f"(d[56]),"+f"(d[57]),"+f"(d[58]),"+f"(d[59]),"+f"(d[60]),"+f"(d[61]),"+f"(d[62]),"+f"(d[63]),"+f"(d[64]),"+f"(d[65]),"+f"(d[66]),
      "+f"(d[67]),"+f"(d[68]),"+f"(d[69]),"+f"(d[70]),"+f"(d[71]),"+f"(d[72]),"+f"(d[73]),"+f"(d[74]),"+f"(d[75]),"+f"(d[76]),"+f"(d[77]),
      "+f"(d[78]),"+f"(d[79])
      : "r"(la), "r"(lb), "n"(TA), "n"(TB), "n"(OA >> 4), "n"(OB >> 4), "l"(ba), "l"(bb), "r"(sc));
}

template <int TA, int TB, uint32_t OA, uint32_t OB>
__device__ __forceinline__ void mma80r(float (&d)[40], uint64_t ba, uint32_t la, uint64_t bb, uint32_t lb, int sc) {
  asm volatile(
      "{\n.reg .pred p;\n.reg .b64 da, db;\nsetp.ne.b32 p, %48, 0;\n"
      "cvt.u64.u32 da, %40;\nadd.s64 da, da, %46;\nadd.s64 da, da, %44;\ncvt.u64.u32 db, %41;\nadd.s64 db, db, %47;\nadd.s64 db, db, %45;\n"
      "wgmma.mma_async.sync.aligned.m64n80k16.f32.bf16.bf16 {"
      "%0,%1,%2,%3,%4,%5,%6,%7,%8,%9,%10,%11,%12,%13,%14,%15,%16,%17,%18,%19,%20,%21,%22,%23,%24,%25,%26,%27,%28,%29,%30,%31,%32,%33,%34,%35,%36,"
      "%37,%38,%39"
      "}, da, db, p, 1, 1, %42, %43;\n}\n"
      :
      "+f"(d[0]),"+f"(d[1]),"+f"(d[2]),"+f"(d[3]),"+f"(d[4]),"+f"(d[5]),"+f"(d[6]),"+f"(d[7]),"+f"(d[8]),"+f"(d[9]),"+f"(d[10]),"+f"(d[11]),
      "+f"(d[12]),"+f"(d[13]),"+f"(d[14]),"+f"(d[15]),"+f"(d[16]),"+f"(d[17]),"+f"(d[18]),"+f"(d[19]),"+f"(d[20]),"+f"(d[21]),"+f"(d[22]),
      "+f"(d[23]),"+f"(d[24]),"+f"(d[25]),"+f"(d[26]),"+f"(d[27]),"+f"(d[28]),"+f"(d[29]),"+f"(d[30]),"+f"(d[31]),"+f"(d[32]),"+f"(d[33]),
      "+f"(d[34]),"+f"(d[35]),"+f"(d[36]),"+f"(d[37]),"+f"(d[38]),"+f"(d[39])
      : "r"(la), "r"(lb), "n"(TA), "n"(TB), "n"(OA >> 4), "n"(OB >> 4), "l"(ba), "l"(bb), "r"(sc));
}

struct Ring { uint32_t s0, ph0; };
__device__ __forceinline__ void ring_pos(const Ring& r, int i, uint32_t& slot, uint32_t& ph) {
  uint32_t s = opaque(r.s0) + (i % NSLOT);
  uint32_t wrap = s >= NSLOT;
  slot = s - (wrap ? NSLOT : 0);
  ph = r.ph0 ^ ((i / NSLOT) & 1) ^ wrap;
}
__device__ __forceinline__ void ring_advance(Ring& r, int n) {
  uint32_t s, p;
  ring_pos(r, n, s, p);
  r.s0 = s; r.ph0 = p;
}
__host__ __device__ constexpr int idxK(int j) { return j == 0 ? 10 : 9 + 2 * j; }
__host__ __device__ constexpr int idxV(int j) { return j == 7 ? 25 : 12 + 2 * j; }
__host__ __device__ constexpr int xs(int c) { return c % NSLOT; }

__device__ __forceinline__ int start_delay(int cta) {
  return max(0, ((cta - N_OCTA) | (STAG_G - 1)) - STAG_A0) * STAG_SLOPE;
}
__device__ __forceinline__ char* o_slot(int item) {
  return (char*)g_o + (size_t)(item < OFRESH ? item % ORING : item - OFRESH + ORING) * O_ITEM_BYTES;
}
__device__ __forceinline__ int next_item(uint32_t a = NEXT_ITEM) {
  int v;
  asm volatile("ld.shared.s32 %0, [%1];" : "=r"(v) : "r"(a) : "memory");
  return __shfl_sync(0xffffffffu, v, 0);
}

template <int W, bool ACC>
__device__ __forceinline__ void mma_main(uint64_t ds, float (&d)[80], uint32_t aaddr, uint32_t baddr) {
  const uint32_t la = aaddr >> 4, lb = baddr >> 4;
  if (ACC) mma160<1, 0, W * 16384, 0>(d, ds, la, ds, lb); else mma160z<1, 0, W * 16384, 0>(d, ds, la, ds, lb);
  mma160<1, 0, W * 16384 + 1 * 2048, 1 * 32>(d, ds, la, ds, lb);
  mma160<1, 0, W * 16384 + 2 * 2048, 2 * 32>(d, ds, la, ds, lb);
  mma160<1, 0, W * 16384 + 3 * 2048, 3 * 32>(d, ds, la, ds, lb);
}
template <int W, bool ACC>
__device__ __forceinline__ void mma_mid(uint64_t ds, float (&d)[40], uint32_t aaddr, uint32_t baddr) {
  const uint32_t la = aaddr >> 4, lb = baddr >> 4;
  if (ACC) mma80<1, 0, 8192, W * 10240>(d, ds, la, ds, lb); else mma80z<1, 0, 8192, W * 10240>(d, ds, la, ds, lb);
  mma80<1, 0, 8192 + 1 * 2048, W * 10240 + 1 * 32>(d, ds, la, ds, lb);
  mma80<1, 0, 8192 + 2 * 2048, W * 10240 + 2 * 32>(d, ds, la, ds, lb);
  mma80<1, 0, 8192 + 3 * 2048, W * 10240 + 3 * 32>(d, ds, la, ds, lb);
}
template <int W, bool ACC>
__device__ __forceinline__ void mma_both(uint64_t ds, float (&dm)[80], float (&dh)[40], uint32_t aaddr, uint32_t baddr) {
  mma_mid<W, ACC>(ds, dh, aaddr, baddr);
  mma_main<W, ACC>(ds, dm, aaddr, baddr);
}
template <int KB, bool ACC>
__device__ __forceinline__ void s_mma(uint64_t ds, float (&sacc)[80], uint32_t kaddr) {
  const uint32_t la = kaddr >> 4, lb = (SB + OFF_B) >> 4;
  if (ACC) mma160<0, 0, KB * 8192, KB * B_SLOT>(sacc, ds, la, ds, lb); else mma160z<0, 0, KB * 8192, KB * B_SLOT>(sacc, ds, la, ds, lb);
  mma160<0, 0, KB * 8192 + 32, KB * B_SLOT + 32>(sacc, ds, la, ds, lb);
  mma160<0, 0, KB * 8192 + 64, KB * B_SLOT + 64>(sacc, ds, la, ds, lb);
  mma160<0, 0, KB * 8192 + 96, KB * B_SLOT + 96>(sacc, ds, la, ds, lb);
}
template <int N>
__device__ __forceinline__ void store_scaled(uint32_t addr, const float (&d)[N], float sc) {
#pragma unroll
  for (int J = 0; J < N / 8; J++)
    stsm_t(addr + J * 2048, pack2(d[8 * J] * sc, d[8 * J + 1] * sc), pack2(d[8 * J + 2] * sc, d[8 * J + 3] * sc),
           pack2(d[8 * J + 4] * sc, d[8 * J + 5] * sc), pack2(d[8 * J + 6] * sc, d[8 * J + 7] * sc));
}
__device__ __forceinline__ float4 lds_f4(uint32_t a) {
  float4 v;
  asm volatile("ld.shared.v4.f32 {%0,%1,%2,%3}, [%4];" : "=f"(v.x), "=f"(v.y), "=f"(v.z), "=f"(v.w) : "r"(a) : "memory");
  return v;
}
__device__ __forceinline__ void norm_pack(uint32_t* p, const float* d, const float4& i) {
  p[0] = pack2(d[0] * i.x, d[1] * i.y); p[1] = pack2(d[4] * i.z, d[5] * i.w);
  p[2] = pack2(d[2] * i.x, d[3] * i.y); p[3] = pack2(d[6] * i.z, d[7] * i.w);
  asm volatile("" : "+r"(p[0]), "+r"(p[1]), "+r"(p[2]), "+r"(p[3])::"memory");
}
template <int W>
__device__ __forceinline__ void pack_first(uint32_t (&pk)[60], const float (&om)[80], const float (&oh)[40], uint32_t laddr) {
  float4 n0 = lds_f4(laddr + W * 80), n1 = lds_f4(laddr + W * 80 + 16);
#pragma unroll
  for (int J = 0; J < 5; J++) {
    const float4 i = n0;
    n0 = n1;
    if (J + 2 < 5) n1 = lds_f4(laddr + W * 80 + (J + 2) * 16);
    norm_pack(&pk[20 + 4 * J], &om[8 * (5 * W + J)], i);
    norm_pack(&pk[4 * J], &oh[8 * J], i);
  }
}
template <int W, int J0, int J1>
__device__ __forceinline__ void pack_second(uint32_t (&pk)[60], const float (&om)[80], uint32_t laddr) {
  float4 n[J1 - J0];
#pragma unroll
  for (int J = J0; J < J1; J++) n[J - J0] = lds_f4(laddr + (1 - W) * 80 + J * 16);
#pragma unroll
  for (int J = J0; J < J1; J++) norm_pack(&pk[40 + 4 * J], &om[8 * (5 * (1 - W) + J)], n[J - J0]);
}
__device__ __forceinline__ char* o_ptr(int item) {
  const uint32_t t = tid_x();
  return o_slot(item) + ((t & 96) * 16 + (t & 28) * 8 + ((((t >> 1) ^ (t >> 4)) & 1) << 4) + (t & 1) * 8);
}
template <int W, int G0, int G1>
__device__ __forceinline__ void store_groups(char* op, const uint32_t (&pk)[60], uint32_t on) {
#pragma unroll
  for (int G = G0; G < G1; G++) {
    const int off = (G < 5 ? 1 : 2 * W) * B_SLOT + (5 * (G < 10 ? W : 1 - W) + G % 5) * 2048;
    asm volatile("{\n.reg .pred p;\nsetp.ne.u32 p, %5, 0;\n@p st.global.v2.b32 [%0], {%1, %2};\n@p st.global.v2.b32 [%0+256], {%3, %4};\n}\n"
                 ::"l"(op + off), "r"(pk[4 * G]), "r"(pk[4 * G + 1]), "r"(pk[4 * G + 2]), "r"(pk[4 * G + 3]), "r"(on) : "memory");
  }
}
__device__ __forceinline__ void publish_generic(uint32_t bar, int lane) {
  __syncwarp();
  mbar_arrive_if0(bar, lane);
}
__device__ __forceinline__ void publish(uint32_t bar, int lane) {
  proxy_fence();
  __syncwarp();
  mbar_arrive_if0(bar, lane);
}

#define A_ADDR(s) (SB + OFF_A + (s) * A_SLOT)
#define B_ADDR(s) (SB + OFF_B + (s) * B_SLOT)
#define WAIT_CHUNK(c, ro, sA)                \
  uint32_t sA;                               \
  {                                          \
    uint32_t pA_;                            \
    ring_pos(ring, (ro) + (c), sA, pA_);     \
    mbar_wait(bud, BAR_FULLA + sA * 8, pA_); \
  }
#define RELEASE_CHUNK(c, sA)                                  \
  mbar_arrive_if0(BAR_EMPTYA + (sA) * 8, tid);                \
  if ((c) < NSLOT) mbar_arrive_if0(BAR_EMPTYB + xs(c) * 8, tid);

template <int W>
__device__ __forceinline__ int attn_consumer(const uint64_t ds, int item) {
  int bud = WAIT_BUDGET;
  const int tid = threadIdx.x & 127, lane = tid & 31, warp = tid >> 5;
  const uint32_t st_off = ((lane & 7) + 8 * (lane >> 4)) * 128 + (((2 * warp + ((lane >> 3) & 1)) ^ (lane & 7)) << 4);
  const uint32_t laddr = SB + OFF_L + (lane & 3) * 160;
  float om[80], oh[40], sacc[80];
  uint32_t pk[60];
#pragma unroll
  for (int i = 0; i < 40; i++) pk[i] = 0;
  zero_regs(om);
  Ring ring{0u, 0u};
  uint32_t par = 0;
  int prev = 0;
  const float qscale = 0.07216878364870322f * 1.4426950408889634f;
  constexpr uint32_t pown = B_ADDR(3 + W), poth = B_ADDR(4 - W);
  TL(0); TLG(62);
  {
    WAIT_CHUNK(0, 0, s0)
    wg_fence();
    mma_both<W, false>(ds, sacc, oh, A_ADDR(s0), B_ADDR(xs(0)));
    wg_commit();
    WAIT_CHUNK(1, 0, s1)
    wg_fence();
    mma_both<W, true>(ds, sacc, oh, A_ADDR(s1), B_ADDR(xs(1)));
    wg_commit();
    wg_wait<1>();
    RELEASE_CHUNK(0, s0)
  }
#pragma unroll 1
  for (int it = 0;; it++) {
    char* op = o_ptr(prev);
#pragma unroll
    for (int c = 2; c < 8 - W; c++) {
      WAIT_CHUNK(c, 0, sA)
      TL(40 + c);
      wg_fence();
      mma_both<W, true>(ds, sacc, oh, A_ADDR(sA), B_ADDR(xs(c)));
      wg_commit();
      wg_wait<1>();
      uint32_t sP, pP;
      ring_pos(ring, c - 1, sP, pP);
      RELEASE_CHUNK(c - 1, sP)
      constexpr int NG = 3;
      if (c == 2) { pack_second<W, 0, 1>(pk, om, laddr); store_groups<W, 0 * NG, 1 * NG>(op, pk, it); }
      if (c == 3) { pack_second<W, 1, 2>(pk, om, laddr); store_groups<W, 1 * NG, 2 * NG>(op, pk, it); }
      if (c == 4) { pack_second<W, 2, 3>(pk, om, laddr); store_groups<W, 2 * NG, 3 * NG>(op, pk, it); }
      if (c == 5) { pack_second<W, 3, 4>(pk, om, laddr); store_groups<W, 3 * NG, 4 * NG>(op, pk, it); }
      if (c == 6) {
        pack_second<W, 4, 5>(pk, om, laddr);
        if (W == 1) {
          wg_wait<0>();
          RELEASE_CHUNK(6, sA)
          mbar_arrive_if0(BAR_XDONE, tid);
        }
        store_groups<W, 4 * NG, 15>(op, pk, it);
        __syncwarp();
        mbar_arrive_if0(BAR_OFULL, lane | (it == 0));
      }
    }
    uint32_t sK0, pK0, s7, p7;
    ring_pos(ring, idxK(W), sK0, pK0);
    ring_pos(ring, 7, s7, p7);
    if (W == 1) mbar_wait(bud, BAR_FULLA + s7 * 8, p7);
    WAIT_CHUNK(8, 0, s8)
    if (W == 0) {
      wg_fence();
      mma_both<W, true>(ds, sacc, oh, A_ADDR(s8), B_ADDR(xs(8)));
      wg_commit();
      wg_wait<1>();
      RELEASE_CHUNK(7, s7)
    }
    WAIT_CHUNK(9, 0, s9)
    TL(48);
    if (W == 0) {
      wg_fence();
      mma_mid<W, true>(ds, oh, A_ADDR(s9), B_ADDR(xs(9)));
      wg_commit();
      mma_main<W, true>(ds, sacc, A_ADDR(s9), B_ADDR(xs(9)));
      wg_commit();
      bar_arrive(5, 256);
      TL(49);
      wg_wait<1>();
      reg_fence(oh);
      mbar_wait(bud, BAR_XDONE, par);
      store_scaled(B_ADDR(1) + st_off, oh, qscale);
    } else {
      bar_sync(5, 256);
      wg_fence();
      mma_mid<W, true>(ds, oh, A_ADDR(s7), B_ADDR(xs(7)));
      mma_mid<W, true>(ds, oh, A_ADDR(s8), B_ADDR(xs(8)));
      mma_mid<W, true>(ds, oh, A_ADDR(s9), B_ADDR(xs(9)));
      wg_commit();
      mma_main<W, true>(ds, sacc, A_ADDR(s7), B_ADDR(xs(7)));
      wg_commit();
      mma_main<W, true>(ds, sacc, A_ADDR(s8), B_ADDR(xs(8)));
      wg_commit();
      wg_wait<2>();
      reg_fence(oh);
      store_scaled(B_ADDR(1) + 10240 + st_off, oh, qscale);
      wg_fence();
      mma_main<W, true>(ds, sacc, A_ADDR(s9), B_ADDR(xs(9)));
      wg_commit();
      bar_arrive(8, 256);
      TL(49);
      wg_wait<2>();
      RELEASE_CHUNK(7, s7)
      publish(BAR_QH, lane);
    }
    wg_wait<0>();
    reg_fence(sacc);
    TL(1);
    RELEASE_CHUNK(8, s8)
    RELEASE_CHUNK(9, s9)
    store_scaled(B_ADDR(2 * W) + st_off, sacc, qscale);
    if (W == 1) publish(BAR_QM, lane); else proxy_fence();
    TL(2);
    uint32_t sK = sK0, sV1 = 0;
    if (W == 0) {
      zero_regs(om); zero_regs(oh);
      reg_fence(om); reg_fence(oh);
      mbar_wait(bud, BAR_FULLA + sK0 * 8, pK0);
      bar_sync(8, 256);
      wg_fence();
      s_mma<0, false>(ds, sacc, A_ADDR(sK));
      mbar_wait(bud, BAR_QH, par);
      TL(3);
      wg_fence();
      s_mma<1, true>(ds, sacc, A_ADDR(sK));
      mbar_wait(bud, BAR_QM, par);
      TL(5);
      wg_fence();
      s_mma<2, true>(ds, sacc, A_ADDR(sK));
      wg_commit();
      wg_commit();
      bar_arrive(2, 256);
    } else {
      uint32_t pV1;
      ring_pos(ring, idxV(0), sV1, pV1);
      mbar_wait(bud, BAR_FULLA + sK * 8, pK0);
      bar_sync(2, 256);
      wg_fence();
      s_mma<0, false>(ds, sacc, A_ADDR(sK));
      s_mma<1, true>(ds, sacc, A_ADDR(sK));
      s_mma<2, true>(ds, sacc, A_ADDR(sK));
      wg_commit();
      TL(6);
      mbar_wait(bud, BAR_FULLA + sV1 * 8, pV1);
      mbar_wait(bud, BAR_PFULL, 0);
      TL(7);
      wg_fence();
      mma_both<W, false>(ds, om, oh, A_ADDR(sV1), poth);
      wg_commit();
      bar_arrive(1, 256);
    }
    Ring rv;
    ring_pos(ring, idxV(W), rv.s0, rv.ph0);
#pragma unroll 1
    for (int jj = 0;; jj++) {
      wg_wait<1>();
      reg_fence(sacc);
      TL(8 + jj * 7);
      mbar_arrive2_if0(BAR_EMPTYA + sK * 8, tid);
      mbar_arrive_if0(BAR_EMPTYB + tid * 8, (tid >= 3) | (jj != 3));
#pragma unroll
      for (int J = 0; J < 10; J++) {
        stsm_t(pown + st_off + J * 2048, pack2(ex2(sacc[8 * J]), ex2(sacc[8 * J + 1])), pack2(ex2(sacc[8 * J + 2]), ex2(sacc[8 * J + 3])),
               pack2(ex2(sacc[8 * J + 4]), ex2(sacc[8 * J + 5])), pack2(ex2(sacc[8 * J + 6]), ex2(sacc[8 * J + 7])));
        if (W == 1 && (J == 2 || J == 5)) publish_generic(BAR_PMID + (J / 3) * 8, lane | (jj != 3));
        if (J == 4) {
          wg_wait<0>();
          mbar_arrive_if0(BAR_EMPTYA + sV1 * 8, tid | (W == 0 && jj == 0));
        }
      }
      publish(BAR_PFULL + W * 8, lane);
      TL(10 + jj * 7);
      if (jj == 3) break;
      uint32_t pK, pV1;
      ring_pos(rv, 1, sK, pK);
      ring_pos(rv, 2, sV1, pV1);
      mbar_wait(bud, BAR_FULLA + rv.s0 * 8, rv.ph0);
      bar_sync(1 + W, 256);
      wg_fence();
      mma_both<W, true>(ds, om, oh, A_ADDR(rv.s0), pown);
      wg_commit();
      mbar_wait(bud, BAR_FULLA + sK * 8, pK);
      TL(11 + jj * 7);
      wg_fence();
      s_mma<0, false>(ds, sacc, A_ADDR(sK));
      s_mma<1, true>(ds, sacc, A_ADDR(sK));
      wg_commit();
      wg_wait<1>();
      mbar_arrive_if0(BAR_EMPTYA + rv.s0 * 8, tid);
      wg_fence();
      s_mma<2, true>(ds, sacc, A_ADDR(sK));
      wg_commit();
      TL(13 + jj * 7);
      mbar_wait(bud, BAR_FULLA + sV1 * 8, pV1);
      mbar_wait(bud, BAR_PFREE + W * 8, jj & 1);
      mbar_wait(bud, BAR_PFULL + (1 - W) * 8, (jj + W) & 1);
      TL(14 + jj * 7);
      wg_fence();
      mma_both<W, true>(ds, om, oh, A_ADDR(sV1), poth);
      wg_commit();
      bar_arrive(2 - W, 256);
      ring_advance(rv, 4);
    }
    uint32_t sV7, pV7;
    ring_pos(ring, idxV(7), sV7, pV7);
    prev = item;
    if (W == 1 && !DEBUG_TIMEOUT) item = next_item();
    if (W == 0) {
      uint32_t sV6, pV6;
      ring_pos(ring, idxV(6), sV6, pV6);
      mbar_wait(bud, BAR_FULLA + sV6 * 8, pV6);
      bar_sync(1, 256);
      wg_fence();
      mma_both<0, true>(ds, om, oh, A_ADDR(sV6), pown);
      wg_commit();
      mbar_wait(bud, BAR_FULLA + sV7 * 8, pV7);
      wg_wait<0>();
      mbar_arrive_if0(BAR_EMPTYA + sV6 * 8, tid);
      mbar_wait(bud, BAR_PFULL + 8, 1);
      wg_fence();
      mma_both<0, true>(ds, om, oh, A_ADDR(sV7), poth);
      wg_commit();
      bar_arrive(6, 256);
    } else {
      mbar_wait(bud, BAR_FULLA + sV7 * 8, pV7);
      bar_sync(6, 256);
    }
    TL(32);
    if (DEBUG_TIMEOUT) item = next_item(NEXT_ITEM + 4);
    else if (W == 0) item = next_item();
    if (item >= NITEMS) {
      if (W == 1) {
        wg_fence();
        mma_both<1, true>(ds, om, oh, A_ADDR(sV7), pown);
        wg_commit();
      }
      wg_wait<0>();
      reg_fence(om); reg_fence(oh);
      TL(33);
      mbar_wait(bud, BAR_LFULL, par);
      mbar_arrive_if0(BAR_FREE, tid);
      TL(34);
      pack_first<W>(pk, om, oh, laddr);
      op = o_ptr(prev);
      store_groups<W, 0, 10>(op, pk, 1);
      pack_second<W, 0, 5>(pk, om, laddr);
      store_groups<W, 10, 15>(op, pk, 1);
      publish_generic(BAR_OFULL, lane);
      TL(35); TLG(63);
      TL_FLUSH();
      return item;
    }
    {
      if (W == 1) {
        wg_fence();
        mma_both<1, true>(ds, om, oh, A_ADDR(sV7), pown);
        wg_commit();
      }
      WAIT_CHUNK(0, 26, s0)
      WAIT_CHUNK(1, 26, s1)
      if (W == 0) {
        wg_wait<0>();
        reg_fence(om); reg_fence(oh);
        TL(33);
        wg_fence();
        mma_main<W, false>(ds, sacc, A_ADDR(s0), B_ADDR(xs(0)));
        wg_commit();
      } else {
        wg_fence();
        mma_main<W, false>(ds, sacc, A_ADDR(s0), B_ADDR(xs(0)));
        mma_main<W, true>(ds, sacc, A_ADDR(s1), B_ADDR(xs(1)));
        wg_commit();
        wg_wait<1>();
        reg_fence(om); reg_fence(oh);
        TL(33);
      }
      mbar_arrive_if0(BAR_EMPTYA + sV7 * 8, tid);
      mbar_wait(bud, BAR_LFULL, par);
      mbar_arrive_if0(BAR_EMPTYB + 24 + tid * 8, tid >= 2);
      TL(34);
      pack_first<W>(pk, om, oh, laddr);
      TL(36);
      wg_fence();
      mma_mid<W, false>(ds, oh, A_ADDR(s0), B_ADDR(xs(0)));
      wg_commit();
      mma_mid<W, true>(ds, oh, A_ADDR(s1), B_ADDR(xs(1)));
      if (W == 0) mma_main<W, true>(ds, sacc, A_ADDR(s1), B_ADDR(xs(1)));
      wg_commit();
      TL(37);
      wg_wait<1>();
      RELEASE_CHUNK(0, s0)
      TL(35); TLG(63);
    }
    TL_FLUSH();
    TL(0); TLG(62);
    ring_advance(ring, 26);
    par ^= 1;
  }
}

__device__ __forceinline__ uint4 lds128(uint32_t a) {
  uint4 v;
  asm volatile("ld.shared.v4.b32 {%0,%1,%2,%3}, [%4];" : "=r"(v.x), "=r"(v.y), "=r"(v.z), "=r"(v.w) : "r"(a) : "memory");
  return v;
}
__device__ __forceinline__ void acc2(float& s, float& t, uint32_t w) {
  s += __uint_as_float(w << 16);
  t += __uint_as_float(w & 0xffff0000u);
}
__device__ __forceinline__ uint32_t badd2(uint32_t a, uint32_t b) { uint32_t r; asm("add.rn.bf16x2 %0, %1, %2;" : "=r"(r) : "r"(a), "r"(b)); return r; }
__device__ __forceinline__ void sum_unit(float& acc, uint32_t pb) {
  const uint4 v0 = lds128(pb), v1 = lds128(pb ^ 32), v2 = lds128(pb ^ 64), v3 = lds128(pb ^ 96);
  const uint32_t w0 = badd2(badd2(v0.x, v0.y), badd2(v0.z, v0.w));
  float s = acc + __uint_as_float(w0 << 16), t = __uint_as_float(w0 & 0xffff0000u);
  acc2(s, t, badd2(badd2(v1.x, v1.y), badd2(v1.z, v1.w)));
  acc2(s, t, badd2(badd2(v2.x, v2.y), badd2(v2.z, v2.w)));
  acc2(s, t, badd2(badd2(v3.x, v3.y), badd2(v3.z, v3.w)));
  acc = s + t;
}
__device__ __forceinline__ float bf_lo(uint32_t w) { return __uint_as_float(w << 16); }
__device__ __forceinline__ float bf_hi(uint32_t w) { return __uint_as_float(w & 0xffff0000u); }
__device__ __forceinline__ float bf_rn(float x) { return __bfloat162float(__float2bfloat16(x)); }
__device__ __forceinline__ void slow_item(const Params& p, int item, int hw) {
  const int blk = item >> 9, h = (item >> 4) & 31, b = item & 15;
#pragma unroll 1
  for (int n = hw; n < SQ; n += 3) {
    float q[6] = {0.f, 0.f, 0.f, 0.f, 0.f, 0.f};
    {
      const uint32_t* xr = (const uint32_t*)(p.xp[blk] + (size_t)(b * SQ + n) * DM);
      const uint32_t* wq = (const uint32_t*)(p.wqp[blk] + h * DH) + (tid_x() & 31);
#pragma unroll 2
      for (int k = 0; k < DM / 2; k++) {
        const uint32_t xv = xr[k];
#pragma unroll
        for (int i = 0; i < 3; i++) {
          const uint32_t w0 = wq[i * 32], w1 = wq[NH * DH / 2 + i * 32];
          q[2 * i] = fmaf(bf_lo(xv), bf_lo(w0), fmaf(bf_hi(xv), bf_lo(w1), q[2 * i]));
          q[2 * i + 1] = fmaf(bf_lo(xv), bf_hi(w0), fmaf(bf_hi(xv), bf_hi(w1), q[2 * i + 1]));
        }
        wq += NH * DH;
      }
    }
    const uint32_t q0 = pack2(q[0], q[1]), q1 = pack2(q[2], q[3]), q2 = pack2(q[4], q[5]);
    float o[6] = {0.f, 0.f, 0.f, 0.f, 0.f, 0.f}, m = -INFINITY, l = 0.f;
    const uint32_t* kg = (const uint32_t*)(p.kp[blk] + (size_t)(b * NH + h) * SK * DH) + (tid_x() & 31);
    const uint32_t* vg = (const uint32_t*)(p.vp[blk] + (size_t)(b * NH + h) * SK * DH) + (tid_x() & 31);
#pragma unroll 1
    for (int k = 0; k < SK; k++) {
      const uint32_t k0 = kg[0], k1 = kg[32], k2 = kg[64], v0 = vg[0], v1 = vg[32], v2 = vg[64];
      kg += DH / 2; vg += DH / 2;
      float sc = fmaf(bf_lo(q0), bf_lo(k0), bf_hi(q0) * bf_hi(k0));
      sc = fmaf(bf_lo(q1), bf_lo(k1), fmaf(bf_hi(q1), bf_hi(k1), sc));
      sc = fmaf(bf_lo(q2), bf_lo(k2), fmaf(bf_hi(q2), bf_hi(k2), sc));
#pragma unroll
      for (int d = 16; d; d >>= 1) sc += __shfl_xor_sync(0xffffffffu, sc, d);
      sc = bf_rn(bf_rn(sc) * 0.07216878364870322f);
      const float mn = fmaxf(m, sc), a = ex2((m - mn) * 1.4426950408889634f), pr = ex2((sc - mn) * 1.4426950408889634f);
      m = mn;
      l = fmaf(l, a, pr);
      o[0] = fmaf(o[0], a, pr * bf_lo(v0)); o[1] = fmaf(o[1], a, pr * bf_hi(v0));
      o[2] = fmaf(o[2], a, pr * bf_lo(v1)); o[3] = fmaf(o[3], a, pr * bf_hi(v1));
      o[4] = fmaf(o[4], a, pr * bf_lo(v2)); o[5] = fmaf(o[5], a, pr * bf_hi(v2));
    }
    float inv;
    asm("rcp.approx.ftz.f32 %0, %1;" : "=f"(inv) : "f"(l));
    const int lane = tid_x() & 31;
    const int r = n & 15, c = 4 * ((r & 7) >> 1) + 2 * (r >> 3) + (r & 1);
    char* on = o_slot(item) + (lane >> 2) * 256 + (lane & 3) * 64 + (n >> 4) * 2048 +
               (((c >> 3) ^ ((lane >> 1) & 1)) << 4) + (c & 7) * 2;
#pragma unroll
    for (int i = 0; i < 3; i++) {
      *(__nv_bfloat16*)(on + i * B_SLOT) = __float2bfloat16(o[2 * i] * inv);
      *(__nv_bfloat16*)(on + i * B_SLOT + 32) = __float2bfloat16(o[2 * i + 1] * inv);
    }
  }
}
__device__ __forceinline__ void attn_helper(const Params& p, int hw, int item, int epoch) {
  int bud = WAIT_BUDGET;
  if (hw == 2) {
    if (item == 0 && elect_one()) {
      *(volatile int*)&g_ticket = 0;
      asm volatile("red.release.gpu.global.add.s32 [%0], 1;" ::"l"(&g_go) : "memory");
    }
    __syncwarp();
    flag_wait(bud, &g_go, epoch + 1);
  }
  if (item < PF_N && hw < 2) {
    const char* g = (const char*)(hw ? p.vp[0] : p.kp[0]) + (size_t)(((item & 15) * NH + (item >> 4)) * SK) * DH * 2;
    const long long t0 = clock64();
#pragma unroll 1
    for (int i = 0; i < 32; i++) {
      while (clock64() - t0 < PF_WAIT + i * PF_GAP) __nanosleep(50);
      for (int k = 0; k < 6; k++) asm volatile("prefetch.global.L2 [%0];" ::"l"(g + i * 6144 + k * 1024 + (tid_x() & 31) * 32));
      __syncwarp();
    }
  }
#pragma unroll 1
  for (int it = 0; item < NITEMS; it++) {
    const uint32_t par = it & 1;
    int lane = tid_x() & 31;
    const int r = lane >> 1;
    const uint32_t a0 = B_ADDR(3) + (16 * hw + r) * 128 + (lane & 1) * 16 + ((r & 3) << 5);
    float acc[4] = {0.f, 0.f, 0.f, 0.f};
#pragma unroll 1
    for (int j = 0; j < 8; j++) {
      const uint32_t pb = a0 + (j & 1) * B_SLOT, bfull = BAR_PFULL + (j & 1) * 8, pfull = (j >> 1) & 1;
      mbar_wait(bud, j == 7 ? BAR_PMID : bfull, j == 7 ? par : pfull);
      sum_unit(acc[0], pb);
      if (j == 7) mbar_wait(bud, BAR_PMID + 8, par);
      sum_unit(acc[1], pb + 6144);
      if (j == 7) mbar_wait(bud, bfull, pfull);
      sum_unit(acc[2], pb + 2 * 6144);
      if (hw == 0) sum_unit(acc[3], pb + 3 * 6144);
      __syncwarp();
      mbar_arrive_if0(BAR_PFREE + (j & 1) * 8, lane);
      if (j == 5 && hw == 2) {
        if (lane == 0) TLP(60);
        if (item >= ORING && item < OFRESH) flag_wait(bud, &g_done[item - ORING], (epoch + 1) * 2);
        if (lane == 0) TLP(61);
      }
    }
    bool bad = false;
    const uint32_t la = SB + OFF_L + (((r & 7) >> 1) * 40 + 2 * (r >> 3) + (r & 1) + 4 * hw) * 4;
#pragma unroll
    for (int u = 0; u < 4; u++) {
      const float l = acc[u] + __shfl_xor_sync(0xffffffffu, acc[u], 1);
      if (u < 3 || hw == 0) {
        bad |= !(l >= 9.094947017729282e-13f && l <= 1.099511627776e12f);
        float inv;
        asm("rcp.approx.ftz.f32 %0, %1;" : "=f"(inv) : "f"(l));
        asm volatile("st.shared.f32 [%0], %1;" ::"r"(la + u * 48), "f"(inv) : "memory");
      }
    }
    publish_generic(BAR_LFULL, lane);
    if (lane == 0) TLP(40 + hw * 4);
    uint32_t anybad;
    asm volatile("{\n.reg .pred p, q;\nsetp.ne.u32 p, %1, 0;\nbarrier.red.or.pred q, 7, 96, p;\nselp.u32 %0, 1, 0, q;\n}\n"
                 : "=r"(anybad) : "r"((uint32_t)bad) : "memory");
    if (__any_sync(0xffffffffu, anybad)) {
      mbar_wait(bud, BAR_OFULL, par);
      slow_item(p, item, hw);
      bar_sync(7, 96);
    }
    if (hw == 1) {
      mbar_wait(bud, BAR_OFULL, par);
      if ((tid_x() & 31) == 0) {
        TLP(41 + hw * 4);
        asm volatile("red.release.gpu.global.add.s32 [%0], 1;" ::"l"(&g_ready[item]) : "memory");
        TLP(42 + hw * 4);
      }
      __syncwarp();
    }
    item = next_item();
  }
}

__device__ __forceinline__ int attn_producer(const Params& p, int item) {
  int bud = WAIT_BUDGET;
  uint32_t sa = 0, pa = 1;
  const uint64_t pol = evict_first_policy();
  const bool draws = item >= N_OCTA;
  const int delay = start_delay(item);
  {
    const long long t0 = clock64();
    while (clock64() - t0 < delay) __nanosleep(100);
  }
#pragma unroll 1
  for (int it = 0; item < NITEMS; it++) {
    const int blk = item >> 9, h = (item >> 4) & 31, b = item & 15;
    const int row0 = (b * NH + h) * SK;
#pragma unroll
    for (int c = 0; c < 10; c++) {
      if (c >= NSLOT || (it | delay)) {
        mbar_wait(bud, BAR_EMPTYA + sa * 8, pa);
        TLP(c);
        mbar_expect(BAR_FULLA + sa * 8, A_SLOT + B_SLOT);
        tma3d(A_ADDR(sa), &p.wq[blk], BAR_FULLA + sa * 8, 0, c * 64, h * 3);
        mbar_wait(bud, BAR_EMPTYB + xs(c) * 8, c < NSLOT);
        TLP(10 + c);
        tma2d(B_ADDR(xs(c)), &p.x[blk], BAR_FULLA + sa * 8, c * 64, b * SQ);
      }
      if (++sa == NSLOT) { sa = 0; pa ^= 1; }
    }
#pragma unroll
    for (int i = 0; i < 16; i++) {
      const bool isK = (i == 0) || ((i & 1) && i < 15);
      const int j = i == 0 ? 0 : (i == 15 ? 7 : (isK ? (i + 1) >> 1 : (i - 2) >> 1));
      mbar_wait(bud, BAR_EMPTYA + sa * 8, pa);
      TLP(20 + i);
      if (i == 11) item = draws ? NCTA + atomicAdd(&g_ticket, 1) : NITEMS;
      if (i == 13) asm volatile("st.shared.s32 [%0], %1;" ::"r"(NEXT_ITEM), "r"(item) : "memory");
      mbar_expect(BAR_FULLA + sa * 8, A_SLOT);
      tma3d_hint(A_ADDR(sa), isK ? &p.k[blk] : &p.v[blk], BAR_FULLA + sa * 8, 0, row0 + j * 64, 0, pol);
      if (++sa == NSLOT) { sa = 0; pa ^= 1; }
    }
  }
  return item;
}

struct OJob { int tile, part, c0, n; };
__device__ __forceinline__ OJob get_ojob(int cta, int last) {
  if (cta < N_OCTA) return OJob{cta, 0, 0, CHUNK1};
  const int u = last - NITEMS, part = 1 + (u >> 5), tile = part == 3 ? 95 - u : u & 31;
  const int c1 = CHUNK1, c2 = c1 + LEN1 - ((tile * LSLOPE1 + 16) >> 5), c3 = c2 + LEN2 - ((tile * LSLOPE2 + 16) >> 5);
  return OJob{tile, part, part == 1 ? c1 : part == 2 ? c2 : c3, part == 1 ? c2 - c1 + 1 : part == 2 ? c3 - c2 + 1 : part == 3 ? 189 - c3 + 1 : 0};
}
__device__ __forceinline__ int unperm(int c) { return 8 * ((c >> 1) & 1) + 4 * (c >> 3) + 2 * ((c >> 2) & 1) + (c & 1); }
__device__ __forceinline__ uint32_t first_stage(const OJob& job) { return job.part ? (uint32_t)(300 - job.n) % 3 : 0; }

template <int W>
__device__ __forceinline__ void oproj_consumer(const Params& p, const OJob job) {
  int bud = WAIT_BUDGET;
  const int tid = threadIdx.x & 127, lane = tid & 31, warp = tid >> 5;
  float a0[80], a1[80], ah[40];
  zero_regs(a0); zero_regs(a1); zero_regs(ah);
  int left = job.n, step = 0;
  uint32_t st = first_stage(job), ph = 0;
#pragma unroll 1
  while (left) {
    const int nc = left > 3 * NH ? 3 * NH : left;
    left -= nc;
#pragma unroll 1
    for (int c = 0; c < nc; c++) {
      mbar_wait(bud, BAR_GFULL + st * 8, (ph >> st) & 1);
      ph ^= 1 << st;
      if (W == 0) asm volatile("{\n.reg .pred p;\nsetp.eq.s32 p, %0, %1;\n@p bar.sync 11, 256;\n}\n" ::"r"(c + 1), "r"(nc) : "memory");
      wg_fence();
      const uint32_t la = (SB + st * O_STAGE) >> 4, lb = la;
#define O_STEP(ks, sc)                                                        \
  mma80r<1, 1, 2 * 8192 + ks * 2048, O_AB + W * 10240 + ks * 512>(ah, p.dsw, la, p.dso, lb, sc);   \
  mma160r<1, 1, (W * 3) * 8192 + ks * 2048, O_AB + ks * 512>(a0, p.dsw, la, p.dso, lb, sc);        \
  mma160r<1, 1, (W * 3 + 1) * 8192 + ks * 2048, O_AB + ks * 512>(a1, p.dsw, la, p.dso, lb, sc);
      O_STEP(0, c != 0) O_STEP(1, 1)
      wg_commit();
      wg_wait<1>();
      mbar_arrive_if0(BAR_GEMPTY + (st == 0 ? 2 : st - 1) * 8, tid | (c == 0));
      wg_fence();
      O_STEP(2, 1) O_STEP(3, 1)
#undef O_STEP
      wg_commit();
      if (++st == 3) {
        st = 0;
        if (W == 0)
          asm volatile("{\n.reg .pred p;\nsetp.eq.u32 p, %1, 0;\n@p red.relaxed.gpu.global.add.s32 [%0], 1;\n}\n"
                       ::"l"(&g_done[step * 16 + (job.tile >> 1)]), "r"(tid | job.part) : "memory");
        TLG(step);
        step++;
      }
    }
    if (W == 1) bar_arrive(11, 256);
    wg_wait<0>();
    reg_fence(a0); reg_fence(a1); reg_fence(ah);
    mbar_arrive_if0(BAR_GEMPTY + (st - 1) * 8, tid | (st == 0));
    TLG(63);
    const int prow = (lane & 7) + 8 * (lane >> 4), qrow = left ? unperm(prow) : prow;
    const uint32_t sg = SB + O_OUT + qrow * 128 + (((2 * warp + ((lane >> 3) & 1)) ^ (qrow & 7)) << 4);
    if (W == 1) {
      bar_arrive(3, 256);
      store_scaled(sg + 3 * B_SLOT, a0, 1.0f);
      publish(BAR_GOUT + 24, lane);
      store_scaled(sg + 4 * B_SLOT, a1, 1.0f);
      publish(BAR_GOUT + 32, lane);
      bar_sync(9, 256);
      store_scaled(sg + 2 * B_SLOT + 10240, ah, 1.0f);
      publish(BAR_GOUT + 16, lane);
    } else {
      bar_arrive(9, 256);
      bar_sync(3, 256);
      store_scaled(sg, a0, 1.0f);
      publish(BAR_GOUT, lane);
      store_scaled(sg + B_SLOT, a1, 1.0f);
      publish(BAR_GOUT + 8, lane);
      store_scaled(sg + 2 * B_SLOT, ah, 1.0f);
      publish(BAR_GOUT + 16, lane);
    }
  }
  TL_FLUSH();
  TLG(0);
  float acc[7][8];
  uint32_t in[7], blk[7], oo[7];
#pragma unroll
  for (int i = 0; i < 7; i++) {
    const int e = min(i * 256 + W * 128 + tid, 1599), r = e / 40, cc = e % 40, R = job.part * 40 + r;
    in[i] = r * 128 + (((cc ^ r) & 7) << 4);
    blk[i] = cc >> 3;
    oo[i] = ((R & ~15) + unperm(R & 15)) * (2 * DM / 8) + cc;
    asm volatile("" : "+r"(oo[i]));
#pragma unroll
    for (int k = 0; k < 8; k++) acc[i][k] = 0.f;
  }
  bar_sync(10, 256);
#pragma unroll 1
  for (int q = 0; q < 4; q++) {
    if (q) mbar_wait(bud, BAR_GRED + (q - 1) * 8, 0);
    if (q == 3) TLG(1);
    const uint32_t base = q ? SB + (q - 1) * 25600 : SB + O_OUT + job.part * 5120, bs = q ? 5120 : B_SLOT;
    uint4 v[7];
#pragma unroll
    for (int i = 0; i < 7; i++) v[i] = lds128(base + blk[i] * bs + in[i]);
#pragma unroll
    for (int i = 0; i < 7; i++) {
      acc[i][0] += bf_lo(v[i].x); acc[i][1] += bf_hi(v[i].x); acc[i][2] += bf_lo(v[i].y); acc[i][3] += bf_hi(v[i].y);
      acc[i][4] += bf_lo(v[i].z); acc[i][5] += bf_hi(v[i].z); acc[i][6] += bf_lo(v[i].w); acc[i][7] += bf_hi(v[i].w);
    }
  }
  uint4* go = (uint4*)p.outp + (job.tile >> 1) * SQ * (2 * DM / 8) + DM / 8 + (job.tile & 1) * 40;
#pragma unroll
  for (int i = 0; i < 7; i++) {
    if (i * 256 + W * 128 + tid < 1600)
      go[oo[i]] = make_uint4(pack2(acc[i][0], acc[i][1]), pack2(acc[i][2], acc[i][3]), pack2(acc[i][4], acc[i][5]), pack2(acc[i][6], acc[i][7]));
  }
  TLG(2);
  TL_FLUSH();
}

__device__ __forceinline__ void oproj_producer(const Params& p, const OJob job, int target) {
  int bud = WAIT_BUDGET;
  const uint64_t polo = evict_first_policy();
  mbar_wait(bud, BAR_FREE, 0);
  uint32_t st = first_stage(job), ph = 7;
  int seen = -1;
#pragma unroll 1
  for (int i = 0; i < job.n; i++) {
    const int c = job.part && i == job.n - 1 ? 188 + job.part : job.c0 + i, step = c / 3, kb = c - 3 * step;
    const int item = step * 16 + (job.tile >> 1);
    if (step != seen) {
      flag_wait(bud, &g_ready[item], target);
      asm volatile("fence.proxy.async.global;" ::: "memory");
      seen = step;
    }
    const uint32_t dst = SB + st * O_STAGE, bar = BAR_GFULL + st * 8;
    const char* og = o_slot(item) + kb * B_SLOT;
    mbar_wait(bud, BAR_GEMPTY + st * 8, (ph >> st) & 1);
    ph ^= 1 << st;
    mbar_expect(bar, O_STAGE);
    tma3d(dst, &p.wo[step >> 5], bar, 0, (c - (step >> 5) * 3 * NH) * 64, (job.tile & 1) * 5);
    bulk_load_hint(dst + O_AB, og, B_SLOT, bar, polo);
    if (++st == 3) st = 0;
  }
  mbar_wait(bud, BAR_GEMPTY, ph & 1);
  mbar_wait(bud, BAR_GEMPTY + 8, (ph >> 1) & 1);
  uint32_t todo = 15 & ~(1 << job.part), dst = SB, bar = BAR_GRED;
  while (todo) {
    int v0, v1, v2, v3;
    asm volatile("ld.acquire.gpu.global.v4.s32 {%0, %1, %2, %3}, [%4];" : "=r"(v0), "=r"(v1), "=r"(v2), "=r"(v3) : "l"(&g_pcnt[job.tile * 4]) : "memory");
    const uint32_t rdy = --bud > 0 ? (v0 - target >= 0) | (v1 - target >= 0) << 1 | (v2 - target >= 0) << 2 | (v3 - target >= 0) << 3 : 15;
    if (!(rdy & todo)) continue;
    asm volatile("fence.proxy.async.global;" ::: "memory");
#pragma unroll 1
    for (int q = 0; q < 4; q++) {
      if (!(((rdy & todo) >> q) & 1)) continue;
      TLE(4 + q);
      mbar_expect(bar, 25600);
      for (int k = 0; k < 5; k++)
        tma2d(dst + k * 5120, &p.part, bar, (job.tile & 1) * 320 + k * 64, q * NB * SQ + (job.tile >> 1) * SQ + job.part * 40);
      todo &= ~(1 << q);
      dst += 25600;
      bar += 8;
    }
  }
}

__device__ __forceinline__ void oproj_storer(const Params& p, const OJob job) {
  int bud = WAIT_BUDGET;
  const int col = (job.tile & 1) * 320, row = (job.tile >> 1) * SQ;
  if (job.part == 0) {
    for (int k = 0; k < 3; k++) {
      mbar_wait(bud, BAR_GOUT + k * 8, 0);
      tma_store2d(&p.out, SB + O_OUT + k * B_SLOT, col + k * 64, row);
    }
    asm volatile("cp.async.bulk.commit_group;" ::: "memory");
    asm volatile("cp.async.bulk.wait_group.read 0;" ::: "memory");
    mbar_arrive2_if0(BAR_GEMPTY + 16, 0);
    mbar_wait(bud, BAR_GFULL + 16, 0);
    for (int k = 3; k < 5; k++) {
      mbar_wait(bud, BAR_GOUT + k * 8, 0);
      tma_store2d(&p.out, SB + O_OUT + k * B_SLOT, col + k * 64, row);
      asm volatile("cp.async.bulk.commit_group;" ::: "memory");
      asm volatile("cp.async.bulk.wait_group.read 0;" ::: "memory");
      __nanosleep(1000);
    }
  }
#pragma unroll 1
  for (int i = 0; i < 5; i++) {
    const int k = (0x21043 >> (4 * i)) & 15;
    mbar_wait(bud, BAR_GOUT + k * 8, job.part == 0);
    if (i == 0) TLE(0);
    for (int q = 1; q < 4; q++) {
      const int sh = (job.part + q) & 3;
      tma_store2d(&p.part, SB + O_OUT + k * B_SLOT + sh * 5120, col + k * 64, job.part * NB * SQ + row + sh * 40);
    }
  }
  asm volatile("cp.async.bulk.commit_group;" ::: "memory");
  TLE(1);
  asm volatile("cp.async.bulk.wait_group 0;" ::: "memory");
  TLE(2);
  asm volatile("fence.proxy.async.global;" ::: "memory");
  asm volatile("red.release.gpu.global.add.s32 [%0], 1;" ::"l"(&g_pcnt[job.tile * 4 + job.part]) : "memory");
  TLE(3);
}

__global__ void __launch_bounds__(384, 1) fused_kernel(const __grid_constant__ Params p) {
  extern __shared__ __align__(1024) char smem_raw[];
  if ((smem_u32(smem_raw) & 0xFFFFFFu) != SB) return;
  const int cta = (((blockIdx.x / PERM_G) * PERM_M) % (NCTA / PERM_G)) * PERM_G + (blockIdx.x % PERM_G);
  const int warp = __shfl_sync(0xffffffffu, threadIdx.x >> 5, 0);
  if (threadIdx.x == 0) {
    for (int i = 0; i < NSLOT; i++) { mbar_init(BAR_FULLA + i * 8, 1); mbar_init(BAR_EMPTYA + i * 8, 2); mbar_init(BAR_EMPTYB + i * 8, 2); }
    proxy_fence();
    if (start_delay(cta) == 0) {
#pragma unroll 1
      for (int c = 0; c < NSLOT; c++) {
        mbar_expect(BAR_FULLA + c * 8, A_SLOT + B_SLOT);
        tma3d(A_ADDR(c), &p.wq[0], BAR_FULLA + c * 8, 0, c * 64, (cta >> 4) * 3);
        tma2d(B_ADDR(c), &p.x[0], BAR_FULLA + c * 8, c * 64, (cta & 15) * SQ);
      }
    }
  }
  if (threadIdx.x == 64) {
    mbar_init(BAR_XDONE, 1); mbar_init(BAR_QH, 4); mbar_init(BAR_QM, 4);
    mbar_init(BAR_PFULL, 4); mbar_init(BAR_PFULL + 8, 4); mbar_init(BAR_PFREE, 3); mbar_init(BAR_PFREE + 8, 3);
    mbar_init(BAR_LFULL, 3); mbar_init(BAR_PMID, 4); mbar_init(BAR_PMID + 8, 4); mbar_init(BAR_OFULL, 8);
  }
  if (threadIdx.x == 96) {
    for (int i = 0; i < O_NST; i++) { mbar_init(BAR_GFULL + i * 8, 1); mbar_init(BAR_GEMPTY + i * 8, 2); }
    for (int i = 0; i < 5; i++) mbar_init(BAR_GOUT + i * 8, i == 2 ? 8 : 4);
    mbar_init(BAR_GRED, 1); mbar_init(BAR_GRED + 8, 1); mbar_init(BAR_GRED + 16, 1); mbar_init(BAR_FREE, 2);
    proxy_fence();
  }
  if (warp == 1 && threadIdx.x < 32 + 12) asm volatile("prefetch.tensormap [%0];" ::"l"(&p.x[0] + (threadIdx.x - 32)) : "memory");
  __syncthreads();
  if (warp >= 8) {
    asm volatile("setmaxnreg.dec.sync.aligned.u32 40;");
    if (warp == 8) {
      if (elect_one()) {
        const OJob job = get_ojob(cta, attn_producer(p, cta));
        const int epoch = *(volatile int*)&g_epoch[cta];
        *(volatile int*)&g_epoch[cta] = epoch + 1;
        if (job.n) oproj_producer(p, job, epoch + 1);
      }
    } else {
      const int epoch = __shfl_sync(0xffffffffu, *(volatile int*)&g_epoch[cta], 0);
      attn_helper(p, warp - 9, cta, epoch);
      if (warp == 9) {
        const OJob job = get_ojob(cta, next_item());
        if (job.n && elect_one()) oproj_storer(p, job);
      }
    }
  } else {
    asm volatile("setmaxnreg.inc.sync.aligned.u32 232;");
    if (warp < 4) {
      const OJob job = get_ojob(cta, attn_consumer<0>(p.dsw, cta));
      if (job.n) oproj_consumer<0>(p, job);
    } else {
      const OJob job = get_ojob(cta, attn_consumer<1>(p.dsw, cta));
      if (job.n) oproj_consumer<1>(p, job);
    }
  }
}

typedef CUresult (*EncodeFn)(CUtensorMap*, CUtensorMapDataType, cuuint32_t, void*, const cuuint64_t*, const cuuint64_t*, const cuuint32_t*,
                             const cuuint32_t*, CUtensorMapInterleave, CUtensorMapSwizzle, CUtensorMapL2promotion, CUtensorMapFloatOOBfill);

void make3d(EncodeFn enc, CUtensorMap* m, const void* ptr, uint64_t rows, uint64_t cols, uint32_t box_rows, uint32_t box_blocks,
            CUtensorMapL2promotion promo = CU_TENSOR_MAP_L2_PROMOTION_L2_128B) {
  cuuint64_t gd[3] = {64, rows, cols / 64};
  cuuint64_t gs[2] = {cols * 2, 128};
  cuuint32_t bd[3] = {64, box_rows, box_blocks}, es[3] = {1, 1, 1};
  enc(m, CU_TENSOR_MAP_DATA_TYPE_BFLOAT16, 3, (void*)ptr, gd, gs, bd, es, CU_TENSOR_MAP_INTERLEAVE_NONE, CU_TENSOR_MAP_SWIZZLE_128B,
      promo, CU_TENSOR_MAP_FLOAT_OOB_FILL_NONE);
}
void make2d(EncodeFn enc, CUtensorMap* m, const void* ptr, uint64_t rows, uint64_t cols, uint32_t box_rows) {
  cuuint64_t gd[2] = {cols, rows};
  cuuint64_t gs[1] = {cols * 2};
  cuuint32_t bd[2] = {64, box_rows}, es[2] = {1, 1};
  enc(m, CU_TENSOR_MAP_DATA_TYPE_BFLOAT16, 2, (void*)ptr, gd, gs, bd, es, CU_TENSOR_MAP_INTERLEAVE_NONE, CU_TENSOR_MAP_SWIZZLE_128B,
      CU_TENSOR_MAP_L2_PROMOTION_L2_128B, CU_TENSOR_MAP_FLOAT_OOB_FILL_NONE);
}

}

extern "C" void kernel_launch(void* const* d_in, const int* in_sizes, int n_in, void* d_out, int out_size) {
  static EncodeFn enc = nullptr;
  static void* part = nullptr;
  if (!enc) {
    cudaGetSymbolAddress(&part, g_part);
    cudaDriverEntryPointQueryResult qr;
    cudaGetDriverEntryPoint("cuTensorMapEncodeTiled", (void**)&enc, cudaEnableDefault, &qr);
    cudaFuncSetAttribute(fused_kernel, cudaFuncAttributeMaxDynamicSharedMemorySize, SMEM_BYTES);
  }
  Params p;
  for (int s = 0; s < 2; s++) {
    make2d(enc, &p.x[s], d_in[5 * s + 0], NB * SQ, DM, SQ);
    make3d(enc, &p.k[s], d_in[5 * s + 1], (uint64_t)NB * NH * SK, DH, 64, 3);
    make3d(enc, &p.v[s], d_in[5 * s + 2], (uint64_t)NB * NH * SK, DH, 64, 3);
    make3d(enc, &p.wq[s], d_in[5 * s + 3], DM, NH * DH, 64, 3);
    make3d(enc, &p.wo[s], d_in[5 * s + 4], NH * DH, DM, 64, 5);
    p.xp[s] = (const __nv_bfloat16*)d_in[5 * s + 0];
    p.wqp[s] = (const __nv_bfloat16*)d_in[5 * s + 3];
    p.kp[s] = (const __nv_bfloat16*)d_in[5 * s + 1];
    p.vp[s] = (const __nv_bfloat16*)d_in[5 * s + 2];
  }
  make2d(enc, &p.out, d_out, NB * SQ, 2 * DM, SQ);
  make2d(enc, &p.part, part, 4 * NB * SQ, DM, 40);
  p.outp = (__nv_bfloat16*)d_out;
  p.dsw = DESC_SW;
  p.dso = DESC_O;
  fused_kernel<<<NCTA, 384, SMEM_BYTES>>>(p);
}
```

```cpp
#include <cuda_runtime.h>
#include <cuda_bf16.h>
#include <cuda.h>
#include <stdint.h>

#define DEBUG_TIMEOUT 0

namespace {

constexpr int SQ = 160, DM = 640, NH = 32, SK = 512, DH = 192, NB = 16;
constexpr int NITEMS = 2 * NB * NH;
constexpr int NCTA = 132, N_OCTA = 32;
constexpr int ORING = 192, OFRESH = 800, CHUNK1 = 157, LEN1 = 18, LEN2 = 13, LSLOPE1 = 4, LSLOPE2 = 4;
constexpr int SL_H = 100, SL_P = 64, SL_S = 100;
constexpr int STAG_G = 4, PERM_G = 4, STAG_A0 = 19, STAG_SLOPE = 275, PERM_M = 20, PF_N = 32, PF_WAIT = 1500, PF_GAP = 300;
constexpr int OSLOTS = ORING + NITEMS - OFRESH;
constexpr int A_SLOT = 24576, B_SLOT = 20480, NSLOT = 5;
constexpr int OFF_A = 0;
constexpr int OFF_B = NSLOT * A_SLOT;
constexpr int O_STAGE = 61440, O_AB = 40960, O_NST = 3;
constexpr int OFF_L = OFF_B + NSLOT * B_SLOT;
constexpr int OFF_BAR = OFF_L + 160 * 4;
constexpr int SMEM_BYTES = OFF_BAR + 512 + 512;
constexpr int O_OUT = 2 * O_STAGE;
static_assert(O_OUT + 5 * B_SLOT <= OFF_L, "smem layout");
constexpr uint32_t SB = 1024;
constexpr uint32_t BARS = SB + OFF_BAR;
constexpr uint32_t BAR_FULLA = BARS, BAR_EMPTYA = BARS + 40, BAR_PMID = BARS + 80, BAR_EMPTYB = BARS + 120, BAR_XDONE = BARS + 160,
                   BAR_QH = BARS + 168, BAR_QM = BARS + 96, BAR_PFULL = BARS + 184, BAR_PFREE = BARS + 200, BAR_LFULL = BARS + 216,
                   BAR_OFULL = BARS + 224, BAR_GFULL = BARS + 248, BAR_GEMPTY = BARS + 280, BAR_GOUT = BARS + 328, BAR_GRED = BARS + 368,
                   BAR_FREE = BARS + 240, NEXT_ITEM = BARS + 320;
constexpr int O_ITEM_BYTES = SQ * DH * 2;

struct alignas(64) Params {
  CUtensorMap x[2], wq[2], k[2], v[2], wo[2], out, part;
  uint64_t dsw, dso;
  __nv_bfloat16* outp;
  const __nv_bfloat16 *xp[2], *wqp[2], *kp[2], *vp[2];
};

__device__ uint4 g_o[(size_t)OSLOTS * O_ITEM_BYTES / 16];
__device__ uint4 g_part[4 * NB * SQ * DM / 8];
__device__ __align__(16) int g_pcnt[4 * N_OCTA];
__device__ int g_ready[NITEMS];
__device__ int g_done[NITEMS];
__device__ int g_ticket;
__device__ int g_go;
__device__ int g_epoch[NCTA];

#define TLE(id)
#define TLP(id)
#define TLG(id)
#define TL(id)
#define TL_FLUSH()
__device__ __forceinline__ uint32_t smem_u32(const void* p) { return (uint32_t)__cvta_generic_to_shared(p); }
__device__ __forceinline__ void wg_fence() { asm volatile("wgmma.fence.sync.aligned;" ::: "memory"); }
__device__ __forceinline__ void wg_commit() { asm volatile("wgmma.commit_group.sync.aligned;" ::: "memory"); }
template <int N> __device__ __forceinline__ void wg_wait() { asm volatile("wgmma.wait_group.sync.aligned %0;" ::"n"(N) : "memory"); }
template <int N> __device__ __forceinline__ void reg_fence(float (&d)[N]) {
#pragma unroll
  for (int i = 0; i < N; i++) asm volatile("" : "+f"(d[i])::"memory");
}
template <int N> __device__ __forceinline__ void zero_regs(float (&d)[N]) {
#pragma unroll
  for (int i = 0; i < N; i++) d[i] = 0.f;
}
__device__ __forceinline__ void proxy_fence() { asm volatile("fence.proxy.async.shared::cta;" ::: "memory"); }
__device__ __forceinline__ void mbar_init(uint32_t bar, int cnt) { asm volatile("mbarrier.init.shared::cta.b64 [%0], %1;" ::"r"(bar), "r"(cnt) : "memory"); }
__device__ __forceinline__ void mbar_arrive_if0(uint32_t bar, uint32_t sel) {
  asm volatile("{\n.reg .pred p;\nsetp.eq.u32 p, %1, 0;\n@p mbarrier.arrive.shared::cta.b64 _, [%0];\n}\n" ::"r"(bar), "r"(sel) : "memory");
}
__device__ __forceinline__ void mbar_arrive2_if0(uint32_t bar, uint32_t sel) {
  asm volatile("{\n.reg .pred p;\nsetp.eq.u32 p, %1, 0;\n@p mbarrier.arrive.shared::cta.b64 _, [%0], 2;\n}\n" ::"r"(bar), "r"(sel) : "memory");
}
__device__ __forceinline__ void mbar_expect(uint32_t bar, uint32_t bytes) {
  asm volatile("mbarrier.arrive.expect_tx.shared::cta.b64 _, [%0], %1;" ::"r"(bar), "r"(bytes) : "memory");
}
__device__ __forceinline__ void mbar_wait(int& bud, uint32_t bar, uint32_t parity) {
  asm volatile(
      "{\n.reg .pred p;\n"
      "LW:\n"
      "mbarrier.try_wait.parity.shared::cta.b64 p, [%0], %1;\n"
      "@!p bra LW;\n}\n" ::"r"(bar), "r"(parity) : "memory");
}
__device__ __forceinline__ void mbar_wait_sleep(int& bud, uint32_t bar, uint32_t parity, uint32_t ns) {
  while (true) {
    uint32_t ok;
    asm volatile("{\n.reg .pred p;\nmbarrier.try_wait.parity.shared::cta.b64 p, [%1], %2;\nselp.u32 %0, 1, 0, p;\n}\n" : "=r"(ok) : "r"(bar), "r"(parity) : "memory");
    if (ok || (DEBUG_TIMEOUT && --bud <= 0)) break;
    __nanosleep(ns);
  }
}
constexpr int WAIT_BUDGET = 1 << 22;
__device__ __forceinline__ bool elect_one() {
  uint32_t p;
  asm volatile("{\n.reg .pred p;\nelect.sync _|p, 0xffffffff;\nselp.u32 %0, 1, 0, p;\n}\n" : "=r"(p));
  return p;
}
__device__ __forceinline__ void tma2d(uint32_t dst, const CUtensorMap* m, uint32_t bar, int c0, int c1) {
  asm volatile("cp.async.bulk.tensor.2d.shared::cluster.global.mbarrier::complete_tx::bytes [%0], [%1, {%3, %4}], [%2];"
               ::"r"(dst), "l"(m), "r"(bar), "r"(c0), "r"(c1) : "memory");
}
__device__ __forceinline__ void tma3d(uint32_t dst, const CUtensorMap* m, uint32_t bar, int c0, int c1, int c2) {
  asm volatile("cp.async.bulk.tensor.3d.shared::cluster.global.mbarrier::complete_tx::bytes [%0], [%1, {%3, %4, %5}], [%2];"
               ::"r"(dst), "l"(m), "r"(bar), "r"(c0), "r"(c1), "r"(c2) : "memory");
}
__device__ __forceinline__ void tma3d_hint(uint32_t dst, const CUtensorMap* m, uint32_t bar, int c0, int c1, int c2, uint64_t pol) {
  asm volatile("cp.async.bulk.tensor.3d.shared::cluster.global.mbarrier::complete_tx::bytes.L2::cache_hint [%0], [%1, {%3, %4, %5}], [%2], %6;"
               ::"r"(dst), "l"(m), "r"(bar), "r"(c0), "r"(c1), "r"(c2), "l"(pol) : "memory");
}
__device__ __forceinline__ void tma_store2d(const CUtensorMap* m, uint32_t src, int c0, int c1) {
  asm volatile("cp.async.bulk.tensor.2d.global.shared::cta.bulk_group [%0, {%2, %3}], [%1];" ::"l"(m), "r"(src), "r"(c0), "r"(c1) : "memory");
}
__device__ __forceinline__ void bar_sync(int id, int n) { asm volatile("bar.sync %0, %1;" ::"r"(id), "r"(n) : "memory"); }
__device__ __forceinline__ void bar_arrive(int id, int n) { asm volatile("bar.arrive %0, %1;" ::"r"(id), "r"(n) : "memory"); }
__device__ __forceinline__ float ex2(float x) { float y; asm("ex2.approx.ftz.f32 %0, %1;" : "=f"(y) : "f"(x)); return y; }
__device__ __forceinline__ uint32_t pack2(float lo, float hi) { uint32_t r; asm("cvt.rn.bf16x2.f32 %0, %1, %2;" : "=r"(r) : "f"(hi), "f"(lo)); return r; }
__device__ __forceinline__ void stsm_t(uint32_t a, uint32_t r0, uint32_t r1, uint32_t r2, uint32_t r3) {
  asm volatile("stmatrix.sync.aligned.m8n8.x4.trans.shared.b16 [%0], {%1,%2,%3,%4};" ::"r"(a), "r"(r0), "r"(r1), "r"(r2), "r"(r3) : "memory");
}
__device__ __forceinline__ uint64_t evict_first_policy() {
  uint64_t pol;
  asm volatile("createpolicy.fractional.L2::evict_first.b64 %0, 1.0;" : "=l"(pol));
  return pol;
}
__device__ __forceinline__ void bulk_load_hint(uint32_t dst, const void* src, uint32_t bytes, uint32_t bar, uint64_t pol) {
  asm volatile("cp.async.bulk.shared::cluster.global.mbarrier::complete_tx::bytes.L2::cache_hint [%0], [%1], %2, [%3], %4;"
               ::"r"(dst), "l"(src), "r"(bytes), "r"(bar), "l"(pol) : "memory");
}
__device__ __forceinline__ void flag_wait(int& bud, const int* p, int target) {
  while (true) {
    int v;
    asm volatile("ld.acquire.gpu.global.s32 %0, [%1];" : "=r"(v) : "l"(p) : "memory");
    if (v - target >= 0 || --bud <= 0) break;
    __nanosleep(64);
  }
}
constexpr uint64_t DESC_SW = 0x4000004000010000ull, DESC_O = 0xC000001000800000ull;
__device__ __forceinline__ uint32_t tid_x() { uint32_t t; asm volatile("mov.u32 %0, %tid.x;" : "=r"(t)); return t; }
__device__ __forceinline__ uint32_t opaque(uint32_t x) { uint32_t y; asm volatile("mov.u32 %0, %1;" : "=r"(y) : "r"(x)); return y; }

template <int TA, int TB, uint32_t OA, uint32_t OB>
__device__ __forceinline__ void mma160(float (&d)[80], uint64_t ba, uint32_t la, uint64_t bb, uint32_t lb) {
  asm volatile(
      "{\n.reg .pred p;\n.reg .b64 da, db;\nsetp.eq.b32 p, 0, 0;\n"
      "cvt.u64.u32 da, %80;\nadd.s64 da, da, %86;\nadd.s64 da, da, %84;\ncvt.u64.u32 db, %81;\nadd.s64 db, db, %87;\nadd.s64 db, db, %85;\n"
      "wgmma.mma_async.sync.aligned.m64n160k16.f32.bf16.bf16 {"
      "%0,%1,%2,%3,%4,%5,%6,%7,%8,%9,%10,%11,%12,%13,%14,%15,%16,%17,%18,%19,%20,%21,%22,%23,%24,%25,%26,%27,%28,%29,%30,%31,%32,%33,%34,%35,%36,"
      "%37,%38,%39,%40,%41,%42,%43,%44,%45,%46,%47,%48,%49,%50,%51,%52,%53,%54,%55,%56,%57,%58,%59,%60,%61,%62,%63,%64,%65,%66,%67,%68,%69,%70,%71,"
      "%72,%73,%74,%75,%76,%77,%78,%79"
      "}, da, db, p, 1, 1, %82, %83;\n}\n"
      :
      "+f"(d[0]),"+f"(d[1]),"+f"(d[2]),"+f"(d[3]),"+f"(d[4]),"+f"(d[5]),"+f"(d[6]),"+f"(d[7]),"+f"(d[8]),"+f"(d[9]),"+f"(d[10]),"+f"(d[11]),
      "+f"(d[12]),"+f"(d[13]),"+f"(d[14]),"+f"(d[15]),"+f"(d[16]),"+f"(d[17]),"+f"(d[18]),"+f"(d[19]),"+f"(d[20]),"+f"(d[21]),"+f"(d[22]),
      "+f"(d[23]),"+f"(d[24]),"+f"(d[25]),"+f"(d[26]),"+f"(d[27]),"+f"(d[28]),"+f"(d[29]),"+f"(d[30]),"+f"(d[31]),"+f"(d[32]),"+f"(d[33]),
      "+f"(d[34]),"+f"(d[35]),"+f"(d[36]),"+f"(d[37]),"+f"(d[38]),"+f"(d[39]),"+f"(d[40]),"+f"(d[41]),"+f"(d[42]),"+f"(d[43]),"+f"(d[44]),
      "+f"(d[45]),"+f"(d[46]),"+f"(d[47]),"+f"(d[48]),"+f"(d[49]),"+f"(d[50]),"+f"(d[51]),"+f"(d[52]),"+f"(d[53]),"+f"(d[54]),"+f"(d[55]),
      "+f"(d[56]),"+f"(d[57]),"+f"(d[58]),"+f"(d[59]),"+f"(d[60]),"+f"(d[61]),"+f"(d[62]),"+f"(d[63]),"+f"(d[64]),"+f"(d[65]),"+f"(d[66]),
      "+f"(d[67]),"+f"(d[68]),"+f"(d[69]),"+f"(d[70]),"+f"(d[71]),"+f"(d[72]),"+f"(d[73]),"+f"(d[74]),"+f"(d[75]),"+f"(d[76]),"+f"(d[77]),
      "+f"(d[78]),"+f"(d[79])
      : "r"(la), "r"(lb), "n"(TA), "n"(TB), "n"(OA >> 4), "n"(OB >> 4), "l"(ba), "l"(bb));
}

template <int TA, int TB, uint32_t OA, uint32_t OB>
__device__ __forceinline__ void mma160z(float (&d)[80], uint64_t ba, uint32_t la, uint64_t bb, uint32_t lb) {
  asm volatile(
      "{\n.reg .pred p;\n.reg .b64 da, db;\nsetp.ne.b32 p, 0, 0;\n"
      "cvt.u64.u32 da, %80;\nadd.s64 da, da, %86;\nadd.s64 da, da, %84;\ncvt.u64.u32 db, %81;\nadd.s64 db, db, %87;\nadd.s64 db, db, %85;\n"
      "wgmma.mma_async.sync.aligned.m64n160k16.f32.bf16.bf16 {"
      "%0,%1,%2,%3,%4,%5,%6,%7,%8,%9,%10,%11,%12,%13,%14,%15,%16,%17,%18,%19,%20,%21,%22,%23,%24,%25,%26,%27,%28,%29,%30,%31,%32,%33,%34,%35,%36,"
      "%37,%38,%39,%40,%41,%42,%43,%44,%45,%46,%47,%48,%49,%50,%51,%52,%53,%54,%55,%56,%57,%58,%59,%60,%61,%62,%63,%64,%65,%66,%67,%68,%69,%70,%71,"
      "%72,%73,%74,%75,%76,%77,%78,%79"
      "}, da, db, p, 1, 1, %82, %83;\n}\n"
      :
      "=f"(d[0]),"=f"(d[1]),"=f"(d[2]),"=f"(d[3]),"=f"(d[4]),"=f"(d[5]),"=f"(d[6]),"=f"(d[7]),"=f"(d[8]),"=f"(d[9]),"=f"(d[10]),"=f"(d[11]),
      "=f"(d[12]),"=f"(d[13]),"=f"(d[14]),"=f"(d[15]),"=f"(d[16]),"=f"(d[17]),"=f"(d[18]),"=f"(d[19]),"=f"(d[20]),"=f"(d[21]),"=f"(d[22]),
      "=f"(d[23]),"=f"(d[24]),"=f"(d[25]),"=f"(d[26]),"=f"(d[27]),"=f"(d[28]),"=f"(d[29]),"=f"(d[30]),"=f"(d[31]),"=f"(d[32]),"=f"(d[33]),
      "=f"(d[34]),"=f"(d[35]),"=f"(d[36]),"=f"(d[37]),"=f"(d[38]),"=f"(d[39]),"=f"(d[40]),"=f"(d[41]),"=f"(d[42]),"=f"(d[43]),"=f"(d[44]),
      "=f"(d[45]),"=f"(d[46]),"=f"(d[47]),"=f"(d[48]),"=f"(d[49]),"=f"(d[50]),"=f"(d[51]),"=f"(d[52]),"=f"(d[53]),"=f"(d[54]),"=f"(d[55]),
      "=f"(d[56]),"=f"(d[57]),"=f"(d[58]),"=f"(d[59]),"=f"(d[60]),"=f"(d[61]),"=f"(d[62]),"=f"(d[63]),"=f"(d[64]),"=f"(d[65]),"=f"(d[66]),
      "=f"(d[67]),"=f"(d[68]),"=f"(d[69]),"=f"(d[70]),"=f"(d[71]),"=f"(d[72]),"=f"(d[73]),"=f"(d[74]),"=f"(d[75]),"=f"(d[76]),"=f"(d[77]),
      "=f"(d[78]),"=f"(d[79])
      : "r"(la), "r"(lb), "n"(TA), "n"(TB), "n"(OA >> 4), "n"(OB >> 4), "l"(ba), "l"(bb));
}

template <int TA, int TB, uint32_t OA, uint32_t OB>
__device__ __forceinline__ void mma80(float (&d)[40], uint64_t ba, uint32_t la, uint64_t bb, uint32_t lb) {
  asm volatile(
      "{\n.reg .pred p;\n.reg .b64 da, db;\nsetp.eq.b32 p, 0, 0;\n"
      "cvt.u64.u32 da, %40;\nadd.s64 da, da, %46;\nadd.s64 da, da, %44;\ncvt.u64.u32 db, %41;\nadd.s64 db, db, %47;\nadd.s64 db, db, %45;\n"
      "wgmma.mma_async.sync.aligned.m64n80k16.f32.bf16.bf16 {"
      "%0,%1,%2,%3,%4,%5,%6,%7,%8,%9,%10,%11,%12,%13,%14,%15,%16,%17,%18,%19,%20,%21,%22,%23,%24,%25,%26,%27,%28,%29,%30,%31,%32,%33,%34,%35,%36,"
      "%37,%38,%39"
      "}, da, db, p, 1, 1, %42, %43;\n}\n"
      :
      "+f"(d[0]),"+f"(d[1]),"+f"(d[2]),"+f"(d[3]),"+f"(d[4]),"+f"(d[5]),"+f"(d[6]),"+f"(d[7]),"+f"(d[8]),"+f"(d[9]),"+f"(d[10]),"+f"(d[11]),
      "+f"(d[12]),"+f"(d[13]),"+f"(d[14]),"+f"(d[15]),"+f"(d[16]),"+f"(d[17]),"+f"(d[18]),"+f"(d[19]),"+f"(d[20]),"+f"(d[21]),"+f"(d[22]),
      "+f"(d[23]),"+f"(d[24]),"+f"(d[25]),"+f"(d[26]),"+f"(d[27]),"+f"(d[28]),"+f"(d[29]),"+f"(d[30]),"+f"(d[31]),"+f"(d[32]),"+f"(d[33]),
      "+f"(d[34]),"+f"(d[35]),"+f"(d[36]),"+f"(d[37]),"+f"(d[38]),"+f"(d[39])
      : "r"(la), "r"(lb), "n"(TA), "n"(TB), "n"(OA >> 4), "n"(OB >> 4), "l"(ba), "l"(bb));
}

template <int TA, int TB, uint32_t OA, uint32_t OB>
__device__ __forceinline__ void mma80z(float (&d)[40], uint64_t ba, uint32_t la, uint64_t bb, uint32_t lb) {
  asm volatile(
      "{\n.reg .pred p;\n.reg .b64 da, db;\nsetp.ne.b32 p, 0, 0;\n"
      "cvt.u64.u32 da, %40;\nadd.s64 da, da, %46;\nadd.s64 da, da, %44;\ncvt.u64.u32 db, %41;\nadd.s64 db, db, %47;\nadd.s64 db, db, %45;\n"
      "wgmma.mma_async.sync.aligned.m64n80k16.f32.bf16.bf16 {"
      "%0,%1,%2,%3,%4,%5,%6,%7,%8,%9,%10,%11,%12,%13,%14,%15,%16,%17,%18,%19,%20,%21,%22,%23,%24,%25,%26,%27,%28,%29,%30,%31,%32,%33,%34,%35,%36,"
      "%37,%38,%39"
      "}, da, db, p, 1, 1, %42, %43;\n}\n"
      :
      "=f"(d[0]),"=f"(d[1]),"=f"(d[2]),"=f"(d[3]),"=f"(d[4]),"=f"(d[5]),"=f"(d[6]),"=f"(d[7]),"=f"(d[8]),"=f"(d[9]),"=f"(d[10]),"=f"(d[11]),
      "=f"(d[12]),"=f"(d[13]),"=f"(d[14]),"=f"(d[15]),"=f"(d[16]),"=f"(d[17]),"=f"(d[18]),"=f"(d[19]),"=f"(d[20]),"=f"(d[21]),"=f"(d[22]),
      "=f"(d[23]),"=f"(d[24]),"=f"(d[25]),"=f"(d[26]),"=f"(d[27]),"=f"(d[28]),"=f"(d[29]),"=f"(d[30]),"=f"(d[31]),"=f"(d[32]),"=f"(d[33]),
      "=f"(d[34]),"=f"(d[35]),"=f"(d[36]),"=f"(d[37]),"=f"(d[38]),"=f"(d[39])
      : "r"(la), "r"(lb), "n"(TA), "n"(TB), "n"(OA >> 4), "n"(OB >> 4), "l"(ba), "l"(bb));
}

template <int TA, int TB, uint32_t OA, uint32_t OB>
__device__ __forceinline__ void mma160r(float (&d)[80], uint64_t ba, uint32_t la, uint64_t bb, uint32_t lb, int sc) {
  asm volatile(
      "{\n.reg .pred p;\n.reg .b64 da, db;\nsetp.ne.b32 p, %88, 0;\n"
      "cvt.u64.u32 da, %80;\nadd.s64 da, da, %86;\nadd.s64 da, da, %84;\ncvt.u64.u32 db, %81;\nadd.s64 db, db, %87;\nadd.s64 db, db, %85;\n"
      "wgmma.mma_async.sync.aligned.m64n160k16.f32.bf16.bf16 {"
      "%0,%1,%2,%3,%4,%5,%6,%7,%8,%9,%10,%11,%12,%13,%14,%15,%16,%17,%18,%19,%20,%21,%22,%23,%24,%25,%26,%27,%28,%29,%30,%31,%32,%33,%34,%35,%36,"
      "%37,%38,%39,%40,%41,%42,%43,%44,%45,%46,%47,%48,%49,%50,%51,%52,%53,%54,%55,%56,%57,%58,%59,%60,%61,%62,%63,%64,%65,%66,%67,%68,%69,%70,%71,"
      "%72,%73,%74,%75,%76,%77,%78,%79"
      "}, da, db, p, 1, 1, %82, %83;\n}\n"
      :
      "+f"(d[0]),"+f"(d[1]),"+f"(d[2]),"+f"(d[3]),"+f"(d[4]),"+f"(d[5]),"+f"(d[6]),"+f"(d[7]),"+f"(d[8]),"+f"(d[9]),"+f"(d[10]),"+f"(d[11]),
      "+f"(d[12]),"+f"(d[13]),"+f"(d[14]),"+f"(d[15]),"+f"(d[16]),"+f"(d[17]),"+f"(d[18]),"+f"(d[19]),"+f"(d[20]),"+f"(d[21]),"+f"(d[22]),
      "+f"(d[23]),"+f"(d[24]),"+f"(d[25]),"+f"(d[26]),"+f"(d[27]),"+f"(d[28]),"+f"(d[29]),"+f"(d[30]),"+f"(d[31]),"+f"(d[32]),"+f"(d[33]),
      "+f"(d[34]),"+f"(d[35]),"+f"(d[36]),"+f"(d[37]),"+f"(d[38]),"+f"(d[39]),"+f"(d[40]),"+f"(d[41]),"+f"(d[42]),"+f"(d[43]),"+f"(d[44]),
      "+f"(d[45]),"+f"(d[46]),"+f"(d[47]),"+f"(d[48]),"+f"(d[49]),"+f"(d[50]),"+f"(d[51]),"+f"(d[52]),"+f"(d[53]),"+f"(d[54]),"+f"(d[55]),
      "+f"(d[56]),"+f"(d[57]),"+f"(d[58]),"+f"(d[59]),"+f"(d[60]),"+f"(d[61]),"+f"(d[62]),"+f"(d[63]),"+f"(d[64]),"+f"(d[65]),"+f"(d[66]),
      "+f"(d[67]),"+f"(d[68]),"+f"(d[69]),"+f"(d[70]),"+f"(d[71]),"+f"(d[72]),"+f"(d[73]),"+f"(d[74]),"+f"(d[75]),"+f"(d[76]),"+f"(d[77]),
      "+f"(d[78]),"+f"(d[79])
      : "r"(la), "r"(lb), "n"(TA), "n"(TB), "n"(OA >> 4), "n"(OB >> 4), "l"(ba), "l"(bb), "r"(sc));
}

template <int TA, int TB, uint32_t OA, uint32_t OB>
__device__ __forceinline__ void mma80r(float (&d)[40], uint64_t ba, uint32_t la, uint64_t bb, uint32_t lb, int sc) {
  asm volatile(
      "{\n.reg .pred p;\n.reg .b64 da, db;\nsetp.ne.b32 p, %48, 0;\n"
      "cvt.u64.u32 da, %40;\nadd.s64 da, da, %46;\nadd.s64 da, da, %44;\ncvt.u64.u32 db, %41;\nadd.s64 db, db, %47;\nadd.s64 db, db, %45;\n"
      "wgmma.mma_async.sync.aligned.m64n80k16.f32.bf16.bf16 {"
      "%0,%1,%2,%3,%4,%5,%6,%7,%8,%9,%10,%11,%12,%13,%14,%15,%16,%17,%18,%19,%20,%21,%22,%23,%24,%25,%26,%27,%28,%29,%30,%31,%32,%33,%34,%35,%36,"
      "%37,%38,%39"
      "}, da, db, p, 1, 1, %42, %43;\n}\n"
      :
      "+f"(d[0]),"+f"(d[1]),"+f"(d[2]),"+f"(d[3]),"+f"(d[4]),"+f"(d[5]),"+f"(d[6]),"+f"(d[7]),"+f"(d[8]),"+f"(d[9]),"+f"(d[10]),"+f"(d[11]),
      "+f"(d[12]),"+f"(d[13]),"+f"(d[14]),"+f"(d[15]),"+f"(d[16]),"+f"(d[17]),"+f"(d[18]),"+f"(d[19]),"+f"(d[20]),"+f"(d[21]),"+f"(d[22]),
      "+f"(d[23]),"+f"(d[24]),"+f"(d[25]),"+f"(d[26]),"+f"(d[27]),"+f"(d[28]),"+f"(d[29]),"+f"(d[30]),"+f"(d[31]),"+f"(d[32]),"+f"(d[33]),
      "+f"(d[34]),"+f"(d[35]),"+f"(d[36]),"+f"(d[37]),"+f"(d[38]),"+f"(d[39])
      : "r"(la), "r"(lb), "n"(TA), "n"(TB), "n"(OA >> 4), "n"(OB >> 4), "l"(ba), "l"(bb), "r"(sc));
}

struct Ring { uint32_t s0, ph0; };
__device__ __forceinline__ void ring_pos(const Ring& r, int i, uint32_t& slot, uint32_t& ph) {
  uint32_t s = opaque(r.s0) + (i % NSLOT);
  uint32_t wrap = s >= NSLOT;
  slot = s - (wrap ? NSLOT : 0);
  ph = r.ph0 ^ ((i / NSLOT) & 1) ^ wrap;
}
__device__ __forceinline__ void ring_advance(Ring& r, int n) {
  uint32_t s, p;
  ring_pos(r, n, s, p);
  r.s0 = s; r.ph0 = p;
}
__host__ __device__ constexpr int idxK(int j) { return j == 0 ? 10 : 9 + 2 * j; }
__host__ __device__ constexpr int idxV(int j) { return j == 7 ? 25 : 12 + 2 * j; }
__host__ __device__ constexpr int xs(int c) { return c % NSLOT; }

__device__ __forceinline__ int start_delay(int cta) {
  return max(0, ((cta - N_OCTA) | (STAG_G - 1)) - STAG_A0) * STAG_SLOPE;
}
__device__ __forceinline__ char* o_slot(int item) {
  return (char*)g_o + (size_t)(item < OFRESH ? item % ORING : item - OFRESH + ORING) * O_ITEM_BYTES;
}
__device__ __forceinline__ int next_item(uint32_t a = NEXT_ITEM) {
  int v;
  asm volatile("ld.shared.s32 %0, [%1];" : "=r"(v) : "r"(a) : "memory");
  return __shfl_sync(0xffffffffu, v, 0);
}

template <int W, bool ACC>
__device__ __forceinline__ void mma_main(uint64_t ds, float (&d)[80], uint32_t aaddr, uint32_t baddr) {
  const uint32_t la = aaddr >> 4, lb = baddr >> 4;
  if (ACC) mma160<1, 0, W * 16384, 0>(d, ds, la, ds, lb); else mma160z<1, 0, W * 16384, 0>(d, ds, la, ds, lb);
  mma160<1, 0, W * 16384 + 1 * 2048, 1 * 32>(d, ds, la, ds, lb);
  mma160<1, 0, W * 16384 + 2 * 2048, 2 * 32>(d, ds, la, ds, lb);
  mma160<1, 0, W * 16384 + 3 * 2048, 3 * 32>(d, ds, la, ds, lb);
}
template <int W, bool ACC>
__device__ __forceinline__ void mma_mid(uint64_t ds, float (&d)[40], uint32_t aaddr, uint32_t baddr) {
  const uint32_t la = aaddr >> 4, lb = baddr >> 4;
  if (ACC) mma80<1, 0, 8192, W * 10240>(d, ds, la, ds, lb); else mma80z<1, 0, 8192, W * 10240>(d, ds, la, ds, lb);
  mma80<1, 0, 8192 + 1 * 2048, W * 10240 + 1 * 32>(d, ds, la, ds, lb);
  mma80<1, 0, 8192 + 2 * 2048, W * 10240 + 2 * 32>(d, ds, la, ds, lb);
  mma80<1, 0, 8192 + 3 * 2048, W * 10240 + 3 * 32>(d, ds, la, ds, lb);
}
template <int W, bool ACC>
__device__ __forceinline__ void mma_both(uint64_t ds, float (&dm)[80], float (&dh)[40], uint32_t aaddr, uint32_t baddr) {
  mma_mid<W, ACC>(ds, dh, aaddr, baddr);
  mma_main<W, ACC>(ds, dm, aaddr, baddr);
}
template <int KB, bool ACC>
__device__ __forceinline__ void s_mma(uint64_t ds, float (&sacc)[80], uint32_t kaddr) {
  const uint32_t la = kaddr >> 4, lb = (SB + OFF_B) >> 4;
  if (ACC) mma160<0, 0, KB * 8192, KB * B_SLOT>(sacc, ds, la, ds, lb); else mma160z<0, 0, KB * 8192, KB * B_SLOT>(sacc, ds, la, ds, lb);
  mma160<0, 0, KB * 8192 + 32, KB * B_SLOT + 32>(sacc, ds, la, ds, lb);
  mma160<0, 0, KB * 8192 + 64, KB * B_SLOT + 64>(sacc, ds, la, ds, lb);
  mma160<0, 0, KB * 8192 + 96, KB * B_SLOT + 96>(sacc, ds, la, ds, lb);
}
template <int N>
__device__ __forceinline__ void store_scaled(uint32_t addr, const float (&d)[N], float sc) {
#pragma unroll
  for (int J = 0; J < N / 8; J++)
    stsm_t(addr + J * 2048, pack2(d[8 * J] * sc, d[8 * J + 1] * sc), pack2(d[8 * J + 2] * sc, d[8 * J + 3] * sc),
           pack2(d[8 * J + 4] * sc, d[8 * J + 5] * sc), pack2(d[8 * J + 6] * sc, d[8 * J + 7] * sc));
}
__device__ __forceinline__ float4 lds_f4(uint32_t a) {
  float4 v;
  asm volatile("ld.shared.v4.f32 {%0,%1,%2,%3}, [%4];" : "=f"(v.x), "=f"(v.y), "=f"(v.z), "=f"(v.w) : "r"(a) : "memory");
  return v;
}
__device__ __forceinline__ void norm_pack(uint32_t* p, const float* d, const float4& i) {
  p[0] = pack2(d[0] * i.x, d[1] * i.y); p[1] = pack2(d[4] * i.z, d[5] * i.w);
  p[2] = pack2(d[2] * i.x, d[3] * i.y); p[3] = pack2(d[6] * i.z, d[7] * i.w);
  asm volatile("" : "+r"(p[0]), "+r"(p[1]), "+r"(p[2]), "+r"(p[3])::"memory");
}
template <int W>
__device__ __forceinline__ void pack_first(uint32_t (&pk)[60], const float (&om)[80], const float (&oh)[40], uint32_t laddr) {
  float4 n0 = lds_f4(laddr + W * 80), n1 = lds_f4(laddr + W * 80 + 16);
#pragma unroll
  for (int J = 0; J < 5; J++) {
    const float4 i = n0;
    n0 = n1;
    if (J + 2 < 5) n1 = lds_f4(laddr + W * 80 + (J + 2) * 16);
    norm_pack(&pk[20 + 4 * J], &om[8 * (5 * W + J)], i);
    norm_pack(&pk[4 * J], &oh[8 * J], i);
  }
}
template <int W, int J0, int J1>
__device__ __forceinline__ void pack_second(uint32_t (&pk)[60], const float (&om)[80], uint32_t laddr) {
  float4 n[J1 - J0];
#pragma unroll
  for (int J = J0; J < J1; J++) n[J - J0] = lds_f4(laddr + (1 - W) * 80 + J * 16);
#pragma unroll
  for (int J = J0; J < J1; J++) norm_pack(&pk[40 + 4 * J], &om[8 * (5 * (1 - W) + J)], n[J - J0]);
}
__device__ __forceinline__ char* o_ptr(int item) {
  const uint32_t t = tid_x();
  return o_slot(item) + ((t & 96) * 16 + (t & 28) * 8 + ((((t >> 1) ^ (t >> 4)) & 1) << 4) + (t & 1) * 8);
}
template <int W, int G0, int G1>
__device__ __forceinline__ void store_groups(char* op, const uint32_t (&pk)[60], uint32_t on) {
#pragma unroll
  for (int G = G0; G < G1; G++) {
    const int off = (G < 5 ? 1 : 2 * W) * B_SLOT + (5 * (G < 10 ? W : 1 - W) + G % 5) * 2048;
    asm volatile("{\n.reg .pred p;\nsetp.ne.u32 p, %5, 0;\n@p st.global.v2.b32 [%0], {%1, %2};\n@p st.global.v2.b32 [%0+256], {%3, %4};\n}\n"
                 ::"l"(op + off), "r"(pk[4 * G]), "r"(pk[4 * G + 1]), "r"(pk[4 * G + 2]), "r"(pk[4 * G + 3]), "r"(on) : "memory");
  }
}
__device__ __forceinline__ void publish_generic(uint32_t bar, int lane) {
  __syncwarp();
  mbar_arrive_if0(bar, lane);
}
__device__ __forceinline__ void publish(uint32_t bar, int lane) {
  proxy_fence();
  __syncwarp();
  mbar_arrive_if0(bar, lane);
}

#define A_ADDR(s) (SB + OFF_A + (s) * A_SLOT)
#define B_ADDR(s) (SB + OFF_B + (s) * B_SLOT)
#define WAIT_CHUNK(c, ro, sA)                \
  uint32_t sA;                               \
  {                                          \
    uint32_t pA_;                            \
    ring_pos(ring, (ro) + (c), sA, pA_);     \
    mbar_wait(bud, BAR_FULLA + sA * 8, pA_); \
  }
#define RELEASE_CHUNK(c, sA)                                  \
  mbar_arrive_if0(BAR_EMPTYA + (sA) * 8, tid);                \
  if ((c) < NSLOT) mbar_arrive_if0(BAR_EMPTYB + xs(c) * 8, tid);

template <int W>
__device__ __forceinline__ int attn_consumer(const uint64_t ds, int item) {
  int bud = WAIT_BUDGET;
  const int tid = threadIdx.x & 127, lane = tid & 31, warp = tid >> 5;
  const uint32_t st_off = ((lane & 7) + 8 * (lane >> 4)) * 128 + (((2 * warp + ((lane >> 3) & 1)) ^ (lane & 7)) << 4);
  const uint32_t laddr = SB + OFF_L + (lane & 3) * 160;
  float om[80], oh[40], sacc[80];
  uint32_t pk[60];
#pragma unroll
  for (int i = 0; i < 40; i++) pk[i] = 0;
  zero_regs(om);
  Ring ring{0u, 0u};
  uint32_t par = 0;
  int prev = 0;
  const float qscale = 0.07216878364870322f * 1.4426950408889634f;
  constexpr uint32_t pown = B_ADDR(3 + W), poth = B_ADDR(4 - W);
  TL(0); TLG(62);
  {
    WAIT_CHUNK(0, 0, s0)
    wg_fence();
    mma_both<W, false>(ds, sacc, oh, A_ADDR(s0), B_ADDR(xs(0)));
    wg_commit();
    WAIT_CHUNK(1, 0, s1)
    wg_fence();
    mma_both<W, true>(ds, sacc, oh, A_ADDR(s1), B_ADDR(xs(1)));
    wg_commit();
    wg_wait<1>();
    RELEASE_CHUNK(0, s0)
  }
#pragma unroll 1
  for (int it = 0;; it++) {
    char* op = o_ptr(prev);
#pragma unroll
    for (int c = 2; c < 8 - W; c++) {
      WAIT_CHUNK(c, 0, sA)
      TL(40 + c);
      wg_fence();
      mma_both<W, true>(ds, sacc, oh, A_ADDR(sA), B_ADDR(xs(c)));
      wg_commit();
      wg_wait<1>();
      uint32_t sP, pP;
      ring_pos(ring, c - 1, sP, pP);
      RELEASE_CHUNK(c - 1, sP)
      constexpr int NG = 3;
      if (c == 2) { pack_second<W, 0, 1>(pk, om, laddr); store_groups<W, 0 * NG, 1 * NG>(op, pk, it); }
      if (c == 3) { pack_second<W, 1, 2>(pk, om, laddr); store_groups<W, 1 * NG, 2 * NG>(op, pk, it); }
      if (c == 4) { pack_second<W, 2, 3>(pk, om, laddr); store_groups<W, 2 * NG, 3 * NG>(op, pk, it); }
      if (c == 5) { pack_second<W, 3, 4>(pk, om, laddr); store_groups<W, 3 * NG, 4 * NG>(op, pk, it); }
      if (c == 6) {
        pack_second<W, 4, 5>(pk, om, laddr);
        if (W == 1) {
          wg_wait<0>();
          RELEASE_CHUNK(6, sA)
          mbar_arrive_if0(BAR_XDONE, tid);
        }
        store_groups<W, 4 * NG, 15>(op, pk, it);
        __syncwarp();
        mbar_arrive_if0(BAR_OFULL, lane | (it == 0));
      }
    }
    uint32_t sK0, pK0, s7, p7;
    ring_pos(ring, idxK(W), sK0, pK0);
    ring_pos(ring, 7, s7, p7);
    if (W == 1) mbar_wait(bud, BAR_FULLA + s7 * 8, p7);
    WAIT_CHUNK(8, 0, s8)
    if (W == 0) {
      wg_fence();
      mma_both<W, true>(ds, sacc, oh, A_ADDR(s8), B_ADDR(xs(8)));
      wg_commit();
      wg_wait<1>();
      RELEASE_CHUNK(7, s7)
    }
    WAIT_CHUNK(9, 0, s9)
    TL(48);
    if (W == 0) {
      wg_fence();
      mma_mid<W, true>(ds, oh, A_ADDR(s9), B_ADDR(xs(9)));
      wg_commit();
      mma_main<W, true>(ds, sacc, A_ADDR(s9), B_ADDR(xs(9)));
      wg_commit();
      bar_arrive(5, 256);
      TL(49);
      wg_wait<1>();
      reg_fence(oh);
      mbar_wait(bud, BAR_XDONE, par);
      store_scaled(B_ADDR(1) + st_off, oh, qscale);
    } else {
      bar_sync(5, 256);
      wg_fence();
      mma_mid<W, true>(ds, oh, A_ADDR(s7), B_ADDR(xs(7)));
      mma_mid<W, true>(ds, oh, A_ADDR(s8), B_ADDR(xs(8)));
      mma_mid<W, true>(ds, oh, A_ADDR(s9), B_ADDR(xs(9)));
      wg_commit();
      mma_main<W, true>(ds, sacc, A_ADDR(s7), B_ADDR(xs(7)));
      wg_commit();
      mma_main<W, true>(ds, sacc, A_ADDR(s8), B_ADDR(xs(8)));
      wg_commit();
      wg_wait<2>();
      reg_fence(oh);
      store_scaled(B_ADDR(1) + 10240 + st_off, oh, qscale);
      wg_fence();
      mma_main<W, true>(ds, sacc, A_ADDR(s9), B_ADDR(xs(9)));
      wg_commit();
      bar_arrive(8, 256);
      TL(49);
      wg_wait<2>();
      RELEASE_CHUNK(7, s7)
      publish(BAR_QH, lane);
    }
    wg_wait<0>();
    reg_fence(sacc);
    TL(1);
    RELEASE_CHUNK(8, s8)
    RELEASE_CHUNK(9, s9)
    store_scaled(B_ADDR(2 * W) + st_off, sacc, qscale);
    if (W == 1) publish(BAR_QM, lane); else proxy_fence();
    TL(2);
    uint32_t sK = sK0, sV1 = 0;
    if (W == 0) {
      zero_regs(om); zero_regs(oh);
      reg_fence(om); reg_fence(oh);
      mbar_wait(bud, BAR_FULLA + sK0 * 8, pK0);
      bar_sync(8, 256);
      wg_fence();
      s_mma<0, false>(ds, sacc, A_ADDR(sK));
      mbar_wait(bud, BAR_QH, par);
      TL(3);
      wg_fence();
      s_mma<1, true>(ds, sacc, A_ADDR(sK));
      mbar_wait(bud, BAR_QM, par);
      TL(5);
      wg_fence();
      s_mma<2, true>(ds, sacc, A_ADDR(sK));
      wg_commit();
      wg_commit();
      bar_arrive(2, 256);
    } else {
      uint32_t pV1;
      ring_pos(ring, idxV(0), sV1, pV1);
      mbar_wait(bud, BAR_FULLA + sK * 8, pK0);
      bar_sync(2, 256);
      wg_fence();
      s_mma<0, false>(ds, sacc, A_ADDR(sK));
      s_mma<1, true>(ds, sacc, A_ADDR(sK));
      s_mma<2, true>(ds, sacc, A_ADDR(sK));
      wg_commit();
      TL(6);
      mbar_wait(bud, BAR_FULLA + sV1 * 8, pV1);
      mbar_wait(bud, BAR_PFULL, 0);
      TL(7);
      wg_fence();
      mma_both<W, false>(ds, om, oh, A_ADDR(sV1), poth);
      wg_commit();
      bar_arrive(1, 256);
    }
    Ring rv;
    ring_pos(ring, idxV(W), rv.s0, rv.ph0);
#pragma unroll 1
    for (int jj = 0;; jj++) {
      wg_wait<1>();
      reg_fence(sacc);
      TL(8 + jj * 7);
      mbar_arrive2_if0(BAR_EMPTYA + sK * 8, tid);
      mbar_arrive_if0(BAR_EMPTYB + tid * 8, (tid >= 3) | (jj != 3));
#pragma unroll
      for (int J = 0; J < 10; J++) {
        stsm_t(pown + st_off + J * 2048, pack2(ex2(sacc[8 * J]), ex2(sacc[8 * J + 1])), pack2(ex2(sacc[8 * J + 2]), ex2(sacc[8 * J + 3])),
               pack2(ex2(sacc[8 * J + 4]), ex2(sacc[8 * J + 5])), pack2(ex2(sacc[8 * J + 6]), ex2(sacc[8 * J + 7])));
        if (W == 1 && (J == 2 || J == 5)) publish_generic(BAR_PMID + (J / 3) * 8, lane | (jj != 3));
        if (J == 4) {
          wg_wait<0>();
          mbar_arrive_if0(BAR_EMPTYA + sV1 * 8, tid | (W == 0 && jj == 0));
        }
      }
      publish(BAR_PFULL + W * 8, lane);
      TL(10 + jj * 7);
      if (jj == 3) break;
      uint32_t pK, pV1;
      ring_pos(rv, 1, sK, pK);
      ring_pos(rv, 2, sV1, pV1);
      mbar_wait(bud, BAR_FULLA + rv.s0 * 8, rv.ph0);
      bar_sync(1 + W, 256);
      wg_fence();
      mma_both<W, true>(ds, om, oh, A_ADDR(rv.s0), pown);
      wg_commit();
      mbar_wait(bud, BAR_FULLA + sK * 8, pK);
      TL(11 + jj * 7);
      wg_fence();
      s_mma<0, false>(ds, sacc, A_ADDR(sK));
      s_mma<1, true>(ds, sacc, A_ADDR(sK));
      wg_commit();
      wg_wait<1>();
      mbar_arrive_if0(BAR_EMPTYA + rv.s0 * 8, tid);
      wg_fence();
      s_mma<2, true>(ds, sacc, A_ADDR(sK));
      wg_commit();
      TL(13 + jj * 7);
      mbar_wait(bud, BAR_FULLA + sV1 * 8, pV1);
      mbar_wait(bud, BAR_PFREE + W * 8, jj & 1);
      mbar_wait(bud, BAR_PFULL + (1 - W) * 8, (jj + W) & 1);
      TL(14 + jj * 7);
      wg_fence();
      mma_both<W, true>(ds, om, oh, A_ADDR(sV1), poth);
      wg_commit();
      bar_arrive(2 - W, 256);
      ring_advance(rv, 4);
    }
    uint32_t sV7, pV7;
    ring_pos(ring, idxV(7), sV7, pV7);
    prev = item;
    if (W == 1 && !DEBUG_TIMEOUT) item = next_item();
    if (W == 0) {
      uint32_t sV6, pV6;
      ring_pos(ring, idxV(6), sV6, pV6);
      mbar_wait(bud, BAR_FULLA + sV6 * 8, pV6);
      bar_sync(1, 256);
      wg_fence();
      mma_both<0, true>(ds, om, oh, A_ADDR(sV6), pown);
      wg_commit();
      mbar_wait(bud, BAR_FULLA + sV7 * 8, pV7);
      wg_wait<0>();
      mbar_arrive_if0(BAR_EMPTYA + sV6 * 8, tid);
      mbar_wait(bud, BAR_PFULL + 8, 1);
      wg_fence();
      mma_both<0, true>(ds, om, oh, A_ADDR(sV7), poth);
      wg_commit();
      bar_arrive(6, 256);
    } else {
      mbar_wait(bud, BAR_FULLA + sV7 * 8, pV7);
      bar_sync(6, 256);
    }
    TL(32);
    if (DEBUG_TIMEOUT) item = next_item(NEXT_ITEM + 4);
    else if (W == 0) item = next_item();
    if (item >= NITEMS) {
      if (W == 1) {
        wg_fence();
        mma_both<1, true>(ds, om, oh, A_ADDR(sV7), pown);
        wg_commit();
      }
      wg_wait<0>();
      reg_fence(om); reg_fence(oh);
      TL(33);
      mbar_wait(bud, BAR_LFULL, par);
      mbar_arrive_if0(BAR_FREE, tid);
      TL(34);
      pack_first<W>(pk, om, oh, laddr);
      op = o_ptr(prev);
      store_groups<W, 0, 10>(op, pk, 1);
      pack_second<W, 0, 5>(pk, om, laddr);
      store_groups<W, 10, 15>(op, pk, 1);
      publish_generic(BAR_OFULL, lane);
      TL(35); TLG(63);
      TL_FLUSH();
      return item;
    }
    {
      if (W == 1) {
        wg_fence();
        mma_both<1, true>(ds, om, oh, A_ADDR(sV7), pown);
        wg_commit();
      }
      WAIT_CHUNK(0, 26, s0)
      WAIT_CHUNK(1, 26, s1)
      if (W == 0) {
        wg_wait<0>();
        reg_fence(om); reg_fence(oh);
        TL(33);
        wg_fence();
        mma_main<W, false>(ds, sacc, A_ADDR(s0), B_ADDR(xs(0)));
        wg_commit();
      } else {
        wg_fence();
        mma_main<W, false>(ds, sacc, A_ADDR(s0), B_ADDR(xs(0)));
        mma_main<W, true>(ds, sacc, A_ADDR(s1), B_ADDR(xs(1)));
        wg_commit();
        wg_wait<1>();
        reg_fence(om); reg_fence(oh);
        TL(33);
      }
      mbar_arrive_if0(BAR_EMPTYA + sV7 * 8, tid);
      mbar_wait(bud, BAR_LFULL, par);
      mbar_arrive_if0(BAR_EMPTYB + 24 + tid * 8, tid >= 2);
      TL(34);
      pack_first<W>(pk, om, oh, laddr);
      TL(36);
      wg_fence();
      mma_mid<W, false>(ds, oh, A_ADDR(s0), B_ADDR(xs(0)));
      wg_commit();
      mma_mid<W, true>(ds, oh, A_ADDR(s1), B_ADDR(xs(1)));
      if (W == 0) mma_main<W, true>(ds, sacc, A_ADDR(s1), B_ADDR(xs(1)));
      wg_commit();
      TL(37);
      wg_wait<1>();
      RELEASE_CHUNK(0, s0)
      TL(35); TLG(63);
    }
    TL_FLUSH();
    TL(0); TLG(62);
    ring_advance(ring, 26);
    par ^= 1;
  }
}

__device__ __forceinline__ uint4 lds128(uint32_t a) {
  uint4 v;
  asm volatile("ld.shared.v4.b32 {%0,%1,%2,%3}, [%4];" : "=r"(v.x), "=r"(v.y), "=r"(v.z), "=r"(v.w) : "r"(a) : "memory");
  return v;
}
__device__ __forceinline__ void acc2(float& s, float& t, uint32_t w) {
  s += __uint_as_float(w << 16);
  t += __uint_as_float(w & 0xffff0000u);
}
__device__ __forceinline__ uint32_t badd2(uint32_t a, uint32_t b) { uint32_t r; asm("add.rn.bf16x2 %0, %1, %2;" : "=r"(r) : "r"(a), "r"(b)); return r; }
__device__ __forceinline__ void sum_unit(float& acc, uint32_t pb) {
  const uint4 v0 = lds128(pb), v1 = lds128(pb ^ 32), v2 = lds128(pb ^ 64), v3 = lds128(pb ^ 96);
  const uint32_t w0 = badd2(badd2(v0.x, v0.y), badd2(v0.z, v0.w));
  float s = acc + __uint_as_float(w0 << 16), t = __uint_as_float(w0 & 0xffff0000u);
  acc2(s, t, badd2(badd2(v1.x, v1.y), badd2(v1.z, v1.w)));
  acc2(s, t, badd2(badd2(v2.x, v2.y), badd2(v2.z, v2.w)));
  acc2(s, t, badd2(badd2(v3.x, v3.y), badd2(v3.z, v3.w)));
  acc = s + t;
}
__device__ __forceinline__ float bf_lo(uint32_t w) { return __uint_as_float(w << 16); }
__device__ __forceinline__ float bf_hi(uint32_t w) { return __uint_as_float(w & 0xffff0000u); }
__device__ __forceinline__ float bf_rn(float x) { return __bfloat162float(__float2bfloat16(x)); }
__device__ __forceinline__ void slow_item(const Params& p, int item, int hw) {
  const int blk = item >> 9, h = (item >> 4) & 31, b = item & 15;
#pragma unroll 1
  for (int n = hw; n < SQ; n += 3) {
    float q[6] = {0.f, 0.f, 0.f, 0.f, 0.f, 0.f};
    {
      const uint32_t* xr = (const uint32_t*)(p.xp[blk] + (size_t)(b * SQ + n) * DM);
      const uint32_t* wq = (const uint32_t*)(p.wqp[blk] + h * DH) + (tid_x() & 31);
#pragma unroll 2
      for (int k = 0; k < DM / 2; k++) {
        const uint32_t xv = xr[k];
#pragma unroll
        for (int i = 0; i < 3; i++) {
          const uint32_t w0 = wq[i * 32], w1 = wq[NH * DH / 2 + i * 32];
          q[2 * i] = fmaf(bf_lo(xv), bf_lo(w0), fmaf(bf_hi(xv), bf_lo(w1), q[2 * i]));
          q[2 * i + 1] = fmaf(bf_lo(xv), bf_hi(w0), fmaf(bf_hi(xv), bf_hi(w1), q[2 * i + 1]));
        }
        wq += NH * DH;
      }
    }
    const uint32_t q0 = pack2(q[0], q[1]), q1 = pack2(q[2], q[3]), q2 = pack2(q[4], q[5]);
    float o[6] = {0.f, 0.f, 0.f, 0.f, 0.f, 0.f}, m = -INFINITY, l = 0.f;
    const uint32_t* kg = (const uint32_t*)(p.kp[blk] + (size_t)(b * NH + h) * SK * DH) + (tid_x() & 31);
    const uint32_t* vg = (const uint32_t*)(p.vp[blk] + (size_t)(b * NH + h) * SK * DH) + (tid_x() & 31);
#pragma unroll 1
    for (int k = 0; k < SK; k++) {
      const uint32_t k0 = kg[0], k1 = kg[32], k2 = kg[64], v0 = vg[0], v1 = vg[32], v2 = vg[64];
      kg += DH / 2; vg += DH / 2;
      float sc = fmaf(bf_lo(q0), bf_lo(k0), bf_hi(q0) * bf_hi(k0));
      sc = fmaf(bf_lo(q1), bf_lo(k1), fmaf(bf_hi(q1), bf_hi(k1), sc));
      sc = fmaf(bf_lo(q2), bf_lo(k2), fmaf(bf_hi(q2), bf_hi(k2), sc));
#pragma unroll
      for (int d = 16; d; d >>= 1) sc += __shfl_xor_sync(0xffffffffu, sc, d);
      sc = bf_rn(bf_rn(sc) * 0.07216878364870322f);
      const float mn = fmaxf(m, sc), a = ex2((m - mn) * 1.4426950408889634f), pr = ex2((sc - mn) * 1.4426950408889634f);
      m = mn;
      l = fmaf(l, a, pr);
      o[0] = fmaf(o[0], a, pr * bf_lo(v0)); o[1] = fmaf(o[1], a, pr * bf_hi(v0));
      o[2] = fmaf(o[2], a, pr * bf_lo(v1)); o[3] = fmaf(o[3], a, pr * bf_hi(v1));
      o[4] = fmaf(o[4], a, pr * bf_lo(v2)); o[5] = fmaf(o[5], a, pr * bf_hi(v2));
    }
    float inv;
    asm("rcp.approx.ftz.f32 %0, %1;" : "=f"(inv) : "f"(l));
    const int lane = tid_x() & 31;
    const int r = n & 15, c = 4 * ((r & 7) >> 1) + 2 * (r >> 3) + (r & 1);
    char* on = o_slot(item) + (lane >> 2) * 256 + (lane & 3) * 64 + (n >> 4) * 2048 +
               (((c >> 3) ^ ((lane >> 1) & 1)) << 4) + (c & 7) * 2;
#pragma unroll
    for (int i = 0; i < 3; i++) {
      *(__nv_bfloat16*)(on + i * B_SLOT) = __float2bfloat16(o[2 * i] * inv);
      *(__nv_bfloat16*)(on + i * B_SLOT + 32) = __float2bfloat16(o[2 * i + 1] * inv);
    }
  }
}
__device__ __forceinline__ void attn_helper(const Params& p, int hw, int item, int epoch) {
  int bud = WAIT_BUDGET;
  if (hw == 2) {
    if (item == 0 && elect_one()) {
      *(volatile int*)&g_ticket = 0;
      asm volatile("red.release.gpu.global.add.s32 [%0], 1;" ::"l"(&g_go) : "memory");
    }
    __syncwarp();
    flag_wait(bud, &g_go, epoch + 1);
  }
  if (item < PF_N && hw < 2) {
    const char* g = (const char*)(hw ? p.vp[0] : p.kp[0]) + (size_t)(((item & 15) * NH + (item >> 4)) * SK) * DH * 2;
    const long long t0 = clock64();
#pragma unroll 1
    for (int i = 0; i < 32; i++) {
      while (clock64() - t0 < PF_WAIT + i * PF_GAP) __nanosleep(50);
      for (int k = 0; k < 6; k++) asm volatile("prefetch.global.L2 [%0];" ::"l"(g + i * 6144 + k * 1024 + (tid_x() & 31) * 32));
      __syncwarp();
    }
  }
#pragma unroll 1
  for (int it = 0; item < NITEMS; it++) {
    const uint32_t par = it & 1;
    int lane = tid_x() & 31;
    const int r = lane >> 1;
    const uint32_t a0 = B_ADDR(3) + (16 * hw + r) * 128 + (lane & 1) * 16 + ((r & 3) << 5);
    float acc[4] = {0.f, 0.f, 0.f, 0.f};
#pragma unroll 1
    for (int j = 0; j < 8; j++) {
      const uint32_t pb = a0 + (j & 1) * B_SLOT, bfull = BAR_PFULL + (j & 1) * 8, pfull = (j >> 1) & 1;
      mbar_wait_sleep(bud, j == 7 ? BAR_PMID : bfull, j == 7 ? par : pfull, SL_H);
      sum_unit(acc[0], pb);
      if (j == 7) mbar_wait(bud, BAR_PMID + 8, par);
      sum_unit(acc[1], pb + 6144);
      if (j == 7) mbar_wait(bud, bfull, pfull);
      sum_unit(acc[2], pb + 2 * 6144);
      if (hw == 0) sum_unit(acc[3], pb + 3 * 6144);
      __syncwarp();
      mbar_arrive_if0(BAR_PFREE + (j & 1) * 8, lane);
      if (j == 5 && hw == 2) {
        if (lane == 0) TLP(60);
        if (item >= ORING && item < OFRESH) flag_wait(bud, &g_done[item - ORING], (epoch + 1) * 2);
        if (lane == 0) TLP(61);
      }
    }
    bool bad = false;
    const uint32_t la = SB + OFF_L + (((r & 7) >> 1) * 40 + 2 * (r >> 3) + (r & 1) + 4 * hw) * 4;
#pragma unroll
    for (int u = 0; u < 4; u++) {
      const float l = acc[u] + __shfl_xor_sync(0xffffffffu, acc[u], 1);
      if (u < 3 || hw == 0) {
        bad |= !(l >= 9.094947017729282e-13f && l <= 1.099511627776e12f);
        float inv;
        asm("rcp.approx.ftz.f32 %0, %1;" : "=f"(inv) : "f"(l));
        asm volatile("st.shared.f32 [%0], %1;" ::"r"(la + u * 48), "f"(inv) : "memory");
      }
    }
    publish_generic(BAR_LFULL, lane);
    if (lane == 0) TLP(40 + hw * 4);
    uint32_t anybad;
    asm volatile("{\n.reg .pred p, q;\nsetp.ne.u32 p, %1, 0;\nbarrier.red.or.pred q, 7, 96, p;\nselp.u32 %0, 1, 0, q;\n}\n"
                 : "=r"(anybad) : "r"((uint32_t)bad) : "memory");
    if (__any_sync(0xffffffffu, anybad)) {
      mbar_wait(bud, BAR_OFULL, par);
      slow_item(p, item, hw);
      bar_sync(7, 96);
    }
    if (hw == 1) {
      mbar_wait_sleep(bud, BAR_OFULL, par, SL_H);
      if ((tid_x() & 31) == 0) {
        TLP(41 + hw * 4);
        asm volatile("red.release.gpu.global.add.s32 [%0], 1;" ::"l"(&g_ready[item]) : "memory");
        TLP(42 + hw * 4);
      }
      __syncwarp();
    }
    item = next_item();
  }
}

__device__ __forceinline__ int attn_producer(const Params& p, int item) {
  int bud = WAIT_BUDGET;
  uint32_t sa = 0, pa = 1;
  const uint64_t pol = evict_first_policy();
  const bool draws = item >= N_OCTA;
  const int delay = start_delay(item);
  {
    const long long t0 = clock64();
    while (clock64() - t0 < delay) __nanosleep(100);
  }
#pragma unroll 1
  for (int it = 0; item < NITEMS; it++) {
    const int blk = item >> 9, h = (item >> 4) & 31, b = item & 15;
    const int row0 = (b * NH + h) * SK;
#pragma unroll
    for (int c = 0; c < 10; c++) {
      if (c >= NSLOT || (it | delay)) {
        mbar_wait_sleep(bud, BAR_EMPTYA + sa * 8, pa, SL_P);
        TLP(c);
        mbar_expect(BAR_FULLA + sa * 8, A_SLOT + B_SLOT);
        tma3d(A_ADDR(sa), &p.wq[blk], BAR_FULLA + sa * 8, 0, c * 64, h * 3);
        mbar_wait_sleep(bud, BAR_EMPTYB + xs(c) * 8, c < NSLOT, SL_P);
        TLP(10 + c);
        tma2d(B_ADDR(xs(c)), &p.x[blk], BAR_FULLA + sa * 8, c * 64, b * SQ);
      }
      if (++sa == NSLOT) { sa = 0; pa ^= 1; }
    }
#pragma unroll
    for (int i = 0; i < 16; i++) {
      const bool isK = (i == 0) || ((i & 1) && i < 15);
      const int j = i == 0 ? 0 : (i == 15 ? 7 : (isK ? (i + 1) >> 1 : (i - 2) >> 1));
      mbar_wait_sleep(bud, BAR_EMPTYA + sa * 8, pa, SL_P);
      TLP(20 + i);
      if (i == 11) item = draws ? NCTA + atomicAdd(&g_ticket, 1) : NITEMS;
      if (i == 13) asm volatile("st.shared.s32 [%0], %1;" ::"r"(NEXT_ITEM), "r"(item) : "memory");
      mbar_expect(BAR_FULLA + sa * 8, A_SLOT);
      tma3d_hint(A_ADDR(sa), isK ? &p.k[blk] : &p.v[blk], BAR_FULLA + sa * 8, 0, row0 + j * 64, 0, pol);
      if (++sa == NSLOT) { sa = 0; pa ^= 1; }
    }
  }
  return item;
}

struct OJob { int tile, part, c0, n; };
__device__ __forceinline__ OJob get_ojob(int cta, int last) {
  if (cta < N_OCTA) return OJob{cta, 0, 0, CHUNK1};
  const int u = last - NITEMS, part = 1 + (u >> 5), tile = part == 3 ? 95 - u : u & 31;
  const int c1 = CHUNK1, c2 = c1 + LEN1 - ((tile * LSLOPE1 + 16) >> 5), c3 = c2 + LEN2 - ((tile * LSLOPE2 + 16) >> 5);
  return OJob{tile, part, part == 1 ? c1 : part == 2 ? c2 : c3, part == 1 ? c2 - c1 + 1 : part == 2 ? c3 - c2 + 1 : part == 3 ? 189 - c3 + 1 : 0};
}
__device__ __forceinline__ int unperm(int c) { return 8 * ((c >> 1) & 1) + 4 * (c >> 3) + 2 * ((c >> 2) & 1) + (c & 1); }
__device__ __forceinline__ uint32_t first_stage(const OJob& job) { return job.part ? (uint32_t)(300 - job.n) % 3 : 0; }

template <int W>
__device__ __forceinline__ void oproj_consumer(const Params& p, const OJob job) {
  int bud = WAIT_BUDGET;
  const int tid = threadIdx.x & 127, lane = tid & 31, warp = tid >> 5;
  float a0[80], a1[80], ah[40];
  zero_regs(a0); zero_regs(a1); zero_regs(ah);
  int left = job.n, step = 0;
  uint32_t st = first_stage(job), ph = 0;
#pragma unroll 1
  while (left) {
    const int nc = left > 3 * NH ? 3 * NH : left;
    left -= nc;
#pragma unroll 1
    for (int c = 0; c < nc; c++) {
      mbar_wait(bud, BAR_GFULL + st * 8, (ph >> st) & 1);
      ph ^= 1 << st;
      if (W == 0) asm volatile("{\n.reg .pred p;\nsetp.eq.s32 p, %0, %1;\n@p bar.sync 11, 256;\n}\n" ::"r"(c + 1), "r"(nc) : "memory");
      wg_fence();
      const uint32_t la = (SB + st * O_STAGE) >> 4, lb = la;
#define O_STEP(ks, sc)                                                        \
  mma80r<1, 1, 2 * 8192 + ks * 2048, O_AB + W * 10240 + ks * 512>(ah, p.dsw, la, p.dso, lb, sc);   \
  mma160r<1, 1, (W * 3) * 8192 + ks * 2048, O_AB + ks * 512>(a0, p.dsw, la, p.dso, lb, sc);        \
  mma160r<1, 1, (W * 3 + 1) * 8192 + ks * 2048, O_AB + ks * 512>(a1, p.dsw, la, p.dso, lb, sc);
      O_STEP(0, c != 0) O_STEP(1, 1)
      wg_commit();
      wg_wait<1>();
      mbar_arrive_if0(BAR_GEMPTY + (st == 0 ? 2 : st - 1) * 8, tid | (c == 0));
      wg_fence();
      O_STEP(2, 1) O_STEP(3, 1)
#undef O_STEP
      wg_commit();
      if (++st == 3) {
        st = 0;
        if (W == 0)
          asm volatile("{\n.reg .pred p;\nsetp.eq.u32 p, %1, 0;\n@p red.relaxed.gpu.global.add.s32 [%0], 1;\n}\n"
                       ::"l"(&g_done[step * 16 + (job.tile >> 1)]), "r"(tid | job.part) : "memory");
        TLG(step);
        step++;
      }
    }
    if (W == 1) bar_arrive(11, 256);
    wg_wait<0>();
    reg_fence(a0); reg_fence(a1); reg_fence(ah);
    mbar_arrive_if0(BAR_GEMPTY + (st - 1) * 8, tid | (st == 0));
    TLG(63);
    const int prow = (lane & 7) + 8 * (lane >> 4), qrow = left ? unperm(prow) : prow;
    const uint32_t sg = SB + O_OUT + qrow * 128 + (((2 * warp + ((lane >> 3) & 1)) ^ (qrow & 7)) << 4);
    if (W == 1) {
      bar_arrive(3, 256);
      store_scaled(sg + 3 * B_SLOT, a0, 1.0f);
      publish(BAR_GOUT + 24, lane);
      store_scaled(sg + 4 * B_SLOT, a1, 1.0f);
      publish(BAR_GOUT + 32, lane);
      bar_sync(9, 256);
      store_scaled(sg + 2 * B_SLOT + 10240, ah, 1.0f);
      publish(BAR_GOUT + 16, lane);
    } else {
      bar_arrive(9, 256);
      bar_sync(3, 256);
      store_scaled(sg, a0, 1.0f);
      publish(BAR_GOUT, lane);
      store_scaled(sg + B_SLOT, a1, 1.0f);
      publish(BAR_GOUT + 8, lane);
      store_scaled(sg + 2 * B_SLOT, ah, 1.0f);
      publish(BAR_GOUT + 16, lane);
    }
  }
  TL_FLUSH();
  TLG(0);
  float acc[7][8];
  uint32_t in[7], blk[7], oo[7];
#pragma unroll
  for (int i = 0; i < 7; i++) {
    const int e = min(i * 256 + W * 128 + tid, 1599), r = e / 40, cc = e % 40, R = job.part * 40 + r;
    in[i] = r * 128 + (((cc ^ r) & 7) << 4);
    blk[i] = cc >> 3;
    oo[i] = ((R & ~15) + unperm(R & 15)) * (2 * DM / 8) + cc;
    asm volatile("" : "+r"(oo[i]));
#pragma unroll
    for (int k = 0; k < 8; k++) acc[i][k] = 0.f;
  }
  bar_sync(10, 256);
#pragma unroll 1
  for (int q = 0; q < 4; q++) {
    if (q) mbar_wait(bud, BAR_GRED + (q - 1) * 8, 0);
    if (q == 3) TLG(1);
    const uint32_t base = q ? SB + (q - 1) * 25600 : SB + O_OUT + job.part * 5120, bs = q ? 5120 : B_SLOT;
    uint4 v[7];
#pragma unroll
    for (int i = 0; i < 7; i++) v[i] = lds128(base + blk[i] * bs + in[i]);
#pragma unroll
    for (int i = 0; i < 7; i++) {
      acc[i][0] += bf_lo(v[i].x); acc[i][1] += bf_hi(v[i].x); acc[i][2] += bf_lo(v[i].y); acc[i][3] += bf_hi(v[i].y);
      acc[i][4] += bf_lo(v[i].z); acc[i][5] += bf_hi(v[i].z); acc[i][6] += bf_lo(v[i].w); acc[i][7] += bf_hi(v[i].w);
    }
  }
  uint4* go = (uint4*)p.outp + (job.tile >> 1) * SQ * (2 * DM / 8) + DM / 8 + (job.tile & 1) * 40;
#pragma unroll
  for (int i = 0; i < 7; i++) {
    if (i * 256 + W * 128 + tid < 1600)
      go[oo[i]] = make_uint4(pack2(acc[i][0], acc[i][1]), pack2(acc[i][2], acc[i][3]), pack2(acc[i][4], acc[i][5]), pack2(acc[i][6], acc[i][7]));
  }
  TLG(2);
  TL_FLUSH();
}

__device__ __forceinline__ void oproj_producer(const Params& p, const OJob job, int target) {
  int bud = WAIT_BUDGET;
  const uint64_t polo = evict_first_policy();
  mbar_wait(bud, BAR_FREE, 0);
  uint32_t st = first_stage(job), ph = 7;
  int seen = -1;
#pragma unroll 1
  for (int i = 0; i < job.n; i++) {
    const int c = job.part && i == job.n - 1 ? 188 + job.part : job.c0 + i, step = c / 3, kb = c - 3 * step;
    const int item = step * 16 + (job.tile >> 1);
    if (step != seen) {
      flag_wait(bud, &g_ready[item], target);
      asm volatile("fence.proxy.async.global;" ::: "memory");
      seen = step;
    }
    const uint32_t dst = SB + st * O_STAGE, bar = BAR_GFULL + st * 8;
    const char* og = o_slot(item) + kb * B_SLOT;
    mbar_wait_sleep(bud, BAR_GEMPTY + st * 8, (ph >> st) & 1, SL_P);
    ph ^= 1 << st;
    mbar_expect(bar, O_STAGE);
    tma3d(dst, &p.wo[step >> 5], bar, 0, (c - (step >> 5) * 3 * NH) * 64, (job.tile & 1) * 5);
    bulk_load_hint(dst + O_AB, og, B_SLOT, bar, polo);
    if (++st == 3) st = 0;
  }
  mbar_wait(bud, BAR_GEMPTY, ph & 1);
  mbar_wait(bud, BAR_GEMPTY + 8, (ph >> 1) & 1);
  uint32_t todo = 15 & ~(1 << job.part), dst = SB, bar = BAR_GRED;
  while (todo) {
    int v0, v1, v2, v3;
    asm volatile("ld.acquire.gpu.global.v4.s32 {%0, %1, %2, %3}, [%4];" : "=r"(v0), "=r"(v1), "=r"(v2), "=r"(v3) : "l"(&g_pcnt[job.tile * 4]) : "memory");
    const uint32_t rdy = --bud > 0 ? (v0 - target >= 0) | (v1 - target >= 0) << 1 | (v2 - target >= 0) << 2 | (v3 - target >= 0) << 3 : 15;
    if (!(rdy & todo)) continue;
    asm volatile("fence.proxy.async.global;" ::: "memory");
#pragma unroll 1
    for (int q = 0; q < 4; q++) {
      if (!(((rdy & todo) >> q) & 1)) continue;
      TLE(4 + q);
      mbar_expect(bar, 25600);
      for (int k = 0; k < 5; k++)
        tma2d(dst + k * 5120, &p.part, bar, (job.tile & 1) * 320 + k * 64, q * NB * SQ + (job.tile >> 1) * SQ + job.part * 40);
      todo &= ~(1 << q);
      dst += 25600;
      bar += 8;
    }
  }
}

__device__ __forceinline__ void oproj_storer(const Params& p, const OJob job) {
  int bud = WAIT_BUDGET;
  const int col = (job.tile & 1) * 320, row = (job.tile >> 1) * SQ;
  if (job.part == 0) {
    mbar_wait_sleep(bud, BAR_GOUT + 24, 0, SL_S);
    for (int k = 0; k < 3; k++) {
      mbar_wait(bud, BAR_GOUT + k * 8, 0);
      tma_store2d(&p.out, SB + O_OUT + k * B_SLOT, col + k * 64, row);
    }
    asm volatile("cp.async.bulk.commit_group;" ::: "memory");
    asm volatile("cp.async.bulk.wait_group.read 0;" ::: "memory");
    mbar_arrive2_if0(BAR_GEMPTY + 16, 0);
    mbar_wait(bud, BAR_GFULL + 16, 0);
    for (int k = 3; k < 5; k++) {
      mbar_wait(bud, BAR_GOUT + k * 8, 0);
      tma_store2d(&p.out, SB + O_OUT + k * B_SLOT, col + k * 64, row);
      asm volatile("cp.async.bulk.commit_group;" ::: "memory");
      asm volatile("cp.async.bulk.wait_group.read 0;" ::: "memory");
      __nanosleep(1000);
    }
  }
  mbar_wait_sleep(bud, BAR_GOUT + 24, job.part == 0, SL_S);
#pragma unroll 1
  for (int i = 0; i < 5; i++) {
    const int k = (0x21043 >> (4 * i)) & 15;
    mbar_wait(bud, BAR_GOUT + k * 8, job.part == 0);
    if (i == 0) TLE(0);
    for (int q = 1; q < 4; q++) {
      const int sh = (job.part + q) & 3;
      tma_store2d(&p.part, SB + O_OUT + k * B_SLOT + sh * 5120, col + k * 64, job.part * NB * SQ + row + sh * 40);
    }
  }
  asm volatile("cp.async.bulk.commit_group;" ::: "memory");
  TLE(1);
  asm volatile("cp.async.bulk.wait_group 0;" ::: "memory");
  TLE(2);
  asm volatile("fence.proxy.async.global;" ::: "memory");
  asm volatile("red.release.gpu.global.add.s32 [%0], 1;" ::"l"(&g_pcnt[job.tile * 4 + job.part]) : "memory");
  TLE(3);
}

__global__ void __launch_bounds__(384, 1) fused_kernel(const __grid_constant__ Params p) {
  extern __shared__ __align__(1024) char smem_raw[];
  if ((smem_u32(smem_raw) & 0xFFFFFFu) != SB) return;
  const int cta = (((blockIdx.x / PERM_G) * PERM_M) % (NCTA / PERM_G)) * PERM_G + (blockIdx.x % PERM_G);
  const int warp = __shfl_sync(0xffffffffu, threadIdx.x >> 5, 0);
  if (threadIdx.x == 0) {
    for (int i = 0; i < NSLOT; i++) { mbar_init(BAR_FULLA + i * 8, 1); mbar_init(BAR_EMPTYA + i * 8, 2); mbar_init(BAR_EMPTYB + i * 8, 2); }
    proxy_fence();
    if (start_delay(cta) == 0) {
#pragma unroll 1
      for (int c = 0; c < NSLOT; c++) {
        mbar_expect(BAR_FULLA + c * 8, A_SLOT + B_SLOT);
        tma3d(A_ADDR(c), &p.wq[0], BAR_FULLA + c * 8, 0, c * 64, (cta >> 4) * 3);
        tma2d(B_ADDR(c), &p.x[0], BAR_FULLA + c * 8, c * 64, (cta & 15) * SQ);
      }
    }
  }
  if (threadIdx.x == 64) {
    mbar_init(BAR_XDONE, 1); mbar_init(BAR_QH, 4); mbar_init(BAR_QM, 4);
    mbar_init(BAR_PFULL, 4); mbar_init(BAR_PFULL + 8, 4); mbar_init(BAR_PFREE, 3); mbar_init(BAR_PFREE + 8, 3);
    mbar_init(BAR_LFULL, 3); mbar_init(BAR_PMID, 4); mbar_init(BAR_PMID + 8, 4); mbar_init(BAR_OFULL, 8);
  }
  if (threadIdx.x == 96) {
    for (int i = 0; i < O_NST; i++) { mbar_init(BAR_GFULL + i * 8, 1); mbar_init(BAR_GEMPTY + i * 8, 2); }
    for (int i = 0; i < 5; i++) mbar_init(BAR_GOUT + i * 8, i == 2 ? 8 : 4);
    mbar_init(BAR_GRED, 1); mbar_init(BAR_GRED + 8, 1); mbar_init(BAR_GRED + 16, 1); mbar_init(BAR_FREE, 2);
    proxy_fence();
  }
  if (warp == 1 && threadIdx.x < 32 + 12) asm volatile("prefetch.tensormap [%0];" ::"l"(&p.x[0] + (threadIdx.x - 32)) : "memory");
  __syncthreads();
  if (warp >= 8) {
    asm volatile("setmaxnreg.dec.sync.aligned.u32 40;");
    if (warp == 8) {
      if (elect_one()) {
        const OJob job = get_ojob(cta, attn_producer(p, cta));
        const int epoch = *(volatile int*)&g_epoch[cta];
        *(volatile int*)&g_epoch[cta] = epoch + 1;
        if (job.n) oproj_producer(p, job, epoch + 1);
      }
    } else {
      const int epoch = __shfl_sync(0xffffffffu, *(volatile int*)&g_epoch[cta], 0);
      attn_helper(p, warp - 9, cta, epoch);
      if (warp == 9) {
        const OJob job = get_ojob(cta, next_item());
        if (job.n && elect_one()) oproj_storer(p, job);
      }
    }
  } else {
    asm volatile("setmaxnreg.inc.sync.aligned.u32 232;");
    if (warp < 4) {
      const OJob job = get_ojob(cta, attn_consumer<0>(p.dsw, cta));
      if (job.n) oproj_consumer<0>(p, job);
    } else {
      const OJob job = get_ojob(cta, attn_consumer<1>(p.dsw, cta));
      if (job.n) oproj_consumer<1>(p, job);
    }
  }
}

typedef CUresult (*EncodeFn)(CUtensorMap*, CUtensorMapDataType, cuuint32_t, void*, const cuuint64_t*, const cuuint64_t*, const cuuint32_t*,
                             const cuuint32_t*, CUtensorMapInterleave, CUtensorMapSwizzle, CUtensorMapL2promotion, CUtensorMapFloatOOBfill);

void make3d(EncodeFn enc, CUtensorMap* m, const void* ptr, uint64_t rows, uint64_t cols, uint32_t box_rows, uint32_t box_blocks,
            CUtensorMapL2promotion promo = CU_TENSOR_MAP_L2_PROMOTION_L2_128B) {
  cuuint64_t gd[3] = {64, rows, cols / 64};
  cuuint64_t gs[2] = {cols * 2, 128};
  cuuint32_t bd[3] = {64, box_rows, box_blocks}, es[3] = {1, 1, 1};
  enc(m, CU_TENSOR_MAP_DATA_TYPE_BFLOAT16, 3, (void*)ptr, gd, gs, bd, es, CU_TENSOR_MAP_INTERLEAVE_NONE, CU_TENSOR_MAP_SWIZZLE_128B,
      promo, CU_TENSOR_MAP_FLOAT_OOB_FILL_NONE);
}
void make2d(EncodeFn enc, CUtensorMap* m, const void* ptr, uint64_t rows, uint64_t cols, uint32_t box_rows) {
  cuuint64_t gd[2] = {cols, rows};
  cuuint64_t gs[1] = {cols * 2};
  cuuint32_t bd[2] = {64, box_rows}, es[2] = {1, 1};
  enc(m, CU_TENSOR_MAP_DATA_TYPE_BFLOAT16, 2, (void*)ptr, gd, gs, bd, es, CU_TENSOR_MAP_INTERLEAVE_NONE, CU_TENSOR_MAP_SWIZZLE_128B,
      CU_TENSOR_MAP_L2_PROMOTION_L2_128B, CU_TENSOR_MAP_FLOAT_OOB_FILL_NONE);
}

}

extern "C" void kernel_launch(void* const* d_in, const int* in_sizes, int n_in, void* d_out, int out_size) {
  static EncodeFn enc = nullptr;
  static void* part = nullptr;
  if (!enc) {
    cudaGetSymbolAddress(&part, g_part);
    cudaDriverEntryPointQueryResult qr;
    cudaGetDriverEntryPoint("cuTensorMapEncodeTiled", (void**)&enc, cudaEnableDefault, &qr);
    cudaFuncSetAttribute(fused_kernel, cudaFuncAttributeMaxDynamicSharedMemorySize, SMEM_BYTES);
  }
  Params p;
  for (int s = 0; s < 2; s++) {
    make2d(enc, &p.x[s], d_in[5 * s + 0], NB * SQ, DM, SQ);
    make3d(enc, &p.k[s], d_in[5 * s + 1], (uint64_t)NB * NH * SK, DH, 64, 3);
    make3d(enc, &p.v[s], d_in[5 * s + 2], (uint64_t)NB * NH * SK, DH, 64, 3);
    make3d(enc, &p.wq[s], d_in[5 * s + 3], DM, NH * DH, 64, 3);
    make3d(enc, &p.wo[s], d_in[5 * s + 4], NH * DH, DM, 64, 5);
    p.xp[s] = (const __nv_bfloat16*)d_in[5 * s + 0];
    p.wqp[s] = (const __nv_bfloat16*)d_in[5 * s + 3];
    p.kp[s] = (const __nv_bfloat16*)d_in[5 * s + 1];
    p.vp[s] = (const __nv_bfloat16*)d_in[5 * s + 2];
  }
  make2d(enc, &p.out, d_out, NB * SQ, 2 * DM, SQ);
  make2d(enc, &p.part, part, 4 * NB * SQ, DM, 40);
  p.outp = (__nv_bfloat16*)d_out;
  p.dsw = DESC_SW;
  p.dso = DESC_O;
  fused_kernel<<<NCTA, 384, SMEM_BYTES>>>(p);
}
```

```cpp
#include <cuda_runtime.h>
#include <cuda_bf16.h>
#include <cuda.h>
#include <stdint.h>

#define DEBUG_TIMEOUT 0

namespace {

constexpr int SQ = 160, DM = 640, NH = 32, SK = 512, DH = 192, NB = 16;
constexpr int NITEMS = 2 * NB * NH;
constexpr int NCTA = 132, N_OCTA = 32;
constexpr int ORING = 192, OFRESH = 800, CHUNK1 = 157, LEN1 = 18, LEN2 = 13, LSLOPE1 = 4, LSLOPE2 = 4;
constexpr int SL_H = 100, SL_P = 64, SL_S = 100;
constexpr int STAG_G = 4, PERM_G = 4, STAG_A0 = 19, STAG_SLOPE = 275, PERM_M = 20, PF_N = 32, PF_WAIT = 1500, PF_GAP = 300;
constexpr int OSLOTS = ORING + NITEMS - OFRESH;
constexpr int A_SLOT = 24576, B_SLOT = 20480, NSLOT = 5;
constexpr int OFF_A = 0;
constexpr int OFF_B = NSLOT * A_SLOT;
constexpr int O_STAGE = 61440, O_AB = 40960, O_NST = 3;
constexpr int OFF_L = OFF_B + NSLOT * B_SLOT;
constexpr int OFF_BAR = OFF_L + 160 * 4;
constexpr int SMEM_BYTES = OFF_BAR + 512 + 512;
constexpr int O_OUT = 2 * O_STAGE;
static_assert(O_OUT + 5 * B_SLOT <= OFF_L, "smem layout");
constexpr uint32_t SB = 1024;
constexpr uint32_t BARS = SB + OFF_BAR;
constexpr uint32_t BAR_FULLA = BARS, BAR_EMPTYA = BARS + 40, BAR_PMID = BARS + 80, BAR_EMPTYB = BARS + 120, BAR_XDONE = BARS + 160,
                   BAR_QH = BARS + 168, BAR_QM = BARS + 96, BAR_PFULL = BARS + 184, BAR_PFREE = BARS + 200, BAR_LFULL = BARS + 216,
                   BAR_OFULL = BARS + 224, BAR_GFULL = BARS + 248, BAR_GEMPTY = BARS + 280, BAR_GOUT = BARS + 328, BAR_GRED = BARS + 368,
                   BAR_FREE = BARS + 240, NEXT_ITEM = BARS + 320;
constexpr int O_ITEM_BYTES = SQ * DH * 2;

struct alignas(64) Params {
  CUtensorMap x[2], wq[2], k[2], v[2], wo[2], out, part;
  uint64_t dsw, dso;
  __nv_bfloat16* outp;
  const __nv_bfloat16 *xp[2], *wqp[2], *kp[2], *vp[2];
};

__device__ uint4 g_o[(size_t)OSLOTS * O_ITEM_BYTES / 16];
__device__ uint4 g_part[4 * NB * SQ * DM / 8];
__device__ __align__(16) int g_pcnt[4 * N_OCTA];
__device__ int g_ready[NITEMS];
__device__ int g_done[NITEMS];
__device__ int g_ticket;
__device__ int g_go;
__device__ int g_epoch[NCTA];

#define TLE(id)
#define TLP(id)
#define TLG(id)
#define TL(id)
#define TL_FLUSH()
__device__ __forceinline__ uint32_t smem_u32(const void* p) { return (uint32_t)__cvta_generic_to_shared(p); }
__device__ __forceinline__ void wg_fence() { asm volatile("wgmma.fence.sync.aligned;" ::: "memory"); }
__device__ __forceinline__ void wg_commit() { asm volatile("wgmma.commit_group.sync.aligned;" ::: "memory"); }
template <int N> __device__ __forceinline__ void wg_wait() { asm volatile("wgmma.wait_group.sync.aligned %0;" ::"n"(N) : "memory"); }
template <int N> __device__ __forceinline__ void reg_fence(float (&d)[N]) {
#pragma unroll
  for (int i = 0; i < N; i++) asm volatile("" : "+f"(d[i])::"memory");
}
template <int N> __device__ __forceinline__ void zero_regs(float (&d)[N]) {
#pragma unroll
  for (int i = 0; i < N; i++) d[i] = 0.f;
}
__device__ __forceinline__ void proxy_fence() { asm volatile("fence.proxy.async.shared::cta;" ::: "memory"); }
__device__ __forceinline__ void mbar_init(uint32_t bar, int cnt) { asm volatile("mbarrier.init.shared::cta.b64 [%0], %1;" ::"r"(bar), "r"(cnt) : "memory"); }
__device__ __forceinline__ void mbar_arrive_if0(uint32_t bar, uint32_t sel) {
  asm volatile("{\n.reg .pred p;\nsetp.eq.u32 p, %1, 0;\n@p mbarrier.arrive.shared::cta.b64 _, [%0];\n}\n" ::"r"(bar), "r"(sel) : "memory");
}
__device__ __forceinline__ void mbar_arrive2_if0(uint32_t bar, uint32_t sel) {
  asm volatile("{\n.reg .pred p;\nsetp.eq.u32 p, %1, 0;\n@p mbarrier.arrive.shared::cta.b64 _, [%0], 2;\n}\n" ::"r"(bar), "r"(sel) : "memory");
}
__device__ __forceinline__ void mbar_expect(uint32_t bar, uint32_t bytes) {
  asm volatile("mbarrier.arrive.expect_tx.shared::cta.b64 _, [%0], %1;" ::"r"(bar), "r"(bytes) : "memory");
}
__device__ __forceinline__ void mbar_wait(int& bud, uint32_t bar, uint32_t parity) {
  asm volatile(
      "{\n.reg .pred p;\n"
      "LW:\n"
      "mbarrier.try_wait.parity.shared::cta.b64 p, [%0], %1;\n"
      "@!p bra LW;\n}\n" ::"r"(bar), "r"(parity) : "memory");
}
__device__ __forceinline__ void mbar_wait_sleep(int& bud, uint32_t bar, uint32_t parity, uint32_t ns) {
  while (true) {
    uint32_t ok;
    asm volatile("{\n.reg .pred p;\nmbarrier.try_wait.parity.shared::cta.b64 p, [%1], %2;\nselp.u32 %0, 1, 0, p;\n}\n" : "=r"(ok) : "r"(bar), "r"(parity) : "memory");
    if (ok || (DEBUG_TIMEOUT && --bud <= 0)) break;
    __nanosleep(ns);
  }
}
constexpr int WAIT_BUDGET = 1 << 22;
__device__ __forceinline__ bool elect_one() {
  uint32_t p;
  asm volatile("{\n.reg .pred p;\nelect.sync _|p, 0xffffffff;\nselp.u32 %0, 1, 0, p;\n}\n" : "=r"(p));
  return p;
}
__device__ __forceinline__ void tma2d(uint32_t dst, const CUtensorMap* m, uint32_t bar, int c0, int c1) {
  asm volatile("cp.async.bulk.tensor.2d.shared::cluster.global.mbarrier::complete_tx::bytes [%0], [%1, {%3, %4}], [%2];"
               ::"r"(dst), "l"(m), "r"(bar), "r"(c0), "r"(c1) : "memory");
}
__device__ __forceinline__ void tma3d(uint32_t dst, const CUtensorMap* m, uint32_t bar, int c0, int c1, int c2) {
  asm volatile("cp.async.bulk.tensor.3d.shared::cluster.global.mbarrier::complete_tx::bytes [%0], [%1, {%3, %4, %5}], [%2];"
               ::"r"(dst), "l"(m), "r"(bar), "r"(c0), "r"(c1), "r"(c2) : "memory");
}
__device__ __forceinline__ void tma3d_hint(uint32_t dst, const CUtensorMap* m, uint32_t bar, int c0, int c1, int c2, uint64_t pol) {
  asm volatile("cp.async.bulk.tensor.3d.shared::cluster.global.mbarrier::complete_tx::bytes.L2::cache_hint [%0], [%1, {%3, %4, %5}], [%2], %6;"
               ::"r"(dst), "l"(m), "r"(bar), "r"(c0), "r"(c1), "r"(c2), "l"(pol) : "memory");
}
__device__ __forceinline__ void tma_store2d(const CUtensorMap* m, uint32_t src, int c0, int c1) {
  asm volatile("cp.async.bulk.tensor.2d.global.shared::cta.bulk_group [%0, {%2, %3}], [%1];" ::"l"(m), "r"(src), "r"(c0), "r"(c1) : "memory");
}
__device__ __forceinline__ void bar_sync(int id, int n) { asm volatile("bar.sync %0, %1;" ::"r"(id), "r"(n) : "memory"); }
__device__ __forceinline__ void bar_arrive(int id, int n) { asm volatile("bar.arrive %0, %1;" ::"r"(id), "r"(n) : "memory"); }
__device__ __forceinline__ float ex2(float x) { float y; asm("ex2.approx.ftz.f32 %0, %1;" : "=f"(y) : "f"(x)); return y; }
__device__ __forceinline__ uint32_t pack2(float lo, float hi) { uint32_t r; asm("cvt.rn.bf16x2.f32 %0, %1, %2;" : "=r"(r) : "f"(hi), "f"(lo)); return r; }
__device__ __forceinline__ void stsm_t(uint32_t a, uint32_t r0, uint32_t r1, uint32_t r2, uint32_t r3) {
  asm volatile("stmatrix.sync.aligned.m8n8.x4.trans.shared.b16 [%0], {%1,%2,%3,%4};" ::"r"(a), "r"(r0), "r"(r1), "r"(r2), "r"(r3) : "memory");
}
__device__ __forceinline__ uint64_t evict_first_policy() {
  uint64_t pol;
  asm volatile("createpolicy.fractional.L2::evict_first.b64 %0, 1.0;" : "=l"(pol));
  return pol;
}
__device__ __forceinline__ void bulk_load_hint(uint32_t dst, const void* src, uint32_t bytes, uint32_t bar, uint64_t pol) {
  asm volatile("cp.async.bulk.shared::cluster.global.mbarrier::complete_tx::bytes.L2::cache_hint [%0], [%1], %2, [%3], %4;"
               ::"r"(dst), "l"(src), "r"(bytes), "r"(bar), "l"(pol) : "memory");
}
__device__ __forceinline__ void flag_wait(int& bud, const int* p, int target) {
  while (true) {
    int v;
    asm volatile("ld.acquire.gpu.global.s32 %0, [%1];" : "=r"(v) : "l"(p) : "memory");
    if (v - target >= 0 || --bud <= 0) break;
    __nanosleep(64);
  }
}
constexpr uint64_t DESC_SW = 0x4000004000010000ull, DESC_O = 0xC000001000800000ull;
__device__ __forceinline__ uint32_t tid_x() { uint32_t t; asm volatile("mov.u32 %0, %tid.x;" : "=r"(t)); return t; }

template <int TA, int TB, uint32_t OA, uint32_t OB>
__device__ __forceinline__ void mma160(float (&d)[80], uint64_t ba, uint32_t la, uint64_t bb, uint32_t lb) {
  asm volatile(
      "{\n.reg .pred p;\n.reg .b64 da, db;\nsetp.eq.b32 p, 0, 0;\n"
      "mad.wide.u32 da, %80, 192, %86;\nadd.s64 da, da, %84;\nmad.wide.u32 db, %81, 1, %87;\nadd.s64 db, db, %85;\n"
      "wgmma.mma_async.sync.aligned.m64n160k16.f32.bf16.bf16 {"
      "%0,%1,%2,%3,%4,%5,%6,%7,%8,%9,%10,%11,%12,%13,%14,%15,%16,%17,%18,%19,%20,%21,%22,%23,%24,%25,%26,%27,%28,%29,%30,%31,%32,%33,%34,%35,%36,"
      "%37,%38,%39,%40,%41,%42,%43,%44,%45,%46,%47,%48,%49,%50,%51,%52,%53,%54,%55,%56,%57,%58,%59,%60,%61,%62,%63,%64,%65,%66,%67,%68,%69,%70,%71,"
      "%72,%73,%74,%75,%76,%77,%78,%79"
      "}, da, db, p, 1, 1, %82, %83;\n}\n"
      :
      "+f"(d[0]),"+f"(d[1]),"+f"(d[2]),"+f"(d[3]),"+f"(d[4]),"+f"(d[5]),"+f"(d[6]),"+f"(d[7]),"+f"(d[8]),"+f"(d[9]),"+f"(d[10]),"+f"(d[11]),
      "+f"(d[12]),"+f"(d[13]),"+f"(d[14]),"+f"(d[15]),"+f"(d[16]),"+f"(d[17]),"+f"(d[18]),"+f"(d[19]),"+f"(d[20]),"+f"(d[21]),"+f"(d[22]),
      "+f"(d[23]),"+f"(d[24]),"+f"(d[25]),"+f"(d[26]),"+f"(d[27]),"+f"(d[28]),"+f"(d[29]),"+f"(d[30]),"+f"(d[31]),"+f"(d[32]),"+f"(d[33]),
      "+f"(d[34]),"+f"(d[35]),"+f"(d[36]),"+f"(d[37]),"+f"(d[38]),"+f"(d[39]),"+f"(d[40]),"+f"(d[41]),"+f"(d[42]),"+f"(d[43]),"+f"(d[44]),
      "+f"(d[45]),"+f"(d[46]),"+f"(d[47]),"+f"(d[48]),"+f"(d[49]),"+f"(d[50]),"+f"(d[51]),"+f"(d[52]),"+f"(d[53]),"+f"(d[54]),"+f"(d[55]),
      "+f"(d[56]),"+f"(d[57]),"+f"(d[58]),"+f"(d[59]),"+f"(d[60]),"+f"(d[61]),"+f"(d[62]),"+f"(d[63]),"+f"(d[64]),"+f"(d[65]),"+f"(d[66]),
      "+f"(d[67]),"+f"(d[68]),"+f"(d[69]),"+f"(d[70]),"+f"(d[71]),"+f"(d[72]),"+f"(d[73]),"+f"(d[74]),"+f"(d[75]),"+f"(d[76]),"+f"(d[77]),
      "+f"(d[78]),"+f"(d[79])
      : "r"(la), "r"(lb), "n"(TA), "n"(TB), "n"((SB + OA) >> 4), "n"(OB >> 4), "l"(ba), "l"(bb));
}

template <int TA, int TB, uint32_t OA, uint32_t OB>
__device__ __forceinline__ void mma160z(float (&d)[80], uint64_t ba, uint32_t la, uint64_t bb, uint32_t lb) {
  asm volatile(
      "{\n.reg .pred p;\n.reg .b64 da, db;\nsetp.ne.b32 p, 0, 0;\n"
      "mad.wide.u32 da, %80, 192, %86;\nadd.s64 da, da, %84;\nmad.wide.u32 db, %81, 1, %87;\nadd.s64 db, db, %85;\n"
      "wgmma.mma_async.sync.aligned.m64n160k16.f32.bf16.bf16 {"
      "%0,%1,%2,%3,%4,%5,%6,%7,%8,%9,%10,%11,%12,%13,%14,%15,%16,%17,%18,%19,%20,%21,%22,%23,%24,%25,%26,%27,%28,%29,%30,%31,%32,%33,%34,%35,%36,"
      "%37,%38,%39,%40,%41,%42,%43,%44,%45,%46,%47,%48,%49,%50,%51,%52,%53,%54,%55,%56,%57,%58,%59,%60,%61,%62,%63,%64,%65,%66,%67,%68,%69,%70,%71,"
      "%72,%73,%74,%75,%76,%77,%78,%79"
      "}, da, db, p, 1, 1, %82, %83;\n}\n"
      :
      "=f"(d[0]),"=f"(d[1]),"=f"(d[2]),"=f"(d[3]),"=f"(d[4]),"=f"(d[5]),"=f"(d[6]),"=f"(d[7]),"=f"(d[8]),"=f"(d[9]),"=f"(d[10]),"=f"(d[11]),
      "=f"(d[12]),"=f"(d[13]),"=f"(d[14]),"=f"(d[15]),"=f"(d[16]),"=f"(d[17]),"=f"(d[18]),"=f"(d[19]),"=f"(d[20]),"=f"(d[21]),"=f"(d[22]),
      "=f"(d[23]),"=f"(d[24]),"=f"(d[25]),"=f"(d[26]),"=f"(d[27]),"=f"(d[28]),"=f"(d[29]),"=f"(d[30]),"=f"(d[31]),"=f"(d[32]),"=f"(d[33]),
      "=f"(d[34]),"=f"(d[35]),"=f"(d[36]),"=f"(d[37]),"=f"(d[38]),"=f"(d[39]),"=f"(d[40]),"=f"(d[41]),"=f"(d[42]),"=f"(d[43]),"=f"(d[44]),
      "=f"(d[45]),"=f"(d[46]),"=f"(d[47]),"=f"(d[48]),"=f"(d[49]),"=f"(d[50]),"=f"(d[51]),"=f"(d[52]),"=f"(d[53]),"=f"(d[54]),"=f"(d[55]),
      "=f"(d[56]),"=f"(d[57]),"=f"(d[58]),"=f"(d[59]),"=f"(d[60]),"=f"(d[61]),"=f"(d[62]),"=f"(d[63]),"=f"(d[64]),"=f"(d[65]),"=f"(d[66]),
      "=f"(d[67]),"=f"(d[68]),"=f"(d[69]),"=f"(d[70]),"=f"(d[71]),"=f"(d[72]),"=f"(d[73]),"=f"(d[74]),"=f"(d[75]),"=f"(d[76]),"=f"(d[77]),
      "=f"(d[78]),"=f"(d[79])
      : "r"(la), "r"(lb), "n"(TA), "n"(TB), "n"((SB + OA) >> 4), "n"(OB >> 4), "l"(ba), "l"(bb));
}

template <int TA, int TB, uint32_t OA, uint32_t OB>
__device__ __forceinline__ void mma80(float (&d)[40], uint64_t ba, uint32_t la, uint64_t bb, uint32_t lb) {
  asm volatile(
      "{\n.reg .pred p;\n.reg .b64 da, db;\nsetp.eq.b32 p, 0, 0;\n"
      "mad.wide.u32 da, %40, 192, %46;\nadd.s64 da, da, %44;\nmad.wide.u32 db, %41, 1, %47;\nadd.s64 db, db, %45;\n"
      "wgmma.mma_async.sync.aligned.m64n80k16.f32.bf16.bf16 {"
      "%0,%1,%2,%3,%4,%5,%6,%7,%8,%9,%10,%11,%12,%13,%14,%15,%16,%17,%18,%19,%20,%21,%22,%23,%24,%25,%26,%27,%28,%29,%30,%31,%32,%33,%34,%35,%36,"
      "%37,%38,%39"
      "}, da, db, p, 1, 1, %42, %43;\n}\n"
      :
      "+f"(d[0]),"+f"(d[1]),"+f"(d[2]),"+f"(d[3]),"+f"(d[4]),"+f"(d[5]),"+f"(d[6]),"+f"(d[7]),"+f"(d[8]),"+f"(d[9]),"+f"(d[10]),"+f"(d[11]),
      "+f"(d[12]),"+f"(d[13]),"+f"(d[14]),"+f"(d[15]),"+f"(d[16]),"+f"(d[17]),"+f"(d[18]),"+f"(d[19]),"+f"(d[20]),"+f"(d[21]),"+f"(d[22]),
      "+f"(d[23]),"+f"(d[24]),"+f"(d[25]),"+f"(d[26]),"+f"(d[27]),"+f"(d[28]),"+f"(d[29]),"+f"(d[30]),"+f"(d[31]),"+f"(d[32]),"+f"(d[33]),
      "+f"(d[34]),"+f"(d[35]),"+f"(d[36]),"+f"(d[37]),"+f"(d[38]),"+f"(d[39])
      : "r"(la), "r"(lb), "n"(TA), "n"(TB), "n"((SB + OA) >> 4), "n"(OB >> 4), "l"(ba), "l"(bb));
}

template <int TA, int TB, uint32_t OA, uint32_t OB>
__device__ __forceinline__ void mma80z(float (&d)[40], uint64_t ba, uint32_t la, uint64_t bb, uint32_t lb) {
  asm volatile(
      "{\n.reg .pred p;\n.reg .b64 da, db;\nsetp.ne.b32 p, 0, 0;\n"
      "mad.wide.u32 da, %40, 192, %46;\nadd.s64 da, da, %44;\nmad.wide.u32 db, %41, 1, %47;\nadd.s64 db, db, %45;\n"
      "wgmma.mma_async.sync.aligned.m64n80k16.f32.bf16.bf16 {"
      "%0,%1,%2,%3,%4,%5,%6,%7,%8,%9,%10,%11,%12,%13,%14,%15,%16,%17,%18,%19,%20,%21,%22,%23,%24,%25,%26,%27,%28,%29,%30,%31,%32,%33,%34,%35,%36,"
      "%37,%38,%39"
      "}, da, db, p, 1, 1, %42, %43;\n}\n"
      :
      "=f"(d[0]),"=f"(d[1]),"=f"(d[2]),"=f"(d[3]),"=f"(d[4]),"=f"(d[5]),"=f"(d[6]),"=f"(d[7]),"=f"(d[8]),"=f"(d[9]),"=f"(d[10]),"=f"(d[11]),
      "=f"(d[12]),"=f"(d[13]),"=f"(d[14]),"=f"(d[15]),"=f"(d[16]),"=f"(d[17]),"=f"(d[18]),"=f"(d[19]),"=f"(d[20]),"=f"(d[21]),"=f"(d[22]),
      "=f"(d[23]),"=f"(d[24]),"=f"(d[25]),"=f"(d[26]),"=f"(d[27]),"=f"(d[28]),"=f"(d[29]),"=f"(d[30]),"=f"(d[31]),"=f"(d[32]),"=f"(d[33]),
      "=f"(d[34]),"=f"(d[35]),"=f"(d[36]),"=f"(d[37]),"=f"(d[38]),"=f"(d[39])
      : "r"(la), "r"(lb), "n"(TA), "n"(TB), "n"((SB + OA) >> 4), "n"(OB >> 4), "l"(ba), "l"(bb));
}

template <int TA, int TB, uint32_t OA, uint32_t OB>
__device__ __forceinline__ void mma160r(float (&d)[80], uint64_t ba, uint32_t la, uint64_t bb, uint32_t lb, int sc) {
  asm volatile(
      "{\n.reg .pred p;\n.reg .b64 da, db;\nsetp.ne.b32 p, %88, 0;\n"
      "mad.wide.u32 da, %80, 3840, %86;\nadd.s64 da, da, %84;\nmad.wide.u32 db, %81, 3840, %87;\nadd.s64 db, db, %85;\n"
      "wgmma.mma_async.sync.aligned.m64n160k16.f32.bf16.bf16 {"
      "%0,%1,%2,%3,%4,%5,%6,%7,%8,%9,%10,%11,%12,%13,%14,%15,%16,%17,%18,%19,%20,%21,%22,%23,%24,%25,%26,%27,%28,%29,%30,%31,%32,%33,%34,%35,%36,"
      "%37,%38,%39,%40,%41,%42,%43,%44,%45,%46,%47,%48,%49,%50,%51,%52,%53,%54,%55,%56,%57,%58,%59,%60,%61,%62,%63,%64,%65,%66,%67,%68,%69,%70,%71,"
      "%72,%73,%74,%75,%76,%77,%78,%79"
      "}, da, db, p, 1, 1, %82, %83;\n}\n"
      :
      "+f"(d[0]),"+f"(d[1]),"+f"(d[2]),"+f"(d[3]),"+f"(d[4]),"+f"(d[5]),"+f"(d[6]),"+f"(d[7]),"+f"(d[8]),"+f"(d[9]),"+f"(d[10]),"+f"(d[11]),
      "+f"(d[12]),"+f"(d[13]),"+f"(d[14]),"+f"(d[15]),"+f"(d[16]),"+f"(d[17]),"+f"(d[18]),"+f"(d[19]),"+f"(d[20]),"+f"(d[21]),"+f"(d[22]),
      "+f"(d[23]),"+f"(d[24]),"+f"(d[25]),"+f"(d[26]),"+f"(d[27]),"+f"(d[28]),"+f"(d[29]),"+f"(d[30]),"+f"(d[31]),"+f"(d[32]),"+f"(d[33]),
      "+f"(d[34]),"+f"(d[35]),"+f"(d[36]),"+f"(d[37]),"+f"(d[38]),"+f"(d[39]),"+f"(d[40]),"+f"(d[41]),"+f"(d[42]),"+f"(d[43]),"+f"(d[44]),
      "+f"(d[45]),"+f"(d[46]),"+f"(d[47]),"+f"(d[48]),"+f"(d[49]),"+f"(d[50]),"+f"(d[51]),"+f"(d[52]),"+f"(d[53]),"+f"(d[54]),"+f"(d[55]),
      "+f"(d[56]),"+f"(d[57]),"+f"(d[58]),"+f"(d[59]),"+f"(d[60]),"+f"(d[61]),"+f"(d[62]),"+f"(d[63]),"+f"(d[64]),"+f"(d[65]),"+f"(d[66]),
      "+f"(d[67]),"+f"(d[68]),"+f"(d[69]),"+f"(d[70]),"+f"(d[71]),"+f"(d[72]),"+f"(d[73]),"+f"(d[74]),"+f"(d[75]),"+f"(d[76]),"+f"(d[77]),
      "+f"(d[78]),"+f"(d[79])
      : "r"(la), "r"(lb), "n"(TA), "n"(TB), "n"((SB + OA) >> 4), "n"(OB >> 4), "l"(ba), "l"(bb), "r"(sc));
}

template <int TA, int TB, uint32_t OA, uint32_t OB>
__device__ __forceinline__ void mma80r(float (&d)[40], uint64_t ba, uint32_t la, uint64_t bb, uint32_t lb, int sc) {
  asm volatile(
      "{\n.reg .pred p;\n.reg .b64 da, db;\nsetp.ne.b32 p, %48, 0;\n"
      "mad.wide.u32 da, %40, 3840, %46;\nadd.s64 da, da, %44;\nmad.wide.u32 db, %41, 3840, %47;\nadd.s64 db, db, %45;\n"
      "wgmma.mma_async.sync.aligned.m64n80k16.f32.bf16.bf16 {"
      "%0,%1,%2,%3,%4,%5,%6,%7,%8,%9,%10,%11,%12,%13,%14,%15,%16,%17,%18,%19,%20,%21,%22,%23,%24,%25,%26,%27,%28,%29,%30,%31,%32,%33,%34,%35,%36,"
      "%37,%38,%39"
      "}, da, db, p, 1, 1, %42, %43;\n}\n"
      :
      "+f"(d[0]),"+f"(d[1]),"+f"(d[2]),"+f"(d[3]),"+f"(d[4]),"+f"(d[5]),"+f"(d[6]),"+f"(d[7]),"+f"(d[8]),"+f"(d[9]),"+f"(d[10]),"+f"(d[11]),
      "+f"(d[12]),"+f"(d[13]),"+f"(d[14]),"+f"(d[15]),"+f"(d[16]),"+f"(d[17]),"+f"(d[18]),"+f"(d[19]),"+f"(d[20]),"+f"(d[21]),"+f"(d[22]),
      "+f"(d[23]),"+f"(d[24]),"+f"(d[25]),"+f"(d[26]),"+f"(d[27]),"+f"(d[28]),"+f"(d[29]),"+f"(d[30]),"+f"(d[31]),"+f"(d[32]),"+f"(d[33]),
      "+f"(d[34]),"+f"(d[35]),"+f"(d[36]),"+f"(d[37]),"+f"(d[38]),"+f"(d[39])
      : "r"(la), "r"(lb), "n"(TA), "n"(TB), "n"((SB + OA) >> 4), "n"(OB >> 4), "l"(ba), "l"(bb), "r"(sc));
}

struct Ring { uint32_t o[NSLOT], m; };
__device__ __forceinline__ void ring_pos(const Ring& r, int i, uint32_t& slot8, uint32_t& ph) {
  slot8 = r.o[i % NSLOT];
  ph = r.m >> (i % (2 * NSLOT));
}
__device__ __forceinline__ void ring_advance(Ring& r, int n) {
  Ring t = r;
#pragma unroll
  for (int k = 0; k < NSLOT; k++) r.o[k] = t.o[(k + n) % NSLOT];
  r.m = ((t.m >> (n % (2 * NSLOT))) & 1023) * 1025;
}
__host__ __device__ constexpr int idxK(int j) { return j == 0 ? 10 : 9 + 2 * j; }
__host__ __device__ constexpr int idxV(int j) { return j == 7 ? 25 : 12 + 2 * j; }
__host__ __device__ constexpr int xs(int c) { return c % NSLOT; }

__device__ __forceinline__ int start_delay(int cta) {
  return max(0, ((cta - N_OCTA) | (STAG_G - 1)) - STAG_A0) * STAG_SLOPE;
}
__device__ __forceinline__ char* o_slot(int item) {
  return (char*)g_o + (size_t)(item < OFRESH ? item % ORING : item - OFRESH + ORING) * O_ITEM_BYTES;
}
__device__ __forceinline__ int next_item(uint32_t a = NEXT_ITEM) {
  int v;
  asm volatile("ld.shared.s32 %0, [%1];" : "=r"(v) : "r"(a) : "memory");
  return __shfl_sync(0xffffffffu, v, 0);
}

template <int W, bool ACC>
__device__ __forceinline__ void mma_main(uint64_t ds, float (&d)[80], uint32_t la, uint32_t baddr) {
  const uint32_t lb = baddr >> 4;
  if (ACC) mma160<1, 0, W * 16384, 0>(d, ds, la, ds, lb); else mma160z<1, 0, W * 16384, 0>(d, ds, la, ds, lb);
  mma160<1, 0, W * 16384 + 1 * 2048, 1 * 32>(d, ds, la, ds, lb);
  mma160<1, 0, W * 16384 + 2 * 2048, 2 * 32>(d, ds, la, ds, lb);
  mma160<1, 0, W * 16384 + 3 * 2048, 3 * 32>(d, ds, la, ds, lb);
}
template <int W, bool ACC>
__device__ __forceinline__ void mma_mid(uint64_t ds, float (&d)[40], uint32_t la, uint32_t baddr) {
  const uint32_t lb = baddr >> 4;
  if (ACC) mma80<1, 0, 8192, W * 10240>(d, ds, la, ds, lb); else mma80z<1, 0, 8192, W * 10240>(d, ds, la, ds, lb);
  mma80<1, 0, 8192 + 1 * 2048, W * 10240 + 1 * 32>(d, ds, la, ds, lb);
  mma80<1, 0, 8192 + 2 * 2048, W * 10240 + 2 * 32>(d, ds, la, ds, lb);
  mma80<1, 0, 8192 + 3 * 2048, W * 10240 + 3 * 32>(d, ds, la, ds, lb);
}
template <int W, bool ACC>
__device__ __forceinline__ void mma_both(uint64_t ds, float (&dm)[80], float (&dh)[40], uint32_t la, uint32_t baddr) {
  mma_mid<W, ACC>(ds, dh, la, baddr);
  mma_main<W, ACC>(ds, dm, la, baddr);
}
template <int KB, bool ACC>
__device__ __forceinline__ void s_mma(uint64_t ds, float (&sacc)[80], uint32_t la) {
  const uint32_t lb = (SB + OFF_B) >> 4;
  if (ACC) mma160<0, 0, KB * 8192, KB * B_SLOT>(sacc, ds, la, ds, lb); else mma160z<0, 0, KB * 8192, KB * B_SLOT>(sacc, ds, la, ds, lb);
  mma160<0, 0, KB * 8192 + 32, KB * B_SLOT + 32>(sacc, ds, la, ds, lb);
  mma160<0, 0, KB * 8192 + 64, KB * B_SLOT + 64>(sacc, ds, la, ds, lb);
  mma160<0, 0, KB * 8192 + 96, KB * B_SLOT + 96>(sacc, ds, la, ds, lb);
}
template <int N>
__device__ __forceinline__ void store_scaled(uint32_t addr, const float (&d)[N], float sc) {
#pragma unroll
  for (int J = 0; J < N / 8; J++)
    stsm_t(addr + J * 2048, pack2(d[8 * J] * sc, d[8 * J + 1] * sc), pack2(d[8 * J + 2] * sc, d[8 * J + 3] * sc),
           pack2(d[8 * J + 4] * sc, d[8 * J + 5] * sc), pack2(d[8 * J + 6] * sc, d[8 * J + 7] * sc));
}
__device__ __forceinline__ float4 lds_f4(uint32_t a) {
  float4 v;
  asm volatile("ld.shared.v4.f32 {%0,%1,%2,%3}, [%4];" : "=f"(v.x), "=f"(v.y), "=f"(v.z), "=f"(v.w) : "r"(a) : "memory");
  return v;
}
__device__ __forceinline__ void norm_pack(uint32_t* p, const float* d, const float4& i) {
  p[0] = pack2(d[0] * i.x, d[1] * i.y); p[1] = pack2(d[4] * i.z, d[5] * i.w);
  p[2] = pack2(d[2] * i.x, d[3] * i.y); p[3] = pack2(d[6] * i.z, d[7] * i.w);
  asm volatile("" : "+r"(p[0]), "+r"(p[1]), "+r"(p[2]), "+r"(p[3])::"memory");
}
template <int W>
__device__ __forceinline__ void pack_first(uint32_t (&pk)[60], const float (&om)[80], const float (&oh)[40], uint32_t laddr) {
  float4 n0 = lds_f4(laddr + W * 80), n1 = lds_f4(laddr + W * 80 + 16);
#pragma unroll
  for (int J = 0; J < 5; J++) {
    const float4 i = n0;
    n0 = n1;
    if (J + 2 < 5) n1 = lds_f4(laddr + W * 80 + (J + 2) * 16);
    norm_pack(&pk[20 + 4 * J], &om[8 * (5 * W + J)], i);
    norm_pack(&pk[4 * J], &oh[8 * J], i);
  }
}
template <int W, int J0, int J1>
__device__ __forceinline__ void pack_second(uint32_t (&pk)[60], const float (&om)[80], uint32_t laddr) {
  float4 n[J1 - J0];
#pragma unroll
  for (int J = J0; J < J1; J++) n[J - J0] = lds_f4(laddr + (1 - W) * 80 + J * 16);
#pragma unroll
  for (int J = J0; J < J1; J++) norm_pack(&pk[40 + 4 * J], &om[8 * (5 * (1 - W) + J)], n[J - J0]);
}
__device__ __forceinline__ char* o_ptr(int item) {
  const uint32_t t = tid_x();
  return o_slot(item) + ((t & 96) * 16 + (t & 28) * 8 + ((((t >> 1) ^ (t >> 4)) & 1) << 4) + (t & 1) * 8);
}
template <int W, int G0, int G1>
__device__ __forceinline__ void store_groups(char* op, const uint32_t (&pk)[60], uint32_t on) {
#pragma unroll
  for (int G = G0; G < G1; G++) {
    const int off = (G < 5 ? 1 : 2 * W) * B_SLOT + (5 * (G < 10 ? W : 1 - W) + G % 5) * 2048;
    asm volatile("{\n.reg .pred p;\nsetp.ne.u32 p, %5, 0;\n@p st.global.v2.b32 [%0], {%1, %2};\n@p st.global.v2.b32 [%0+256], {%3, %4};\n}\n"
                 ::"l"(op + off), "r"(pk[4 * G]), "r"(pk[4 * G + 1]), "r"(pk[4 * G + 2]), "r"(pk[4 * G + 3]), "r"(on) : "memory");
  }
}
__device__ __forceinline__ void publish_generic(uint32_t bar, int lane) {
  __syncwarp();
  mbar_arrive_if0(bar, lane);
}
__device__ __forceinline__ void publish(uint32_t bar, int lane) {
  proxy_fence();
  __syncwarp();
  mbar_arrive_if0(bar, lane);
}

#define A_ADDR(s) (SB + OFF_A + (s) * A_SLOT)
#define B_ADDR(s) (SB + OFF_B + (s) * B_SLOT)
#define WAIT_CHUNK(c, ro, sA)                \
  uint32_t sA;                               \
  {                                          \
    uint32_t pA_;                            \
    ring_pos(ring, (ro) + (c), sA, pA_);     \
    mbar_wait(bud, BAR_FULLA + sA, pA_); \
  }
#define RELEASE_CHUNK(c, sA)                                  \
  mbar_arrive_if0(BAR_EMPTYA + sA, tid);                \
  if ((c) < NSLOT) mbar_arrive_if0(BAR_EMPTYB + xs(c) * 8, tid);

template <int W>
__device__ __forceinline__ int attn_consumer(const uint64_t ds, int item) {
  int bud = WAIT_BUDGET;
  const int tid = threadIdx.x & 127, lane = tid & 31, warp = tid >> 5;
  const uint32_t st_off = ((lane & 7) + 8 * (lane >> 4)) * 128 + (((2 * warp + ((lane >> 3) & 1)) ^ (lane & 7)) << 4);
  const uint32_t laddr = SB + OFF_L + (lane & 3) * 160;
  float om[80], oh[40], sacc[80];
  uint32_t pk[60];
#pragma unroll
  for (int i = 0; i < 40; i++) pk[i] = 0;
  zero_regs(om);
  Ring ring{{0u, 8u, 16u, 24u, 32u}, 0x3E0u * 1025};
  uint32_t par = 0;
  int prev = 0;
  const float qscale = 0.07216878364870322f * 1.4426950408889634f;
  constexpr uint32_t pown = B_ADDR(3 + W), poth = B_ADDR(4 - W);
  TL(0); TLG(62);
  {
    WAIT_CHUNK(0, 0, s0)
    wg_fence();
    mma_both<W, false>(ds, sacc, oh, s0, B_ADDR(xs(0)));
    wg_commit();
    WAIT_CHUNK(1, 0, s1)
    wg_fence();
    mma_both<W, true>(ds, sacc, oh, s1, B_ADDR(xs(1)));
    wg_commit();
    wg_wait<1>();
    RELEASE_CHUNK(0, s0)
  }
#pragma unroll 1
  for (int it = 0;; it++) {
    char* op = o_ptr(prev);
#pragma unroll
    for (int c = 2; c < 8 - W; c++) {
      WAIT_CHUNK(c, 0, sA)
      TL(40 + c);
      wg_fence();
      mma_both<W, true>(ds, sacc, oh, sA, B_ADDR(xs(c)));
      wg_commit();
      wg_wait<1>();
      uint32_t sP, pP;
      ring_pos(ring, c - 1, sP, pP);
      RELEASE_CHUNK(c - 1, sP)
      constexpr int NG = 3;
      if (c == 2) { pack_second<W, 0, 1>(pk, om, laddr); store_groups<W, 0 * NG, 1 * NG>(op, pk, it); }
      if (c == 3) { pack_second<W, 1, 2>(pk, om, laddr); store_groups<W, 1 * NG, 2 * NG>(op, pk, it); }
      if (c == 4) { pack_second<W, 2, 3>(pk, om, laddr); store_groups<W, 2 * NG, 3 * NG>(op, pk, it); }
      if (c == 5) { pack_second<W, 3, 4>(pk, om, laddr); store_groups<W, 3 * NG, 4 * NG>(op, pk, it); }
      if (c == 6) {
        pack_second<W, 4, 5>(pk, om, laddr);
        if (W == 1) {
          wg_wait<0>();
          RELEASE_CHUNK(6, sA)
          mbar_arrive_if0(BAR_XDONE, tid);
        }
        store_groups<W, 4 * NG, 15>(op, pk, it);
        __syncwarp();
        mbar_arrive_if0(BAR_OFULL, lane | (it == 0));
      }
    }
    uint32_t sK0, pK0, s7, p7;
    ring_pos(ring, idxK(W), sK0, pK0);
    ring_pos(ring, 7, s7, p7);
    if (W == 1) mbar_wait(bud, BAR_FULLA + s7, p7);
    WAIT_CHUNK(8, 0, s8)
    if (W == 0) {
      wg_fence();
      mma_both<W, true>(ds, sacc, oh, s8, B_ADDR(xs(8)));
      wg_commit();
      wg_wait<1>();
      RELEASE_CHUNK(7, s7)
    }
    WAIT_CHUNK(9, 0, s9)
    TL(48);
    if (W == 0) {
      wg_fence();
      mma_mid<W, true>(ds, oh, s9, B_ADDR(xs(9)));
      wg_commit();
      mma_main<W, true>(ds, sacc, s9, B_ADDR(xs(9)));
      wg_commit();
      bar_arrive(5, 256);
      TL(49);
      wg_wait<1>();
      reg_fence(oh);
      mbar_wait(bud, BAR_XDONE, par);
      store_scaled(B_ADDR(1) + st_off, oh, qscale);
    } else {
      bar_sync(5, 256);
      wg_fence();
      mma_mid<W, true>(ds, oh, s7, B_ADDR(xs(7)));
      mma_mid<W, true>(ds, oh, s8, B_ADDR(xs(8)));
      mma_mid<W, true>(ds, oh, s9, B_ADDR(xs(9)));
      wg_commit();
      mma_main<W, true>(ds, sacc, s7, B_ADDR(xs(7)));
      wg_commit();
      mma_main<W, true>(ds, sacc, s8, B_ADDR(xs(8)));
      wg_commit();
      wg_wait<2>();
      reg_fence(oh);
      store_scaled(B_ADDR(1) + 10240 + st_off, oh, qscale);
      wg_fence();
      mma_main<W, true>(ds, sacc, s9, B_ADDR(xs(9)));
      wg_commit();
      bar_arrive(8, 256);
      TL(49);
      wg_wait<2>();
      RELEASE_CHUNK(7, s7)
      publish(BAR_QH, lane);
    }
    wg_wait<0>();
    reg_fence(sacc);
    TL(1);
    RELEASE_CHUNK(8, s8)
    RELEASE_CHUNK(9, s9)
    store_scaled(B_ADDR(2 * W) + st_off, sacc, qscale);
    if (W == 1) publish(BAR_QM, lane); else proxy_fence();
    TL(2);
    uint32_t sK = sK0, sV1 = 0;
    if (W == 0) {
      zero_regs(om); zero_regs(oh);
      reg_fence(om); reg_fence(oh);
      mbar_wait(bud, BAR_FULLA + sK0, pK0);
      bar_sync(8, 256);
      wg_fence();
      s_mma<0, false>(ds, sacc, sK);
      mbar_wait(bud, BAR_QH, par);
      TL(3);
      wg_fence();
      s_mma<1, true>(ds, sacc, sK);
      mbar_wait(bud, BAR_QM, par);
      TL(5);
      wg_fence();
      s_mma<2, true>(ds, sacc, sK);
      wg_commit();
      wg_commit();
      bar_arrive(2, 256);
    } else {
      uint32_t pV1;
      ring_pos(ring, idxV(0), sV1, pV1);
      mbar_wait(bud, BAR_FULLA + sK, pK0);
      bar_sync(2, 256);
      wg_fence();
      s_mma<0, false>(ds, sacc, sK);
      s_mma<1, true>(ds, sacc, sK);
      s_mma<2, true>(ds, sacc, sK);
      wg_commit();
      TL(6);
      mbar_wait(bud, BAR_FULLA + sV1, pV1);
      mbar_wait(bud, BAR_PFULL, 0);
      TL(7);
      wg_fence();
      mma_both<W, false>(ds, om, oh, sV1, poth);
      wg_commit();
      bar_arrive(1, 256);
    }
#pragma unroll 1
    for (int jj = 0;; jj++) {
      wg_wait<1>();
      reg_fence(sacc);
      TL(8 + jj * 7);
      mbar_arrive2_if0(BAR_EMPTYA + sK, tid);
      mbar_arrive_if0(BAR_EMPTYB + tid * 8, (tid >= 3) | (jj != 3));
#pragma unroll
      for (int J = 0; J < 10; J++) {
        stsm_t(pown + st_off + J * 2048, pack2(ex2(sacc[8 * J]), ex2(sacc[8 * J + 1])), pack2(ex2(sacc[8 * J + 2]), ex2(sacc[8 * J + 3])),
               pack2(ex2(sacc[8 * J + 4]), ex2(sacc[8 * J + 5])), pack2(ex2(sacc[8 * J + 6]), ex2(sacc[8 * J + 7])));
        if (W == 1 && (J == 2 || J == 5)) publish_generic(BAR_PMID + (J / 3) * 8, lane | (jj != 3));
        if (J == 4) {
          wg_wait<0>();
          mbar_arrive_if0(BAR_EMPTYA + sV1, tid | (W == 0 && jj == 0));
        }
      }
      publish(BAR_PFULL + W * 8, lane);
      TL(10 + jj * 7);
      if (jj == 3) break;
      uint32_t sV, pV, pK, pV1;
      ring_pos(ring, idxV(W), sV, pV);
      ring_pos(ring, idxV(W) + 1, sK, pK);
      ring_pos(ring, idxV(W) + 2, sV1, pV1);
      mbar_wait(bud, BAR_FULLA + sV, pV);
      bar_sync(1 + W, 256);
      wg_fence();
      mma_both<W, true>(ds, om, oh, sV, pown);
      wg_commit();
      mbar_wait(bud, BAR_FULLA + sK, pK);
      TL(11 + jj * 7);
      wg_fence();
      s_mma<0, false>(ds, sacc, sK);
      s_mma<1, true>(ds, sacc, sK);
      wg_commit();
      wg_wait<1>();
      mbar_arrive_if0(BAR_EMPTYA + sV, tid);
      wg_fence();
      s_mma<2, true>(ds, sacc, sK);
      wg_commit();
      TL(13 + jj * 7);
      mbar_wait(bud, BAR_FULLA + sV1, pV1);
      mbar_wait(bud, BAR_PFREE + W * 8, jj & 1);
      mbar_wait(bud, BAR_PFULL + (1 - W) * 8, (jj + W) & 1);
      TL(14 + jj * 7);
      wg_fence();
      mma_both<W, true>(ds, om, oh, sV1, poth);
      wg_commit();
      bar_arrive(2 - W, 256);
      ring_advance(ring, 4);
    }
    uint32_t sV7, pV7;
    ring_pos(ring, idxV(7) - 12, sV7, pV7);
    prev = item;
    if (W == 1 && !DEBUG_TIMEOUT) item = next_item();
    if (W == 0) {
      uint32_t sV6, pV6;
      ring_pos(ring, idxV(6) - 12, sV6, pV6);
      mbar_wait(bud, BAR_FULLA + sV6, pV6);
      bar_sync(1, 256);
      wg_fence();
      mma_both<0, true>(ds, om, oh, sV6, pown);
      wg_commit();
      mbar_wait(bud, BAR_FULLA + sV7, pV7);
      wg_wait<0>();
      mbar_arrive_if0(BAR_EMPTYA + sV6, tid);
      mbar_wait(bud, BAR_PFULL + 8, 1);
      wg_fence();
      mma_both<0, true>(ds, om, oh, sV7, poth);
      wg_commit();
      bar_arrive(6, 256);
    } else {
      mbar_wait(bud, BAR_FULLA + sV7, pV7);
      bar_sync(6, 256);
    }
    TL(32);
    if (DEBUG_TIMEOUT) item = next_item(NEXT_ITEM + 4);
    else if (W == 0) item = next_item();
    if (item >= NITEMS) {
      if (W == 1) {
        wg_fence();
        mma_both<1, true>(ds, om, oh, sV7, pown);
        wg_commit();
      }
      wg_wait<0>();
      reg_fence(om); reg_fence(oh);
      TL(33);
      mbar_wait(bud, BAR_LFULL, par);
      mbar_arrive_if0(BAR_FREE, tid);
      TL(34);
      pack_first<W>(pk, om, oh, laddr);
      op = o_ptr(prev);
      store_groups<W, 0, 10>(op, pk, 1);
      pack_second<W, 0, 5>(pk, om, laddr);
      store_groups<W, 10, 15>(op, pk, 1);
      publish_generic(BAR_OFULL, lane);
      TL(35); TLG(63);
      TL_FLUSH();
      return item;
    }
    {
      if (W == 1) {
        wg_fence();
        mma_both<1, true>(ds, om, oh, sV7, pown);
        wg_commit();
      }
      WAIT_CHUNK(0, 26 - 12, s0)
      WAIT_CHUNK(1, 26 - 12, s1)
      if (W == 0) {
        wg_wait<0>();
        reg_fence(om); reg_fence(oh);
        TL(33);
        wg_fence();
        mma_main<W, false>(ds, sacc, s0, B_ADDR(xs(0)));
        wg_commit();
      } else {
        wg_fence();
        mma_main<W, false>(ds, sacc, s0, B_ADDR(xs(0)));
        mma_main<W, true>(ds, sacc, s1, B_ADDR(xs(1)));
        wg_commit();
        wg_wait<1>();
        reg_fence(om); reg_fence(oh);
        TL(33);
      }
      mbar_arrive_if0(BAR_EMPTYA + sV7, tid);
      mbar_wait(bud, BAR_LFULL, par);
      mbar_arrive_if0(BAR_EMPTYB + 24 + tid * 8, tid >= 2);
      TL(34);
      pack_first<W>(pk, om, oh, laddr);
      TL(36);
      wg_fence();
      mma_mid<W, false>(ds, oh, s0, B_ADDR(xs(0)));
      wg_commit();
      mma_mid<W, true>(ds, oh, s1, B_ADDR(xs(1)));
      if (W == 0) mma_main<W, true>(ds, sacc, s1, B_ADDR(xs(1)));
      wg_commit();
      TL(37);
      wg_wait<1>();
      RELEASE_CHUNK(0, s0)
      TL(35); TLG(63);
    }
    TL_FLUSH();
    TL(0); TLG(62);
    ring_advance(ring, 26 - 12);
    par ^= 1;
  }
}

__device__ __forceinline__ uint4 lds128(uint32_t a) {
  uint4 v;
  asm volatile("ld.shared.v4.b32 {%0,%1,%2,%3}, [%4];" : "=r"(v.x), "=r"(v.y), "=r"(v.z), "=r"(v.w) : "r"(a) : "memory");
  return v;
}
__device__ __forceinline__ void acc2(float& s, float& t, uint32_t w) {
  s += __uint_as_float(w << 16);
  t += __uint_as_float(w & 0xffff0000u);
}
__device__ __forceinline__ uint32_t badd2(uint32_t a, uint32_t b) { uint32_t r; asm("add.rn.bf16x2 %0, %1, %2;" : "=r"(r) : "r"(a), "r"(b)); return r; }
__device__ __forceinline__ void sum_unit(float& acc, uint32_t pb) {
  const uint4 v0 = lds128(pb), v1 = lds128(pb ^ 32), v2 = lds128(pb ^ 64), v3 = lds128(pb ^ 96);
  const uint32_t w0 = badd2(badd2(v0.x, v0.y), badd2(v0.z, v0.w));
  float s = acc + __uint_as_float(w0 << 16), t = __uint_as_float(w0 & 0xffff0000u);
  acc2(s, t, badd2(badd2(v1.x, v1.y), badd2(v1.z, v1.w)));
  acc2(s, t, badd2(badd2(v2.x, v2.y), badd2(v2.z, v2.w)));
  acc2(s, t, badd2(badd2(v3.x, v3.y), badd2(v3.z, v3.w)));
  acc = s + t;
}
__device__ __forceinline__ float bf_lo(uint32_t w) { return __uint_as_float(w << 16); }
__device__ __forceinline__ float bf_hi(uint32_t w) { return __uint_as_float(w & 0xffff0000u); }
__device__ __forceinline__ float bf_rn(float x) { return __bfloat162float(__float2bfloat16(x)); }
__device__ __forceinline__ void slow_item(const Params& p, int item, int hw) {
  const int blk = item >> 9, h = (item >> 4) & 31, b = item & 15;
#pragma unroll 1
  for (int n = hw; n < SQ; n += 3) {
    float q[6] = {0.f, 0.f, 0.f, 0.f, 0.f, 0.f};
    {
      const uint32_t* xr = (const uint32_t*)(p.xp[blk] + (size_t)(b * SQ + n) * DM);
      const uint32_t* wq = (const uint32_t*)(p.wqp[blk] + h * DH) + (tid_x() & 31);
#pragma unroll 2
      for (int k = 0; k < DM / 2; k++) {
        const uint32_t xv = xr[k];
#pragma unroll
        for (int i = 0; i < 3; i++) {
          const uint32_t w0 = wq[i * 32], w1 = wq[NH * DH / 2 + i * 32];
          q[2 * i] = fmaf(bf_lo(xv), bf_lo(w0), fmaf(bf_hi(xv), bf_lo(w1), q[2 * i]));
          q[2 * i + 1] = fmaf(bf_lo(xv), bf_hi(w0), fmaf(bf_hi(xv), bf_hi(w1), q[2 * i + 1]));
        }
        wq += NH * DH;
      }
    }
    const uint32_t q0 = pack2(q[0], q[1]), q1 = pack2(q[2], q[3]), q2 = pack2(q[4], q[5]);
    float o[6] = {0.f, 0.f, 0.f, 0.f, 0.f, 0.f}, m = -INFINITY, l = 0.f;
    const uint32_t* kg = (const uint32_t*)(p.kp[blk] + (size_t)(b * NH + h) * SK * DH) + (tid_x() & 31);
    const uint32_t* vg = (const uint32_t*)(p.vp[blk] + (size_t)(b * NH + h) * SK * DH) + (tid_x() & 31);
#pragma unroll 1
    for (int k = 0; k < SK; k++) {
      const uint32_t k0 = kg[0], k1 = kg[32], k2 = kg[64], v0 = vg[0], v1 = vg[32], v2 = vg[64];
      kg += DH / 2; vg += DH / 2;
      float sc = fmaf(bf_lo(q0), bf_lo(k0), bf_hi(q0) * bf_hi(k0));
      sc = fmaf(bf_lo(q1), bf_lo(k1), fmaf(bf_hi(q1), bf_hi(k1), sc));
      sc = fmaf(bf_lo(q2), bf_lo(k2), fmaf(bf_hi(q2), bf_hi(k2), sc));
#pragma unroll
      for (int d = 16; d; d >>= 1) sc += __shfl_xor_sync(0xffffffffu, sc, d);
      sc = bf_rn(bf_rn(sc) * 0.07216878364870322f);
      const float mn = fmaxf(m, sc), a = ex2((m - mn) * 1.4426950408889634f), pr = ex2((sc - mn) * 1.4426950408889634f);
      m = mn;
      l = fmaf(l, a, pr);
      o[0] = fmaf(o[0], a, pr * bf_lo(v0)); o[1] = fmaf(o[1], a, pr * bf_hi(v0));
      o[2] = fmaf(o[2], a, pr * bf_lo(v1)); o[3] = fmaf(o[3], a, pr * bf_hi(v1));
      o[4] = fmaf(o[4], a, pr * bf_lo(v2)); o[5] = fmaf(o[5], a, pr * bf_hi(v2));
    }
    float inv;
    asm("rcp.approx.ftz.f32 %0, %1;" : "=f"(inv) : "f"(l));
    const int lane = tid_x() & 31;
    const int r = n & 15, c = 4 * ((r & 7) >> 1) + 2 * (r >> 3) + (r & 1);
    char* on = o_slot(item) + (lane >> 2) * 256 + (lane & 3) * 64 + (n >> 4) * 2048 +
               (((c >> 3) ^ ((lane >> 1) & 1)) << 4) + (c & 7) * 2;
#pragma unroll
    for (int i = 0; i < 3; i++) {
      *(__nv_bfloat16*)(on + i * B_SLOT) = __float2bfloat16(o[2 * i] * inv);
      *(__nv_bfloat16*)(on + i * B_SLOT + 32) = __float2bfloat16(o[2 * i + 1] * inv);
    }
  }
}
__device__ __forceinline__ void attn_helper(const Params& p, int hw, int item, int epoch) {
  int bud = WAIT_BUDGET;
  if (hw == 2) {
    if (item == 0 && elect_one()) {
      *(volatile int*)&g_ticket = 0;
      asm volatile("red.release.gpu.global.add.s32 [%0], 1;" ::"l"(&g_go) : "memory");
    }
    __syncwarp();
    flag_wait(bud, &g_go, epoch + 1);
  }
  if (item < PF_N && hw < 2) {
    const char* g = (const char*)(hw ? p.vp[0] : p.kp[0]) + (size_t)(((item & 15) * NH + (item >> 4)) * SK) * DH * 2;
    const long long t0 = clock64();
#pragma unroll 1
    for (int i = 0; i < 32; i++) {
      while (clock64() - t0 < PF_WAIT + i * PF_GAP) __nanosleep(50);
      for (int k = 0; k < 6; k++) asm volatile("prefetch.global.L2 [%0];" ::"l"(g + i * 6144 + k * 1024 + (tid_x() & 31) * 32));
      __syncwarp();
    }
  }
#pragma unroll 1
  for (int it = 0; item < NITEMS; it++) {
    const uint32_t par = it & 1;
    int lane = tid_x() & 31;
    const int r = lane >> 1;
    const uint32_t a0 = B_ADDR(3) + (16 * hw + r) * 128 + (lane & 1) * 16 + ((r & 3) << 5);
    float acc[4] = {0.f, 0.f, 0.f, 0.f};
#pragma unroll 1
    for (int j = 0; j < 8; j++) {
      const uint32_t pb = a0 + (j & 1) * B_SLOT, bfull = BAR_PFULL + (j & 1) * 8, pfull = (j >> 1) & 1;
      mbar_wait_sleep(bud, j == 7 ? BAR_PMID : bfull, j == 7 ? par : pfull, SL_H);
      sum_unit(acc[0], pb);
      if (j == 7) mbar_wait(bud, BAR_PMID + 8, par);
      sum_unit(acc[1], pb + 6144);
      if (j == 7) mbar_wait(bud, bfull, pfull);
      sum_unit(acc[2], pb + 2 * 6144);
      if (hw == 0) sum_unit(acc[3], pb + 3 * 6144);
      __syncwarp();
      mbar_arrive_if0(BAR_PFREE + (j & 1) * 8, lane);
      if (j == 5 && hw == 2) {
        if (lane == 0) TLP(60);
        if (item >= ORING && item < OFRESH) flag_wait(bud, &g_done[item - ORING], (epoch + 1) * 2);
        if (lane == 0) TLP(61);
      }
    }
    bool bad = false;
    const uint32_t la = SB + OFF_L + (((r & 7) >> 1) * 40 + 2 * (r >> 3) + (r & 1) + 4 * hw) * 4;
#pragma unroll
    for (int u = 0; u < 4; u++) {
      const float l = acc[u] + __shfl_xor_sync(0xffffffffu, acc[u], 1);
      if (u < 3 || hw == 0) {
        bad |= !(l >= 9.094947017729282e-13f && l <= 1.099511627776e12f);
        float inv;
        asm("rcp.approx.ftz.f32 %0, %1;" : "=f"(inv) : "f"(l));
        asm volatile("st.shared.f32 [%0], %1;" ::"r"(la + u * 48), "f"(inv) : "memory");
      }
    }
    publish_generic(BAR_LFULL, lane);
    if (lane == 0) TLP(40 + hw * 4);
    uint32_t anybad;
    asm volatile("{\n.reg .pred p, q;\nsetp.ne.u32 p, %1, 0;\nbarrier.red.or.pred q, 7, 96, p;\nselp.u32 %0, 1, 0, q;\n}\n"
                 : "=r"(anybad) : "r"((uint32_t)bad) : "memory");
    if (__any_sync(0xffffffffu, anybad)) {
      mbar_wait(bud, BAR_OFULL, par);
      slow_item(p, item, hw);
      bar_sync(7, 96);
    }
    if (hw == 1) {
      mbar_wait_sleep(bud, BAR_OFULL, par, SL_H);
      if ((tid_x() & 31) == 0) {
        TLP(41 + hw * 4);
        asm volatile("red.release.gpu.global.add.s32 [%0], 1;" ::"l"(&g_ready[item]) : "memory");
        TLP(42 + hw * 4);
      }
      __syncwarp();
    }
    item = next_item();
  }
}

__device__ __forceinline__ int attn_producer(const Params& p, int item) {
  int bud = WAIT_BUDGET;
  uint32_t sa = 0, pa = 1;
  const uint64_t pol = evict_first_policy();
  const bool draws = item >= N_OCTA;
  const int delay = start_delay(item);
  {
    const long long t0 = clock64();
    while (clock64() - t0 < delay) __nanosleep(100);
  }
#pragma unroll 1
  for (int it = 0; item < NITEMS; it++) {
    const int blk = item >> 9, h = (item >> 4) & 31, b = item & 15;
    const int row0 = (b * NH + h) * SK;
    if (!(it | delay)) pa = 0;
#pragma unroll 1
    for (int c = (it | delay) ? 0 : NSLOT; c < 10; c++) {
      const uint32_t sx = c < NSLOT ? c : c - NSLOT;
      mbar_wait_sleep(bud, BAR_EMPTYA + sa * 8, pa, SL_P);
      TLP(c);
      mbar_expect(BAR_FULLA + sa * 8, A_SLOT + B_SLOT);
      tma3d(A_ADDR(sa), &p.wq[blk], BAR_FULLA + sa * 8, 0, c * 64, h * 3);
      mbar_wait_sleep(bud, BAR_EMPTYB + sx * 8, c < NSLOT, SL_P);
      TLP(10 + c);
      tma2d(B_ADDR(sx), &p.x[blk], BAR_FULLA + sa * 8, c * 64, b * SQ);
      if (++sa == NSLOT) { sa = 0; pa ^= 1; }
    }
#pragma unroll 1
    for (int i = 0; i < 16; i++) {
      const bool isK = (i == 0) || ((i & 1) && i < 15);
      const int j = i == 0 ? 0 : (i == 15 ? 7 : (isK ? (i + 1) >> 1 : (i - 2) >> 1));
      mbar_wait_sleep(bud, BAR_EMPTYA + sa * 8, pa, SL_P);
      TLP(20 + i);
      mbar_expect(BAR_FULLA + sa * 8, A_SLOT);
      tma3d_hint(A_ADDR(sa), isK ? &p.k[blk] : &p.v[blk], BAR_FULLA + sa * 8, 0, row0 + j * 64, 0, pol);
      if (i == 12) {
        item = draws ? NCTA + atomicAdd(&g_ticket, 1) : NITEMS;
        asm volatile("st.shared.s32 [%0], %1;" ::"r"(NEXT_ITEM), "r"(item) : "memory");
      }
      if (++sa == NSLOT) { sa = 0; pa ^= 1; }
    }
  }
  return item;
}

struct OJob { int tile, part, c0, n; };
__device__ __forceinline__ OJob get_ojob(int cta, int last) {
  if (cta < N_OCTA) return OJob{cta, 0, 0, CHUNK1};
  const int u = last - NITEMS, part = 1 + (u >> 5), tile = part == 3 ? 95 - u : u & 31;
  const int c1 = CHUNK1, c2 = c1 + LEN1 - ((tile * LSLOPE1 + 16) >> 5), c3 = c2 + LEN2 - ((tile * LSLOPE2 + 16) >> 5);
  return OJob{tile, part, part == 1 ? c1 : part == 2 ? c2 : c3, part == 1 ? c2 - c1 + 1 : part == 2 ? c3 - c2 + 1 : part == 3 ? 189 - c3 + 1 : 0};
}
__device__ __forceinline__ int unperm(int c) { return 8 * ((c >> 1) & 1) + 4 * (c >> 3) + 2 * ((c >> 2) & 1) + (c & 1); }
__device__ __forceinline__ uint32_t first_stage(const OJob& job) { return job.part ? (uint32_t)(300 - job.n) % 3 : 0; }

template <int W>
__device__ __forceinline__ void oproj_consumer(const Params& p, const OJob job) {
  int bud = WAIT_BUDGET;
  const int tid = threadIdx.x & 127, lane = tid & 31, warp = tid >> 5;
  float a0[80], a1[80], ah[40];
  zero_regs(a0); zero_regs(a1); zero_regs(ah);
  int left = job.n, step = 0;
  uint32_t st = first_stage(job), ph = 0;
#pragma unroll 1
  while (left) {
    const int nc = left > 3 * NH ? 3 * NH : left;
    left -= nc;
#pragma unroll 1
    for (int c = 0; c < nc; c++) {
      mbar_wait(bud, BAR_GFULL + st * 8, (ph >> st) & 1);
      ph ^= 1 << st;
      if (W == 0) asm volatile("{\n.reg .pred p;\nsetp.eq.s32 p, %0, %1;\n@p bar.sync 11, 256;\n}\n" ::"r"(c + 1), "r"(nc) : "memory");
      wg_fence();
      const uint32_t la = st, lb = st;
#define O_STEP(ks, sc)                                                        \
  mma80r<1, 1, 2 * 8192 + ks * 2048, SB + O_AB + W * 10240 + ks * 512>(ah, p.dsw, la, p.dso, lb, sc);   \
  mma160r<1, 1, (W * 3) * 8192 + ks * 2048, SB + O_AB + ks * 512>(a0, p.dsw, la, p.dso, lb, sc);        \
  mma160r<1, 1, (W * 3 + 1) * 8192 + ks * 2048, SB + O_AB + ks * 512>(a1, p.dsw, la, p.dso, lb, sc);
      O_STEP(0, c != 0) O_STEP(1, 1)
      wg_commit();
      wg_wait<1>();
      mbar_arrive_if0(BAR_GEMPTY + (st == 0 ? 2 : st - 1) * 8, tid | (c == 0));
      wg_fence();
      O_STEP(2, 1) O_STEP(3, 1)
#undef O_STEP
      wg_commit();
      if (++st == 3) {
        st = 0;
        if (W == 0)
          asm volatile("{\n.reg .pred p;\nsetp.eq.u32 p, %1, 0;\n@p red.relaxed.gpu.global.add.s32 [%0], 1;\n}\n"
                       ::"l"(&g_done[step * 16 + (job.tile >> 1)]), "r"(tid | job.part) : "memory");
        TLG(step);
        step++;
      }
    }
    if (W == 1) bar_arrive(11, 256);
    wg_wait<0>();
    reg_fence(a0); reg_fence(a1); reg_fence(ah);
    mbar_arrive_if0(BAR_GEMPTY + (st - 1) * 8, tid | (st == 0));
    TLG(63);
    const int prow = (lane & 7) + 8 * (lane >> 4), qrow = left ? unperm(prow) : prow;
    const uint32_t sg = SB + O_OUT + qrow * 128 + (((2 * warp + ((lane >> 3) & 1)) ^ (qrow & 7)) << 4);
    if (W == 1) {
      bar_arrive(3, 256);
      store_scaled(sg + 3 * B_SLOT, a0, 1.0f);
      publish(BAR_GOUT + 24, lane);
      store_scaled(sg + 4 * B_SLOT, a1, 1.0f);
      publish(BAR_GOUT + 32, lane);
      bar_sync(9, 256);
      store_scaled(sg + 2 * B_SLOT + 10240, ah, 1.0f);
      publish(BAR_GOUT + 16, lane);
    } else {
      bar_arrive(9, 256);
      bar_sync(3, 256);
      store_scaled(sg, a0, 1.0f);
      publish(BAR_GOUT, lane);
      store_scaled(sg + B_SLOT, a1, 1.0f);
      publish(BAR_GOUT + 8, lane);
      store_scaled(sg + 2 * B_SLOT, ah, 1.0f);
      publish(BAR_GOUT + 16, lane);
    }
  }
  TL_FLUSH();
  TLG(0);
  float acc[7][8];
  uint32_t in[7], blk[7], oo[7];
#pragma unroll
  for (int i = 0; i < 7; i++) {
    const int e = min(i * 256 + W * 128 + tid, 1599), r = e / 40, cc = e % 40, R = job.part * 40 + r;
    in[i] = r * 128 + (((cc ^ r) & 7) << 4);
    blk[i] = cc >> 3;
    oo[i] = ((R & ~15) + unperm(R & 15)) * (2 * DM / 8) + cc;
    asm volatile("" : "+r"(oo[i]));
#pragma unroll
    for (int k = 0; k < 8; k++) acc[i][k] = 0.f;
  }
  bar_sync(10, 256);
#pragma unroll 1
  for (int q = 0; q < 4; q++) {
    if (q) mbar_wait(bud, BAR_GRED + (q - 1) * 8, 0);
    if (q == 3) TLG(1);
    const uint32_t base = q ? SB + (q - 1) * 25600 : SB + O_OUT + job.part * 5120, bs = q ? 5120 : B_SLOT;
    uint4 v[7];
#pragma unroll
    for (int i = 0; i < 7; i++) v[i] = lds128(base + blk[i] * bs + in[i]);
#pragma unroll
    for (int i = 0; i < 7; i++) {
      acc[i][0] += bf_lo(v[i].x); acc[i][1] += bf_hi(v[i].x); acc[i][2] += bf_lo(v[i].y); acc[i][3] += bf_hi(v[i].y);
      acc[i][4] += bf_lo(v[i].z); acc[i][5] += bf_hi(v[i].z); acc[i][6] += bf_lo(v[i].w); acc[i][7] += bf_hi(v[i].w);
    }
  }
  uint4* go = (uint4*)p.outp + (job.tile >> 1) * SQ * (2 * DM / 8) + DM / 8 + (job.tile & 1) * 40;
#pragma unroll
  for (int i = 0; i < 7; i++) {
    if (i * 256 + W * 128 + tid < 1600)
      go[oo[i]] = make_uint4(pack2(acc[i][0], acc[i][1]), pack2(acc[i][2], acc[i][3]), pack2(acc[i][4], acc[i][5]), pack2(acc[i][6], acc[i][7]));
  }
  TLG(2);
  TL_FLUSH();
}

__device__ __forceinline__ void oproj_producer(const Params& p, const OJob job, int target) {
  int bud = WAIT_BUDGET;
  const uint64_t polo = evict_first_policy();
  mbar_wait(bud, BAR_FREE, 0);
  uint32_t st = first_stage(job), ph = 7;
  int seen = -1;
#pragma unroll 1
  for (int i = 0; i < job.n; i++) {
    const int c = job.part && i == job.n - 1 ? 188 + job.part : job.c0 + i, step = c / 3, kb = c - 3 * step;
    const int item = step * 16 + (job.tile >> 1);
    if (step != seen) {
      flag_wait(bud, &g_ready[item], target);
      asm volatile("fence.proxy.async.global;" ::: "memory");
      seen = step;
    }
    const uint32_t dst = SB + st * O_STAGE, bar = BAR_GFULL + st * 8;
    const char* og = o_slot(item) + kb * B_SLOT;
    mbar_wait_sleep(bud, BAR_GEMPTY + st * 8, (ph >> st) & 1, SL_P);
    ph ^= 1 << st;
    mbar_expect(bar, O_STAGE);
    tma3d(dst, &p.wo[step >> 5], bar, 0, (c - (step >> 5) * 3 * NH) * 64, (job.tile & 1) * 5);
    bulk_load_hint(dst + O_AB, og, B_SLOT, bar, polo);
    if (++st == 3) st = 0;
  }
  mbar_wait(bud, BAR_GEMPTY, ph & 1);
  mbar_wait(bud, BAR_GEMPTY + 8, (ph >> 1) & 1);
  uint32_t todo = 15 & ~(1 << job.part), dst = SB, bar = BAR_GRED;
  while (todo) {
    int v0, v1, v2, v3;
    asm volatile("ld.acquire.gpu.global.v4.s32 {%0, %1, %2, %3}, [%4];" : "=r"(v0), "=r"(v1), "=r"(v2), "=r"(v3) : "l"(&g_pcnt[job.tile * 4]) : "memory");
    const uint32_t rdy = --bud > 0 ? (v0 - target >= 0) | (v1 - target >= 0) << 1 | (v2 - target >= 0) << 2 | (v3 - target >= 0) << 3 : 15;
    if (!(rdy & todo)) continue;
    asm volatile("fence.proxy.async.global;" ::: "memory");
#pragma unroll 1
    for (int q = 0; q < 4; q++) {
      if (!(((rdy & todo) >> q) & 1)) continue;
      TLE(4 + q);
      mbar_expect(bar, 25600);
      for (int k = 0; k < 5; k++)
        tma2d(dst + k * 5120, &p.part, bar, (job.tile & 1) * 320 + k * 64, q * NB * SQ + (job.tile >> 1) * SQ + job.part * 40);
      todo &= ~(1 << q);
      dst += 25600;
      bar += 8;
    }
  }
}

__device__ __forceinline__ void oproj_storer(const Params& p, const OJob job) {
  int bud = WAIT_BUDGET;
  const int col = (job.tile & 1) * 320, row = (job.tile >> 1) * SQ;
  if (job.part == 0) {
    mbar_wait_sleep(bud, BAR_GOUT + 24, 0, SL_S);
    for (int k = 0; k < 3; k++) {
      mbar_wait(bud, BAR_GOUT + k * 8, 0);
      tma_store2d(&p.out, SB + O_OUT + k * B_SLOT, col + k * 64, row);
    }
    asm volatile("cp.async.bulk.commit_group;" ::: "memory");
    asm volatile("cp.async.bulk.wait_group.read 0;" ::: "memory");
    mbar_arrive2_if0(BAR_GEMPTY + 16, 0);
    mbar_wait(bud, BAR_GFULL + 16, 0);
    for (int k = 3; k < 5; k++) {
      mbar_wait(bud, BAR_GOUT + k * 8, 0);
      tma_store2d(&p.out, SB + O_OUT + k * B_SLOT, col + k * 64, row);
      asm volatile("cp.async.bulk.commit_group;" ::: "memory");
      asm volatile("cp.async.bulk.wait_group.read 0;" ::: "memory");
      __nanosleep(1000);
    }
  }
  mbar_wait_sleep(bud, BAR_GOUT + 24, job.part == 0, SL_S);
#pragma unroll 1
  for (int i = 0; i < 5; i++) {
    const int k = (0x21043 >> (4 * i)) & 15;
    mbar_wait(bud, BAR_GOUT + k * 8, job.part == 0);
    if (i == 0) TLE(0);
    for (int q = 1; q < 4; q++) {
      const int sh = (job.part + q) & 3;
      tma_store2d(&p.part, SB + O_OUT + k * B_SLOT + sh * 5120, col + k * 64, job.part * NB * SQ + row + sh * 40);
    }
  }
  asm volatile("cp.async.bulk.commit_group;" ::: "memory");
  TLE(1);
  asm volatile("cp.async.bulk.wait_group 0;" ::: "memory");
  TLE(2);
  asm volatile("fence.proxy.async.global;" ::: "memory");
  asm volatile("red.release.gpu.global.add.s32 [%0], 1;" ::"l"(&g_pcnt[job.tile * 4 + job.part]) : "memory");
  TLE(3);
}

__global__ void __launch_bounds__(384, 1) fused_kernel(const __grid_constant__ Params p) {
  extern __shared__ __align__(1024) char smem_raw[];
  if ((smem_u32(smem_raw) & 0xFFFFFFu) != SB) return;
  const int cta = (((blockIdx.x / PERM_G) * PERM_M) % (NCTA / PERM_G)) * PERM_G + (blockIdx.x % PERM_G);
  const int warp = __shfl_sync(0xffffffffu, threadIdx.x >> 5, 0);
  if (threadIdx.x == 0) {
    for (int i = 0; i < NSLOT; i++) { mbar_init(BAR_FULLA + i * 8, 1); mbar_init(BAR_EMPTYA + i * 8, 2); mbar_init(BAR_EMPTYB + i * 8, 2); }
    proxy_fence();
    if (start_delay(cta) == 0) {
#pragma unroll 1
      for (int c = 0; c < NSLOT; c++) {
        mbar_expect(BAR_FULLA + c * 8, A_SLOT + B_SLOT);
        tma3d(A_ADDR(c), &p.wq[0], BAR_FULLA + c * 8, 0, c * 64, (cta >> 4) * 3);
        tma2d(B_ADDR(c), &p.x[0], BAR_FULLA + c * 8, c * 64, (cta & 15) * SQ);
      }
    }
  }
  if (threadIdx.x == 64) {
    mbar_init(BAR_XDONE, 1); mbar_init(BAR_QH, 4); mbar_init(BAR_QM, 4);
    mbar_init(BAR_PFULL, 4); mbar_init(BAR_PFULL + 8, 4); mbar_init(BAR_PFREE, 3); mbar_init(BAR_PFREE + 8, 3);
    mbar_init(BAR_LFULL, 3); mbar_init(BAR_PMID, 4); mbar_init(BAR_PMID + 8, 4); mbar_init(BAR_OFULL, 8);
  }
  if (threadIdx.x == 96) {
    for (int i = 0; i < O_NST; i++) { mbar_init(BAR_GFULL + i * 8, 1); mbar_init(BAR_GEMPTY + i * 8, 2); }
    for (int i = 0; i < 5; i++) mbar_init(BAR_GOUT + i * 8, i == 2 ? 8 : 4);
    mbar_init(BAR_GRED, 1); mbar_init(BAR_GRED + 8, 1); mbar_init(BAR_GRED + 16, 1); mbar_init(BAR_FREE, 2);
    proxy_fence();
  }
  if (warp == 1 && threadIdx.x < 32 + 12) asm volatile("prefetch.tensormap [%0];" ::"l"(&p.x[0] + (threadIdx.x - 32)) : "memory");
  __syncthreads();
  if (warp >= 8) {
    asm volatile("setmaxnreg.dec.sync.aligned.u32 40;");
    if (warp == 8) {
      if (elect_one()) {
        const OJob job = get_ojob(cta, attn_producer(p, cta));
        const int epoch = *(volatile int*)&g_epoch[cta];
        *(volatile int*)&g_epoch[cta] = epoch + 1;
        if (job.n) oproj_producer(p, job, epoch + 1);
      }
    } else {
      const int epoch = __shfl_sync(0xffffffffu, *(volatile int*)&g_epoch[cta], 0);
      attn_helper(p, warp - 9, cta, epoch);
      if (warp == 9) {
        const OJob job = get_ojob(cta, next_item());
        if (job.n && elect_one()) oproj_storer(p, job);
      }
    }
  } else {
    asm volatile("setmaxnreg.inc.sync.aligned.u32 232;");
    if (warp < 4) {
      const OJob job = get_ojob(cta, attn_consumer<0>(p.dsw, cta));
      if (job.n) oproj_consumer<0>(p, job);
    } else {
      const OJob job = get_ojob(cta, attn_consumer<1>(p.dsw, cta));
      if (job.n) oproj_consumer<1>(p, job);
    }
  }
}

typedef CUresult (*EncodeFn)(CUtensorMap*, CUtensorMapDataType, cuuint32_t, void*, const cuuint64_t*, const cuuint64_t*, const cuuint32_t*,
                             const cuuint32_t*, CUtensorMapInterleave, CUtensorMapSwizzle, CUtensorMapL2promotion, CUtensorMapFloatOOBfill);

void make3d(EncodeFn enc, CUtensorMap* m, const void* ptr, uint64_t rows, uint64_t cols, uint32_t box_rows, uint32_t box_blocks,
            CUtensorMapL2promotion promo = CU_TENSOR_MAP_L2_PROMOTION_L2_128B) {
  cuuint64_t gd[3] = {64, rows, cols / 64};
  cuuint64_t gs[2] = {cols * 2, 128};
  cuuint32_t bd[3] = {64, box_rows, box_blocks}, es[3] = {1, 1, 1};
  enc(m, CU_TENSOR_MAP_DATA_TYPE_BFLOAT16, 3, (void*)ptr, gd, gs, bd, es, CU_TENSOR_MAP_INTERLEAVE_NONE, CU_TENSOR_MAP_SWIZZLE_128B,
      promo, CU_TENSOR_MAP_FLOAT_OOB_FILL_NONE);
}
void make2d(EncodeFn enc, CUtensorMap* m, const void* ptr, uint64_t rows, uint64_t cols, uint32_t box_rows) {
  cuuint64_t gd[2] = {cols, rows};
  cuuint64_t gs[1] = {cols * 2};
  cuuint32_t bd[2] = {64, box_rows}, es[2] = {1, 1};
  enc(m, CU_TENSOR_MAP_DATA_TYPE_BFLOAT16, 2, (void*)ptr, gd, gs, bd, es, CU_TENSOR_MAP_INTERLEAVE_NONE, CU_TENSOR_MAP_SWIZZLE_128B,
      CU_TENSOR_MAP_L2_PROMOTION_L2_128B, CU_TENSOR_MAP_FLOAT_OOB_FILL_NONE);
}

}

extern "C" void kernel_launch(void* const* d_in, const int* in_sizes, int n_in, void* d_out, int out_size) {
  static EncodeFn enc = nullptr;
  static void* part = nullptr;
  if (!enc) {
    cudaGetSymbolAddress(&part, g_part);
    cudaDriverEntryPointQueryResult qr;
    cudaGetDriverEntryPoint("cuTensorMapEncodeTiled", (void**)&enc, cudaEnableDefault, &qr);
    cudaFuncSetAttribute(fused_kernel, cudaFuncAttributeMaxDynamicSharedMemorySize, SMEM_BYTES);
  }
  Params p;
  for (int s = 0; s < 2; s++) {
    make2d(enc, &p.x[s], d_in[5 * s + 0], NB * SQ, DM, SQ);
    make3d(enc, &p.k[s], d_in[5 * s + 1], (uint64_t)NB * NH * SK, DH, 64, 3);
    make3d(enc, &p.v[s], d_in[5 * s + 2], (uint64_t)NB * NH * SK, DH, 64, 3);
    make3d(enc, &p.wq[s], d_in[5 * s + 3], DM, NH * DH, 64, 3);
    make3d(enc, &p.wo[s], d_in[5 * s + 4], NH * DH, DM, 64, 5);
    p.xp[s] = (const __nv_bfloat16*)d_in[5 * s + 0];
    p.wqp[s] = (const __nv_bfloat16*)d_in[5 * s + 3];
    p.kp[s] = (const __nv_bfloat16*)d_in[5 * s + 1];
    p.vp[s] = (const __nv_bfloat16*)d_in[5 * s + 2];
  }
  make2d(enc, &p.out, d_out, NB * SQ, 2 * DM, SQ);
  make2d(enc, &p.part, part, 4 * NB * SQ, DM, 40);
  p.outp = (__nv_bfloat16*)d_out;
  p.dsw = DESC_SW;
  p.dso = DESC_O;
  fused_kernel<<<NCTA, 384, SMEM_BYTES>>>(p);
}
```

```cpp
#include <cuda_runtime.h>
#include <cuda_bf16.h>
#include <cuda.h>
#include <stdint.h>

#define DEBUG_TIMEOUT 0

namespace {

constexpr int SQ = 160, DM = 640, NH = 32, SK = 512, DH = 192, NB = 16;
constexpr int NITEMS = 2 * NB * NH;
constexpr int NCTA = 132, N_OCTA = 32;
constexpr int ORING = 192, OFRESH = 848, CHUNK1 = 158, LEN1 = 18, LEN2 = 13, LSLOPE1 = 4, LSLOPE2 = 5;
constexpr int STAG_G = 4, PERM_G = 4, STAG_A0 = 19, STAG_SLOPE = 275, PERM_M = 20, PF_N = 32, PF_WAIT = 1500, PF_GAP = 300;
constexpr int OSLOTS = ORING + NITEMS - OFRESH;
constexpr int A_SLOT = 24576, B_SLOT = 20480, NSLOT = 5;
constexpr int OFF_A = 0;
constexpr int OFF_B = NSLOT * A_SLOT;
constexpr int O_STAGE = 61440, O_AB = 40960, O_NST = 3;
constexpr int OFF_L = OFF_B + NSLOT * B_SLOT;
constexpr int OFF_BAR = OFF_L + 160 * 4;
constexpr int SMEM_BYTES = OFF_BAR + 512 + 512;
constexpr int O_OUT = 2 * O_STAGE;
static_assert(O_OUT + 5 * B_SLOT <= OFF_L, "smem layout");
constexpr uint32_t SB = 1024;
constexpr uint32_t BARS = SB + OFF_BAR;
constexpr uint32_t BAR_FULLA = BARS, BAR_EMPTYA = BARS + 40, BAR_PMID = BARS + 80, BAR_EMPTYB = BARS + 120, BAR_XDONE = BARS + 160,
                   BAR_QH = BARS + 168, BAR_QM = BARS + 96, BAR_PFULL = BARS + 184, BAR_PFREE = BARS + 200, BAR_LFULL = BARS + 216,
                   BAR_OFULL = BARS + 224, BAR_GFULL = BARS + 248, BAR_GEMPTY = BARS + 280, BAR_GOUT = BARS + 328, BAR_GRED = BARS + 368,
                   BAR_FREE = BARS + 240, NEXT_ITEM = BARS + 320;
constexpr int O_ITEM_BYTES = SQ * DH * 2;

struct alignas(64) Params {
  CUtensorMap x[2], wq[2], k[2], v[2], wo[2], out, part;
  uint64_t dsw, dso, zero;
  __nv_bfloat16* outp;
  const __nv_bfloat16 *xp[2], *wqp[2], *kp[2], *vp[2];
};

__device__ uint4 g_o[(size_t)OSLOTS * O_ITEM_BYTES / 16];
__device__ uint4 g_part[4 * NB * SQ * DM / 8];
__device__ __align__(16) int g_pcnt[4 * N_OCTA];
__device__ int g_ready[NITEMS];
__device__ int g_done[NITEMS];
__device__ int g_ticket;
__device__ int g_go;
__device__ int g_epoch[NCTA];

#define TLE(id)
#define TLP(id)
#define TLG(id)
#define TL(id)
#define TL_FLUSH()
__device__ __forceinline__ uint32_t smem_u32(const void* p) { return (uint32_t)__cvta_generic_to_shared(p); }
__device__ __forceinline__ void wg_fence() { asm volatile("wgmma.fence.sync.aligned;" ::: "memory"); }
__device__ __forceinline__ void wg_commit() { asm volatile("wgmma.commit_group.sync.aligned;" ::: "memory"); }
template <int N> __device__ __forceinline__ void wg_wait() { asm volatile("wgmma.wait_group.sync.aligned %0;" ::"n"(N) : "memory"); }
template <int N> __device__ __forceinline__ void reg_fence(float (&d)[N]) {
#pragma unroll
  for (int i = 0; i < N; i++) asm volatile("" : "+f"(d[i])::"memory");
}
template <int N> __device__ __forceinline__ void zero_regs(float (&d)[N]) {
#pragma unroll
  for (int i = 0; i < N; i++) d[i] = 0.f;
}
__device__ __forceinline__ void proxy_fence() { asm volatile("fence.proxy.async.shared::cta;" ::: "memory"); }
__device__ __forceinline__ void mbar_init(uint32_t bar, int cnt) { asm volatile("mbarrier.init.shared::cta.b64 [%0], %1;" ::"r"(bar), "r"(cnt) : "memory"); }
__device__ __forceinline__ void mbar_arrive_if0(uint32_t bar, uint32_t sel) {
  asm volatile("{\n.reg .pred p;\nsetp.eq.u32 p, %1, 0;\n@p mbarrier.arrive.shared::cta.b64 _, [%0];\n}\n" ::"r"(bar), "r"(sel) : "memory");
}
__device__ __forceinline__ void mbar_arrive2_if0(uint32_t bar, uint32_t sel) {
  asm volatile("{\n.reg .pred p;\nsetp.eq.u32 p, %1, 0;\n@p mbarrier.arrive.shared::cta.b64 _, [%0], 2;\n}\n" ::"r"(bar), "r"(sel) : "memory");
}
__device__ __forceinline__ void mbar_expect(uint32_t bar, uint32_t bytes) {
  asm volatile("mbarrier.arrive.expect_tx.shared::cta.b64 _, [%0], %1;" ::"r"(bar), "r"(bytes) : "memory");
}
__device__ __forceinline__ void mbar_wait(int& bud, uint32_t bar, uint32_t parity) {
  asm volatile(
      "{\n.reg .pred p;\n"
      "LW:\n"
      "mbarrier.try_wait.parity.shared::cta.b64 p, [%0], %1;\n"
      "@!p bra LW;\n}\n" ::"r"(bar), "r"(parity) : "memory");
}
constexpr int WAIT_BUDGET = 1 << 22;
__device__ __forceinline__ bool elect_one() {
  uint32_t p;
  asm volatile("{\n.reg .pred p;\nelect.sync _|p, 0xffffffff;\nselp.u32 %0, 1, 0, p;\n}\n" : "=r"(p));
  return p;
}
__device__ __forceinline__ void tma2d(uint32_t dst, const CUtensorMap* m, uint32_t bar, int c0, int c1) {
  asm volatile("cp.async.bulk.tensor.2d.shared::cluster.global.mbarrier::complete_tx::bytes [%0], [%1, {%3, %4}], [%2];"
               ::"r"(dst), "l"(m), "r"(bar), "r"(c0), "r"(c1) : "memory");
}
__device__ __forceinline__ void tma3d(uint32_t dst, const CUtensorMap* m, uint32_t bar, int c0, int c1, int c2) {
  asm volatile("cp.async.bulk.tensor.3d.shared::cluster.global.mbarrier::complete_tx::bytes [%0], [%1, {%3, %4, %5}], [%2];"
               ::"r"(dst), "l"(m), "r"(bar), "r"(c0), "r"(c1), "r"(c2) : "memory");
}
__device__ __forceinline__ void tma3d_hint(uint32_t dst, const CUtensorMap* m, uint32_t bar, int c0, int c1, int c2, uint64_t pol) {
  asm volatile("cp.async.bulk.tensor.3d.shared::cluster.global.mbarrier::complete_tx::bytes.L2::cache_hint [%0], [%1, {%3, %4, %5}], [%2], %6;"
               ::"r"(dst), "l"(m), "r"(bar), "r"(c0), "r"(c1), "r"(c2), "l"(pol) : "memory");
}
__device__ __forceinline__ void tma_store2d(const CUtensorMap* m, uint32_t src, int c0, int c1) {
  asm volatile("cp.async.bulk.tensor.2d.global.shared::cta.bulk_group [%0, {%2, %3}], [%1];" ::"l"(m), "r"(src), "r"(c0), "r"(c1) : "memory");
}
__device__ __forceinline__ void bar_sync(int id, int n) { asm volatile("bar.sync %0, %1;" ::"r"(id), "r"(n) : "memory"); }
__device__ __forceinline__ void bar_arrive(int id, int n) { asm volatile("bar.arrive %0, %1;" ::"r"(id), "r"(n) : "memory"); }
__device__ __forceinline__ void bar_sync_if0(int id, int sel) {
  asm volatile("{\n.reg .pred p;\nsetp.eq.s32 p, %1, 0;\n@p bar.sync %0, 256;\n}\n" ::"r"(id), "r"(sel) : "memory");
}
__device__ __forceinline__ float ex2(float x) { float y; asm("ex2.approx.ftz.f32 %0, %1;" : "=f"(y) : "f"(x)); return y; }
__device__ __forceinline__ uint32_t pack2(float lo, float hi) { uint32_t r; asm("cvt.rn.bf16x2.f32 %0, %1, %2;" : "=r"(r) : "f"(hi), "f"(lo)); return r; }
__device__ __forceinline__ void stsm_t(uint32_t a, uint32_t r0, uint32_t r1, uint32_t r2, uint32_t r3) {
  asm volatile("stmatrix.sync.aligned.m8n8.x4.trans.shared.b16 [%0], {%1,%2,%3,%4};" ::"r"(a), "r"(r0), "r"(r1), "r"(r2), "r"(r3) : "memory");
}
__device__ __forceinline__ uint64_t evict_first_policy() {
  uint64_t pol;
  asm volatile("createpolicy.fractional.L2::evict_first.b64 %0, 1.0;" : "=l"(pol));
  return pol;
}
__device__ __forceinline__ void bulk_load_hint(uint32_t dst, const void* src, uint32_t bytes, uint32_t bar, uint64_t pol) {
  asm volatile("cp.async.bulk.shared::cluster.global.mbarrier::complete_tx::bytes.L2::cache_hint [%0], [%1], %2, [%3], %4;"
               ::"r"(dst), "l"(src), "r"(bytes), "r"(bar), "l"(pol) : "memory");
}
__device__ __forceinline__ void flag_wait(int& bud, const int* p, int target) {
  while (true) {
    int v;
    asm volatile("ld.acquire.gpu.global.s32 %0, [%1];" : "=r"(v) : "l"(p) : "memory");
    if (v - target >= 0 || --bud <= 0) break;
    __nanosleep(64);
  }
}
constexpr uint64_t DESC_SW = 0x4000004000010000ull, DESC_O = 0xC000001000800000ull;
__device__ __forceinline__ uint32_t tid_x() { uint32_t t; asm volatile("mov.u32 %0, %tid.x;" : "=r"(t)); return t; }

template <int TA, int TB, uint32_t OA, uint32_t OB>
__device__ __forceinline__ void mma160(float (&d)[80], uint64_t ba, uint32_t la, uint64_t bb, uint32_t lb) {
  asm volatile(
      "{\n.reg .pred p;\n.reg .b64 da, db;\nsetp.eq.b32 p, 0, 0;\n"
      "mad.wide.u32 da, %80, 192, %86;\nadd.s64 da, da, %84;\nmad.wide.u32 db, %81, 1, %87;\nadd.s64 db, db, %85;\n"
      "wgmma.mma_async.sync.aligned.m64n160k16.f32.bf16.bf16 {"
      "%0,%1,%2,%3,%4,%5,%6,%7,%8,%9,%10,%11,%12,%13,%14,%15,%16,%17,%18,%19,%20,%21,%22,%23,%24,%25,%26,%27,%28,%29,%30,%31,%32,%33,%34,%35,%36,"
      "%37,%38,%39,%40,%41,%42,%43,%44,%45,%46,%47,%48,%49,%50,%51,%52,%53,%54,%55,%56,%57,%58,%59,%60,%61,%62,%63,%64,%65,%66,%67,%68,%69,%70,%71,"
      "%72,%73,%74,%75,%76,%77,%78,%79"
      "}, da, db, p, 1, 1, %82, %83;\n}\n"
      :
      "+f"(d[0]),"+f"(d[1]),"+f"(d[2]),"+f"(d[3]),"+f"(d[4]),"+f"(d[5]),"+f"(d[6]),"+f"(d[7]),"+f"(d[8]),"+f"(d[9]),"+f"(d[10]),"+f"(d[11]),
      "+f"(d[12]),"+f"(d[13]),"+f"(d[14]),"+f"(d[15]),"+f"(d[16]),"+f"(d[17]),"+f"(d[18]),"+f"(d[19]),"+f"(d[20]),"+f"(d[21]),"+f"(d[22]),
      "+f"(d[23]),"+f"(d[24]),"+f"(d[25]),"+f"(d[26]),"+f"(d[27]),"+f"(d[28]),"+f"(d[29]),"+f"(d[30]),"+f"(d[31]),"+f"(d[32]),"+f"(d[33]),
      "+f"(d[34]),"+f"(d[35]),"+f"(d[36]),"+f"(d[37]),"+f"(d[38]),"+f"(d[39]),"+f"(d[40]),"+f"(d[41]),"+f"(d[42]),"+f"(d[43]),"+f"(d[44]),
      "+f"(d[45]),"+f"(d[46]),"+f"(d[47]),"+f"(d[48]),"+f"(d[49]),"+f"(d[50]),"+f"(d[51]),"+f"(d[52]),"+f"(d[53]),"+f"(d[54]),"+f"(d[55]),
      "+f"(d[56]),"+f"(d[57]),"+f"(d[58]),"+f"(d[59]),"+f"(d[60]),"+f"(d[61]),"+f"(d[62]),"+f"(d[63]),"+f"(d[64]),"+f"(d[65]),"+f"(d[66]),
      "+f"(d[67]),"+f"(d[68]),"+f"(d[69]),"+f"(d[70]),"+f"(d[71]),"+f"(d[72]),"+f"(d[73]),"+f"(d[74]),"+f"(d[75]),"+f"(d[76]),"+f"(d[77]),
      "+f"(d[78]),"+f"(d[79])
      : "r"(la), "r"(lb), "n"(TA), "n"(TB), "n"((SB + OA) >> 4), "n"(OB >> 4), "l"(ba), "l"(bb));
}

template <int TA, int TB, uint32_t OA, uint32_t OB>
__device__ __forceinline__ void mma160z(float (&d)[80], uint64_t ba, uint32_t la, uint64_t bb, uint32_t lb) {
  asm volatile(
      "{\n.reg .pred p;\n.reg .b64 da, db;\nsetp.ne.b32 p, 0, 0;\n"
      "mad.wide.u32 da, %80, 192, %86;\nadd.s64 da, da, %84;\nmad.wide.u32 db, %81, 1, %87;\nadd.s64 db, db, %85;\n"
      "wgmma.mma_async.sync.aligned.m64n160k16.f32.bf16.bf16 {"
      "%0,%1,%2,%3,%4,%5,%6,%7,%8,%9,%10,%11,%12,%13,%14,%15,%16,%17,%18,%19,%20,%21,%22,%23,%24,%25,%26,%27,%28,%29,%30,%31,%32,%33,%34,%35,%36,"
      "%37,%38,%39,%40,%41,%42,%43,%44,%45,%46,%47,%48,%49,%50,%51,%52,%53,%54,%55,%56,%57,%58,%59,%60,%61,%62,%63,%64,%65,%66,%67,%68,%69,%70,%71,"
      "%72,%73,%74,%75,%76,%77,%78,%79"
      "}, da, db, p, 1, 1, %82, %83;\n}\n"
      :
      "=f"(d[0]),"=f"(d[1]),"=f"(d[2]),"=f"(d[3]),"=f"(d[4]),"=f"(d[5]),"=f"(d[6]),"=f"(d[7]),"=f"(d[8]),"=f"(d[9]),"=f"(d[10]),"=f"(d[11]),
      "=f"(d[12]),"=f"(d[13]),"=f"(d[14]),"=f"(d[15]),"=f"(d[16]),"=f"(d[17]),"=f"(d[18]),"=f"(d[19]),"=f"(d[20]),"=f"(d[21]),"=f"(d[22]),
      "=f"(d[23]),"=f"(d[24]),"=f"(d[25]),"=f"(d[26]),"=f"(d[27]),"=f"(d[28]),"=f"(d[29]),"=f"(d[30]),"=f"(d[31]),"=f"(d[32]),"=f"(d[33]),
      "=f"(d[34]),"=f"(d[35]),"=f"(d[36]),"=f"(d[37]),"=f"(d[38]),"=f"(d[39]),"=f"(d[40]),"=f"(d[41]),"=f"(d[42]),"=f"(d[43]),"=f"(d[44]),
      "=f"(d[45]),"=f"(d[46]),"=f"(d[47]),"=f"(d[48]),"=f"(d[49]),"=f"(d[50]),"=f"(d[51]),"=f"(d[52]),"=f"(d[53]),"=f"(d[54]),"=f"(d[55]),
      "=f"(d[56]),"=f"(d[57]),"=f"(d[58]),"=f"(d[59]),"=f"(d[60]),"=f"(d[61]),"=f"(d[62]),"=f"(d[63]),"=f"(d[64]),"=f"(d[65]),"=f"(d[66]),
      "=f"(d[67]),"=f"(d[68]),"=f"(d[69]),"=f"(d[70]),"=f"(d[71]),"=f"(d[72]),"=f"(d[73]),"=f"(d[74]),"=f"(d[75]),"=f"(d[76]),"=f"(d[77]),
      "=f"(d[78]),"=f"(d[79])
      : "r"(la), "r"(lb), "n"(TA), "n"(TB), "n"((SB + OA) >> 4), "n"(OB >> 4), "l"(ba), "l"(bb));
}

template <int TA, int TB, uint32_t OA, uint32_t OB>
__device__ __forceinline__ void mma80(float (&d)[40], uint64_t ba, uint32_t la, uint64_t bb, uint32_t lb) {
  asm volatile(
      "{\n.reg .pred p;\n.reg .b64 da, db;\nsetp.eq.b32 p, 0, 0;\n"
      "mad.wide.u32 da, %40, 192, %46;\nadd.s64 da, da, %44;\nmad.wide.u32 db, %41, 1, %47;\nadd.s64 db, db, %45;\n"
      "wgmma.mma_async.sync.aligned.m64n80k16.f32.bf16.bf16 {"
      "%0,%1,%2,%3,%4,%5,%6,%7,%8,%9,%10,%11,%12,%13,%14,%15,%16,%17,%18,%19,%20,%21,%22,%23,%24,%25,%26,%27,%28,%29,%30,%31,%32,%33,%34,%35,%36,"
      "%37,%38,%39"
      "}, da, db, p, 1, 1, %42, %43;\n}\n"
      :
      "+f"(d[0]),"+f"(d[1]),"+f"(d[2]),"+f"(d[3]),"+f"(d[4]),"+f"(d[5]),"+f"(d[6]),"+f"(d[7]),"+f"(d[8]),"+f"(d[9]),"+f"(d[10]),"+f"(d[11]),
      "+f"(d[12]),"+f"(d[13]),"+f"(d[14]),"+f"(d[15]),"+f"(d[16]),"+f"(d[17]),"+f"(d[18]),"+f"(d[19]),"+f"(d[20]),"+f"(d[21]),"+f"(d[22]),
      "+f"(d[23]),"+f"(d[24]),"+f"(d[25]),"+f"(d[26]),"+f"(d[27]),"+f"(d[28]),"+f"(d[29]),"+f"(d[30]),"+f"(d[31]),"+f"(d[32]),"+f"(d[33]),
      "+f"(d[34]),"+f"(d[35]),"+f"(d[36]),"+f"(d[37]),"+f"(d[38]),"+f"(d[39])
      : "r"(la), "r"(lb), "n"(TA), "n"(TB), "n"((SB + OA) >> 4), "n"(OB >> 4), "l"(ba), "l"(bb));
}

template <int TA, int TB, uint32_t OA, uint32_t OB>
__device__ __forceinline__ void mma80z(float (&d)[40], uint64_t ba, uint32_t la, uint64_t bb, uint32_t lb) {
  asm volatile(
      "{\n.reg .pred p;\n.reg .b64 da, db;\nsetp.ne.b32 p, 0, 0;\n"
      "mad.wide.u32 da, %40, 192, %46;\nadd.s64 da, da, %44;\nmad.wide.u32 db, %41, 1, %47;\nadd.s64 db, db, %45;\n"
      "wgmma.mma_async.sync.aligned.m64n80k16.f32.bf16.bf16 {"
      "%0,%1,%2,%3,%4,%5,%6,%7,%8,%9,%10,%11,%12,%13,%14,%15,%16,%17,%18,%19,%20,%21,%22,%23,%24,%25,%26,%27,%28,%29,%30,%31,%32,%33,%34,%35,%36,"
      "%37,%38,%39"
      "}, da, db, p, 1, 1, %42, %43;\n}\n"
      :
      "=f"(d[0]),"=f"(d[1]),"=f"(d[2]),"=f"(d[3]),"=f"(d[4]),"=f"(d[5]),"=f"(d[6]),"=f"(d[7]),"=f"(d[8]),"=f"(d[9]),"=f"(d[10]),"=f"(d[11]),
      "=f"(d[12]),"=f"(d[13]),"=f"(d[14]),"=f"(d[15]),"=f"(d[16]),"=f"(d[17]),"=f"(d[18]),"=f"(d[19]),"=f"(d[20]),"=f"(d[21]),"=f"(d[22]),
      "=f"(d[23]),"=f"(d[24]),"=f"(d[25]),"=f"(d[26]),"=f"(d[27]),"=f"(d[28]),"=f"(d[29]),"=f"(d[30]),"=f"(d[31]),"=f"(d[32]),"=f"(d[33]),
      "=f"(d[34]),"=f"(d[35]),"=f"(d[36]),"=f"(d[37]),"=f"(d[38]),"=f"(d[39])
      : "r"(la), "r"(lb), "n"(TA), "n"(TB), "n"((SB + OA) >> 4), "n"(OB >> 4), "l"(ba), "l"(bb));
}

template <int TA, int TB, uint32_t OA, uint32_t OB>
__device__ __forceinline__ void mma160r(float (&d)[80], uint64_t ba, uint32_t la, uint64_t bb, uint32_t lb, int sc) {
  asm volatile(
      "{\n.reg .pred p;\n.reg .b64 da, db;\nsetp.ne.b32 p, %88, 0;\n"
      "mad.wide.u32 da, %80, 3840, %86;\nadd.s64 da, da, %84;\nmad.wide.u32 db, %81, 3840, %87;\nadd.s64 db, db, %85;\n"
      "wgmma.mma_async.sync.aligned.m64n160k16.f32.bf16.bf16 {"
      "%0,%1,%2,%3,%4,%5,%6,%7,%8,%9,%10,%11,%12,%13,%14,%15,%16,%17,%18,%19,%20,%21,%22,%23,%24,%25,%26,%27,%28,%29,%30,%31,%32,%33,%34,%35,%36,"
      "%37,%38,%39,%40,%41,%42,%43,%44,%45,%46,%47,%48,%49,%50,%51,%52,%53,%54,%55,%56,%57,%58,%59,%60,%61,%62,%63,%64,%65,%66,%67,%68,%69,%70,%71,"
      "%72,%73,%74,%75,%76,%77,%78,%79"
      "}, da, db, p, 1, 1, %82, %83;\n}\n"
      :
      "+f"(d[0]),"+f"(d[1]),"+f"(d[2]),"+f"(d[3]),"+f"(d[4]),"+f"(d[5]),"+f"(d[6]),"+f"(d[7]),"+f"(d[8]),"+f"(d[9]),"+f"(d[10]),"+f"(d[11]),
      "+f"(d[12]),"+f"(d[13]),"+f"(d[14]),"+f"(d[15]),"+f"(d[16]),"+f"(d[17]),"+f"(d[18]),"+f"(d[19]),"+f"(d[20]),"+f"(d[21]),"+f"(d[22]),
      "+f"(d[23]),"+f"(d[24]),"+f"(d[25]),"+f"(d[26]),"+f"(d[27]),"+f"(d[28]),"+f"(d[29]),"+f"(d[30]),"+f"(d[31]),"+f"(d[32]),"+f"(d[33]),
      "+f"(d[34]),"+f"(d[35]),"+f"(d[36]),"+f"(d[37]),"+f"(d[38]),"+f"(d[39]),"+f"(d[40]),"+f"(d[41]),"+f"(d[42]),"+f"(d[43]),"+f"(d[44]),
      "+f"(d[45]),"+f"(d[46]),"+f"(d[47]),"+f"(d[48]),"+f"(d[49]),"+f"(d[50]),"+f"(d[51]),"+f"(d[52]),"+f"(d[53]),"+f"(d[54]),"+f"(d[55]),
      "+f"(d[56]),"+f"(d[57]),"+f"(d[58]),"+f"(d[59]),"+f"(d[60]),"+f"(d[61]),"+f"(d[62]),"+f"(d[63]),"+f"(d[64]),"+f"(d[65]),"+f"(d[66]),
      "+f"(d[67]),"+f"(d[68]),"+f"(d[69]),"+f"(d[70]),"+f"(d[71]),"+f"(d[72]),"+f"(d[73]),"+f"(d[74]),"+f"(d[75]),"+f"(d[76]),"+f"(d[77]),
      "+f"(d[78]),"+f"(d[79])
      : "r"(la), "r"(lb), "n"(TA), "n"(TB), "n"((SB + OA) >> 4), "n"(OB >> 4), "l"(ba), "l"(bb), "r"(sc));
}

template <int TA, int TB, uint32_t OA, uint32_t OB>
__device__ __forceinline__ void mma80r(float (&d)[40], uint64_t ba, uint32_t la, uint64_t bb, uint32_t lb, int sc) {
  asm volatile(
      "{\n.reg .pred p;\n.reg .b64 da, db;\nsetp.ne.b32 p, %48, 0;\n"
      "mad.wide.u32 da, %40, 3840, %46;\nadd.s64 da, da, %44;\nmad.wide.u32 db, %41, 3840, %47;\nadd.s64 db, db, %45;\n"
      "wgmma.mma_async.sync.aligned.m64n80k16.f32.bf16.bf16 {"
      "%0,%1,%2,%3,%4,%5,%6,%7,%8,%9,%10,%11,%12,%13,%14,%15,%16,%17,%18,%19,%20,%21,%22,%23,%24,%25,%26,%27,%28,%29,%30,%31,%32,%33,%34,%35,%36,"
      "%37,%38,%39"
      "}, da, db, p, 1, 1, %42, %43;\n}\n"
      :
      "+f"(d[0]),"+f"(d[1]),"+f"(d[2]),"+f"(d[3]),"+f"(d[4]),"+f"(d[5]),"+f"(d[6]),"+f"(d[7]),"+f"(d[8]),"+f"(d[9]),"+f"(d[10]),"+f"(d[11]),
      "+f"(d[12]),"+f"(d[13]),"+f"(d[14]),"+f"(d[15]),"+f"(d[16]),"+f"(d[17]),"+f"(d[18]),"+f"(d[19]),"+f"(d[20]),"+f"(d[21]),"+f"(d[22]),
      "+f"(d[23]),"+f"(d[24]),"+f"(d[25]),"+f"(d[26]),"+f"(d[27]),"+f"(d[28]),"+f"(d[29]),"+f"(d[30]),"+f"(d[31]),"+f"(d[32]),"+f"(d[33]),
      "+f"(d[34]),"+f"(d[35]),"+f"(d[36]),"+f"(d[37]),"+f"(d[38]),"+f"(d[39])
      : "r"(la), "r"(lb), "n"(TA), "n"(TB), "n"((SB + OA) >> 4), "n"(OB >> 4), "l"(ba), "l"(bb), "r"(sc));
}

struct Ring { uint32_t o[NSLOT], m; };
__device__ __forceinline__ void ring_pos(const Ring& r, int i, uint32_t& slot8, uint32_t& ph) {
  slot8 = r.o[i % NSLOT];
  ph = r.m >> (i % (2 * NSLOT));
}
__device__ __forceinline__ void ring_advance(Ring& r, int n) {
  Ring t = r;
#pragma unroll
  for (int k = 0; k < NSLOT; k++) r.o[k] = t.o[(k + n) % NSLOT];
  r.m = ((t.m >> (n % (2 * NSLOT))) & 1023) * 1025;
}
__host__ __device__ constexpr int idxK(int j) { return j == 0 ? 10 : 9 + 2 * j; }
__host__ __device__ constexpr int idxV(int j) { return j == 7 ? 25 : 12 + 2 * j; }
__host__ __device__ constexpr int xs(int c) { return c % NSLOT; }

__device__ __forceinline__ int start_delay(int cta) {
  return max(0, ((cta - N_OCTA) | (STAG_G - 1)) - STAG_A0) * STAG_SLOPE;
}
__device__ __forceinline__ char* o_slot(int item) {
  return (char*)g_o + (size_t)(item < OFRESH ? item % ORING : item - OFRESH + ORING) * O_ITEM_BYTES;
}
__device__ __forceinline__ int next_item(uint32_t a = NEXT_ITEM) {
  int v;
  asm volatile("ld.shared.s32 %0, [%1];" : "=r"(v) : "r"(a) : "memory");
  return __shfl_sync(0xffffffffu, v, 0);
}

template <int W, bool ACC>
__device__ __forceinline__ void mma_main(uint64_t ds, float (&d)[80], uint32_t la, uint32_t baddr) {
  const uint32_t lb = baddr >> 4;
  if (ACC) mma160<1, 0, W * 16384, 0>(d, ds, la, ds, lb); else mma160z<1, 0, W * 16384, 0>(d, ds, la, ds, lb);
  mma160<1, 0, W * 16384 + 1 * 2048, 1 * 32>(d, ds, la, ds, lb);
  mma160<1, 0, W * 16384 + 2 * 2048, 2 * 32>(d, ds, la, ds, lb);
  mma160<1, 0, W * 16384 + 3 * 2048, 3 * 32>(d, ds, la, ds, lb);
}
template <int W, bool ACC>
__device__ __forceinline__ void mma_mid(uint64_t ds, float (&d)[40], uint32_t la, uint32_t baddr) {
  const uint32_t lb = baddr >> 4;
  if (ACC) mma80<1, 0, 8192, W * 10240>(d, ds, la, ds, lb); else mma80z<1, 0, 8192, W * 10240>(d, ds, la, ds, lb);
  mma80<1, 0, 8192 + 1 * 2048, W * 10240 + 1 * 32>(d, ds, la, ds, lb);
  mma80<1, 0, 8192 + 2 * 2048, W * 10240 + 2 * 32>(d, ds, la, ds, lb);
  mma80<1, 0, 8192 + 3 * 2048, W * 10240 + 3 * 32>(d, ds, la, ds, lb);
}
template <int W, bool ACC>
__device__ __forceinline__ void mma_both(uint64_t ds, float (&dm)[80], float (&dh)[40], uint32_t la, uint32_t baddr) {
  mma_mid<W, ACC>(ds, dh, la, baddr);
  mma_main<W, ACC>(ds, dm, la, baddr);
}
template <int KB, bool ACC>
__device__ __forceinline__ void s_mma(uint64_t ds, float (&sacc)[80], uint32_t la) {
  const uint32_t lb = (SB + OFF_B) >> 4;
  if (ACC) mma160<0, 0, KB * 8192, KB * B_SLOT>(sacc, ds, la, ds, lb); else mma160z<0, 0, KB * 8192, KB * B_SLOT>(sacc, ds, la, ds, lb);
  mma160<0, 0, KB * 8192 + 32, KB * B_SLOT + 32>(sacc, ds, la, ds, lb);
  mma160<0, 0, KB * 8192 + 64, KB * B_SLOT + 64>(sacc, ds, la, ds, lb);
  mma160<0, 0, KB * 8192 + 96, KB * B_SLOT + 96>(sacc, ds, la, ds, lb);
}
template <int N>
__device__ __forceinline__ void store_scaled(uint32_t addr, const float (&d)[N], float sc) {
#pragma unroll
  for (int J = 0; J < N / 8; J++)
    stsm_t(addr + J * 2048, pack2(d[8 * J] * sc, d[8 * J + 1] * sc), pack2(d[8 * J + 2] * sc, d[8 * J + 3] * sc),
           pack2(d[8 * J + 4] * sc, d[8 * J + 5] * sc), pack2(d[8 * J + 6] * sc, d[8 * J + 7] * sc));
}
__device__ __forceinline__ float4 lds_f4(uint32_t a) {
  float4 v;
  asm volatile("ld.shared.v4.f32 {%0,%1,%2,%3}, [%4];" : "=f"(v.x), "=f"(v.y), "=f"(v.z), "=f"(v.w) : "r"(a) : "memory");
  return v;
}
__device__ __forceinline__ void norm_pack(uint32_t* p, const float* d, const float4& i) {
  p[0] = pack2(d[0] * i.x, d[1] * i.y); p[1] = pack2(d[4] * i.z, d[5] * i.w);
  p[2] = pack2(d[2] * i.x, d[3] * i.y); p[3] = pack2(d[6] * i.z, d[7] * i.w);
  asm volatile("" : "+r"(p[0]), "+r"(p[1]), "+r"(p[2]), "+r"(p[3])::"memory");
}
template <int W>
__device__ __forceinline__ void pack_first(uint32_t (&pk)[60], const float (&om)[80], const float (&oh)[40], uint32_t laddr) {
  float4 n0 = lds_f4(laddr + W * 80), n1 = lds_f4(laddr + W * 80 + 16);
#pragma unroll
  for (int J = 0; J < 5; J++) {
    const float4 i = n0;
    n0 = n1;
    if (J + 2 < 5) n1 = lds_f4(laddr + W * 80 + (J + 2) * 16);
    norm_pack(&pk[20 + 4 * J], &om[8 * (5 * W + J)], i);
    norm_pack(&pk[4 * J], &oh[8 * J], i);
  }
}
template <int W, int J0, int J1>
__device__ __forceinline__ void pack_second(uint32_t (&pk)[60], const float (&om)[80], uint32_t laddr) {
  float4 n[J1 - J0];
#pragma unroll
  for (int J = J0; J < J1; J++) n[J - J0] = lds_f4(laddr + (1 - W) * 80 + J * 16);
#pragma unroll
  for (int J = J0; J < J1; J++) norm_pack(&pk[40 + 4 * J], &om[8 * (5 * (1 - W) + J)], n[J - J0]);
}
__device__ __forceinline__ char* o_ptr(int item) {
  const uint32_t t = tid_x();
  return o_slot(item) + ((t & 96) * 16 + (t & 28) * 8 + ((((t >> 1) ^ (t >> 4)) & 1) << 4) + (t & 1) * 8);
}
template <int W, int G0, int G1>
__device__ __forceinline__ void store_groups(char* op, const uint32_t (&pk)[60], uint32_t on) {
#pragma unroll
  for (int G = G0; G < G1; G++) {
    const int off = (G < 5 ? 1 : 2 * W) * B_SLOT + (5 * (G < 10 ? W : 1 - W) + G % 5) * 2048;
    asm volatile("{\n.reg .pred p;\nsetp.ne.u32 p, %5, 0;\n@p st.global.v2.b32 [%0], {%1, %2};\n@p st.global.v2.b32 [%0+256], {%3, %4};\n}\n"
                 ::"l"(op + off), "r"(pk[4 * G]), "r"(pk[4 * G + 1]), "r"(pk[4 * G + 2]), "r"(pk[4 * G + 3]), "r"(on) : "memory");
  }
}
__device__ __forceinline__ void publish_generic(uint32_t bar, int lane) {
  __syncwarp();
  mbar_arrive_if0(bar, lane);
}
__device__ __forceinline__ void publish(uint32_t bar, int lane) {
  proxy_fence();
  __syncwarp();
  mbar_arrive_if0(bar, lane);
}

#define MMA_BEGIN()                                                 \
  asm volatile("add.s64 %0, %0, %1;" : "+l"(ds) : "l"(zero));       \
  wg_fence()
#define A_ADDR(s) (SB + OFF_A + (s) * A_SLOT)
#define B_ADDR(s) (SB + OFF_B + (s) * B_SLOT)
#define WAIT_CHUNK(c, ro, sA)                \
  uint32_t sA;                               \
  {                                          \
    uint32_t pA_;                            \
    ring_pos(ring, (ro) + (c), sA, pA_);     \
    mbar_wait(bud, BAR_FULLA + sA, pA_); \
  }
#define RELEASE_CHUNK(c, sA)                                  \
  mbar_arrive_if0(BAR_EMPTYA + sA, tid);                \
  if ((c) < NSLOT) mbar_arrive_if0(BAR_EMPTYB + xs(c) * 8, tid);

template <int W>
__device__ __forceinline__ int attn_consumer(uint64_t ds, const uint64_t zero, int item) {
  int bud = WAIT_BUDGET;
  const int tid = threadIdx.x & 127, lane = tid & 31;
  const uint32_t laddr = SB + OFF_L + (lane & 3) * 160;
  float om[80], oh[40], sacc[80];
  uint32_t pk[60];
#pragma unroll
  for (int i = 0; i < 40; i++) pk[i] = 0;
  zero_regs(om);
  Ring ring{{0u, 8u, 16u, 24u, 32u}, 0x3E0u * 1025};
  uint32_t par = 0;
  int prev = 0;
  const float qscale = 0.07216878364870322f * 1.4426950408889634f;
  constexpr uint32_t pown = B_ADDR(3 + W), poth = B_ADDR(4 - W);
  TL(0); TLG(62);
  {
    WAIT_CHUNK(0, 0, s0)
    MMA_BEGIN();
    mma_both<W, false>(ds, sacc, oh, s0, B_ADDR(xs(0)));
    wg_commit();
    WAIT_CHUNK(1, 0, s1)
    MMA_BEGIN();
    mma_both<W, true>(ds, sacc, oh, s1, B_ADDR(xs(1)));
    wg_commit();
    wg_wait<1>();
    RELEASE_CHUNK(0, s0)
  }
#pragma unroll 1
  for (int it = 0;; it++) {
    char* op = o_ptr(prev);
#pragma unroll
    for (int c = 2; c < 8 - W; c++) {
      WAIT_CHUNK(c, 0, sA)
      TL(40 + c);
      MMA_BEGIN();
      mma_both<W, true>(ds, sacc, oh, sA, B_ADDR(xs(c)));
      wg_commit();
      wg_wait<1>();
      uint32_t sP, pP;
      ring_pos(ring, c - 1, sP, pP);
      RELEASE_CHUNK(c - 1, sP)
      constexpr int NG = 3;
      if (c == 2) { pack_second<W, 0, 1>(pk, om, laddr); store_groups<W, 0 * NG, 1 * NG>(op, pk, it); }
      if (c == 3) { pack_second<W, 1, 2>(pk, om, laddr); store_groups<W, 1 * NG, 2 * NG>(op, pk, it); }
      if (c == 4) { pack_second<W, 2, 3>(pk, om, laddr); store_groups<W, 2 * NG, 3 * NG>(op, pk, it); }
      if (c == 5) { pack_second<W, 3, 4>(pk, om, laddr); store_groups<W, 3 * NG, 4 * NG>(op, pk, it); }
      if (c == 6) {
        pack_second<W, 4, 5>(pk, om, laddr);
        if (W == 1) {
          wg_wait<0>();
          RELEASE_CHUNK(6, sA)
          mbar_arrive_if0(BAR_XDONE, tid);
        }
        store_groups<W, 4 * NG, 15>(op, pk, it);
        __syncwarp();
        mbar_arrive_if0(BAR_OFULL, lane | (it == 0));
      }
    }
    const uint32_t t_ = tid_x(), st_off = ((t_ & 7) + ((t_ & 16) >> 1)) * 128 + (((((t_ & 96) >> 4) + ((t_ >> 3) & 1)) ^ (t_ & 7)) << 4);
    uint32_t sK0, pK0, s7, p7;
    ring_pos(ring, idxK(W), sK0, pK0);
    ring_pos(ring, 7, s7, p7);
    if (W == 1) mbar_wait(bud, BAR_FULLA + s7, p7);
    WAIT_CHUNK(8, 0, s8)
    if (W == 0) {
      MMA_BEGIN();
      mma_both<W, true>(ds, sacc, oh, s8, B_ADDR(xs(8)));
      wg_commit();
      wg_wait<1>();
      RELEASE_CHUNK(7, s7)
    }
    WAIT_CHUNK(9, 0, s9)
    TL(48);
    if (W == 0) {
      MMA_BEGIN();
      mma_mid<W, true>(ds, oh, s9, B_ADDR(xs(9)));
      wg_commit();
      mma_main<W, true>(ds, sacc, s9, B_ADDR(xs(9)));
      wg_commit();
      bar_arrive(5, 256);
      TL(49);
      wg_wait<1>();
      reg_fence(oh);
      mbar_wait(bud, BAR_XDONE, par);
      store_scaled(B_ADDR(1) + st_off, oh, qscale);
    } else {
      bar_sync(5, 256);
      MMA_BEGIN();
      mma_mid<W, true>(ds, oh, s7, B_ADDR(xs(7)));
      mma_mid<W, true>(ds, oh, s8, B_ADDR(xs(8)));
      mma_mid<W, true>(ds, oh, s9, B_ADDR(xs(9)));
      wg_commit();
      mma_main<W, true>(ds, sacc, s7, B_ADDR(xs(7)));
      wg_commit();
      mma_main<W, true>(ds, sacc, s8, B_ADDR(xs(8)));
      wg_commit();
      wg_wait<2>();
      reg_fence(oh);
      store_scaled(B_ADDR(1) + 10240 + st_off, oh, qscale);
      MMA_BEGIN();
      mma_main<W, true>(ds, sacc, s9, B_ADDR(xs(9)));
      wg_commit();
      bar_arrive(8, 256);
      TL(49);
      wg_wait<2>();
      RELEASE_CHUNK(7, s7)
      publish(BAR_QH, lane);
    }
    wg_wait<0>();
    reg_fence(sacc);
    TL(1);
    RELEASE_CHUNK(8, s8)
    RELEASE_CHUNK(9, s9)
    store_scaled(B_ADDR(2 * W) + st_off, sacc, qscale);
    if (W == 1) publish(BAR_QM, lane); else proxy_fence();
    TL(2);
    uint32_t sK = sK0, sV1 = 0;
    if (W == 0) {
      zero_regs(om); zero_regs(oh);
      reg_fence(om); reg_fence(oh);
      mbar_wait(bud, BAR_FULLA + sK0, pK0);
      bar_sync(8, 256);
      MMA_BEGIN();
      s_mma<0, false>(ds, sacc, sK);
      mbar_wait(bud, BAR_QH, par);
      TL(3);
      MMA_BEGIN();
      s_mma<1, true>(ds, sacc, sK);
      mbar_wait(bud, BAR_QM, par);
      TL(5);
      MMA_BEGIN();
      s_mma<2, true>(ds, sacc, sK);
      wg_commit();
      wg_commit();
      bar_arrive(2, 256);
    } else {
      uint32_t pV1;
      ring_pos(ring, idxV(0), sV1, pV1);
      mbar_wait(bud, BAR_FULLA + sK, pK0);
      bar_sync(2, 256);
      MMA_BEGIN();
      s_mma<0, false>(ds, sacc, sK);
      s_mma<1, true>(ds, sacc, sK);
      s_mma<2, true>(ds, sacc, sK);
      wg_commit();
      TL(6);
      mbar_wait(bud, BAR_FULLA + sV1, pV1);
      mbar_wait(bud, BAR_PFULL, 0);
      TL(7);
      MMA_BEGIN();
      mma_both<W, false>(ds, om, oh, sV1, poth);
      wg_commit();
      bar_arrive(1, 256);
    }
#pragma unroll 1
    for (int jj = 0;; jj++) {
      wg_wait<1>();
      reg_fence(sacc);
      TL(8 + jj * 7);
      mbar_arrive2_if0(BAR_EMPTYA + sK, tid);
      mbar_arrive_if0(BAR_EMPTYB + tid * 8, (tid >= 3) | (jj != 3));
#pragma unroll
      for (int J = 0; J < 10; J++) {
        stsm_t(pown + st_off + J * 2048, pack2(ex2(sacc[8 * J]), ex2(sacc[8 * J + 1])), pack2(ex2(sacc[8 * J + 2]), ex2(sacc[8 * J + 3])),
               pack2(ex2(sacc[8 * J + 4]), ex2(sacc[8 * J + 5])), pack2(ex2(sacc[8 * J + 6]), ex2(sacc[8 * J + 7])));
        if (W == 1 && (J == 2 || J == 5)) publish_generic(BAR_PMID + (J / 3) * 8, lane | (jj != 3));
        if (J == 4) {
          wg_wait<0>();
          mbar_arrive_if0(BAR_EMPTYA + sV1, tid | (W == 0 && jj == 0));
        }
      }
      publish(BAR_PFULL + W * 8, lane);
      TL(10 + jj * 7);
      if (jj == 3) break;
      uint32_t sV, pV, pK, pV1;
      ring_pos(ring, idxV(W), sV, pV);
      ring_pos(ring, idxV(W) + 1, sK, pK);
      ring_pos(ring, idxV(W) + 2, sV1, pV1);
      mbar_wait(bud, BAR_FULLA + sV, pV);
      bar_sync(1 + W, 256);
      MMA_BEGIN();
      mma_both<W, true>(ds, om, oh, sV, pown);
      wg_commit();
      mbar_wait(bud, BAR_FULLA + sK, pK);
      TL(11 + jj * 7);
      MMA_BEGIN();
      s_mma<0, false>(ds, sacc, sK);
      s_mma<1, true>(ds, sacc, sK);
      wg_commit();
      wg_wait<1>();
      mbar_arrive_if0(BAR_EMPTYA + sV, tid);
      MMA_BEGIN();
      s_mma<2, true>(ds, sacc, sK);
      wg_commit();
      TL(13 + jj * 7);
      mbar_wait(bud, BAR_FULLA + sV1, pV1);
      mbar_wait(bud, BAR_PFREE + W * 8, jj & 1);
      mbar_wait(bud, BAR_PFULL + (1 - W) * 8, (jj + W) & 1);
      TL(14 + jj * 7);
      MMA_BEGIN();
      mma_both<W, true>(ds, om, oh, sV1, poth);
      wg_commit();
      bar_arrive(2 - W, 256);
      ring_advance(ring, 4);
    }
    uint32_t sV7, pV7;
    ring_pos(ring, idxV(7) - 12, sV7, pV7);
    prev = item;
    if (W == 1 && !DEBUG_TIMEOUT) item = next_item();
    if (W == 0) {
      uint32_t sV6, pV6;
      ring_pos(ring, idxV(6) - 12, sV6, pV6);
      mbar_wait(bud, BAR_FULLA + sV6, pV6);
      bar_sync(1, 256);
      MMA_BEGIN();
      mma_both<0, true>(ds, om, oh, sV6, pown);
      wg_commit();
      mbar_wait(bud, BAR_FULLA + sV7, pV7);
      wg_wait<0>();
      mbar_arrive_if0(BAR_EMPTYA + sV6, tid);
      mbar_wait(bud, BAR_PFULL + 8, 1);
      MMA_BEGIN();
      mma_both<0, true>(ds, om, oh, sV7, poth);
      wg_commit();
      bar_arrive(6, 256);
    } else {
      mbar_wait(bud, BAR_FULLA + sV7, pV7);
      bar_sync(6, 256);
    }
    TL(32);
    if (DEBUG_TIMEOUT) item = next_item(NEXT_ITEM + 4);
    else if (W == 0) item = next_item();
    if (item >= NITEMS) {
      if (W == 1) {
        MMA_BEGIN();
        mma_both<1, true>(ds, om, oh, sV7, pown);
        wg_commit();
      }
      wg_wait<0>();
      reg_fence(om); reg_fence(oh);
      TL(33);
      mbar_wait(bud, BAR_LFULL, par);
      mbar_arrive_if0(BAR_FREE, tid);
      TL(34);
      pack_first<W>(pk, om, oh, laddr);
      op = o_ptr(prev);
      store_groups<W, 0, 10>(op, pk, 1);
      pack_second<W, 0, 5>(pk, om, laddr);
      store_groups<W, 10, 15>(op, pk, 1);
      publish_generic(BAR_OFULL, lane);
      TL(35); TLG(63);
      TL_FLUSH();
      return item;
    }
    {
      if (W == 1) {
        MMA_BEGIN();
        mma_both<1, true>(ds, om, oh, sV7, pown);
        wg_commit();
      }
      WAIT_CHUNK(0, 26 - 12, s0)
      WAIT_CHUNK(1, 26 - 12, s1)
      if (W == 0) {
        wg_wait<0>();
        reg_fence(om); reg_fence(oh);
        TL(33);
        MMA_BEGIN();
        mma_main<W, false>(ds, sacc, s0, B_ADDR(xs(0)));
        wg_commit();
      } else {
        MMA_BEGIN();
        mma_main<W, false>(ds, sacc, s0, B_ADDR(xs(0)));
        mma_main<W, true>(ds, sacc, s1, B_ADDR(xs(1)));
        wg_commit();
        wg_wait<1>();
        reg_fence(om); reg_fence(oh);
        TL(33);
      }
      mbar_arrive_if0(BAR_EMPTYA + sV7, tid);
      mbar_wait(bud, BAR_LFULL, par);
      mbar_arrive_if0(BAR_EMPTYB + 24 + tid * 8, tid >= 2);
      TL(34);
      pack_first<W>(pk, om, oh, laddr);
      TL(36);
      MMA_BEGIN();
      mma_mid<W, false>(ds, oh, s0, B_ADDR(xs(0)));
      wg_commit();
      mma_mid<W, true>(ds, oh, s1, B_ADDR(xs(1)));
      if (W == 0) mma_main<W, true>(ds, sacc, s1, B_ADDR(xs(1)));
      wg_commit();
      TL(37);
      wg_wait<1>();
      RELEASE_CHUNK(0, s0)
      TL(35); TLG(63);
    }
    TL_FLUSH();
    TL(0); TLG(62);
    ring_advance(ring, 26 - 12);
    par ^= 1;
  }
}

__device__ __forceinline__ uint4 lds128(uint32_t a) {
  uint4 v;
  asm volatile("ld.shared.v4.b32 {%0,%1,%2,%3}, [%4];" : "=r"(v.x), "=r"(v.y), "=r"(v.z), "=r"(v.w) : "r"(a) : "memory");
  return v;
}
__device__ __forceinline__ void acc2(float& s, float& t, uint32_t w) {
  s += __uint_as_float(w << 16);
  t += __uint_as_float(w & 0xffff0000u);
}
__device__ __forceinline__ uint32_t badd2(uint32_t a, uint32_t b) { uint32_t r; asm("add.rn.bf16x2 %0, %1, %2;" : "=r"(r) : "r"(a), "r"(b)); return r; }
__device__ __forceinline__ void sum_unit(float& acc, uint32_t pb) {
  const uint4 v0 = lds128(pb), v1 = lds128(pb ^ 32), v2 = lds128(pb ^ 64), v3 = lds128(pb ^ 96);
  const uint32_t w0 = badd2(badd2(v0.x, v0.y), badd2(v0.z, v0.w));
  float s = acc + __uint_as_float(w0 << 16), t = __uint_as_float(w0 & 0xffff0000u);
  acc2(s, t, badd2(badd2(v1.x, v1.y), badd2(v1.z, v1.w)));
  acc2(s, t, badd2(badd2(v2.x, v2.y), badd2(v2.z, v2.w)));
  acc2(s, t, badd2(badd2(v3.x, v3.y), badd2(v3.z, v3.w)));
  acc = s + t;
}
__device__ __forceinline__ float bf_lo(uint32_t w) { return __uint_as_float(w << 16); }
__device__ __forceinline__ float bf_hi(uint32_t w) { return __uint_as_float(w & 0xffff0000u); }
__device__ __forceinline__ float bf_rn(float x) { return __bfloat162float(__float2bfloat16(x)); }
__device__ __forceinline__ void slow_item(const Params& p, int item, int hw) {
  const int blk = item >> 9, h = (item >> 4) & 31, b = item & 15;
#pragma unroll 1
  for (int n = hw; n < SQ; n += 3) {
    float q[6] = {0.f, 0.f, 0.f, 0.f, 0.f, 0.f};
    {
      const uint32_t* xr = (const uint32_t*)(p.xp[blk] + (size_t)(b * SQ + n) * DM);
      const uint32_t* wq = (const uint32_t*)(p.wqp[blk] + h * DH) + (tid_x() & 31);
#pragma unroll 2
      for (int k = 0; k < DM / 2; k++) {
        const uint32_t xv = xr[k];
#pragma unroll
        for (int i = 0; i < 3; i++) {
          const uint32_t w0 = wq[i * 32], w1 = wq[NH * DH / 2 + i * 32];
          q[2 * i] = fmaf(bf_lo(xv), bf_lo(w0), fmaf(bf_hi(xv), bf_lo(w1), q[2 * i]));
          q[2 * i + 1] = fmaf(bf_lo(xv), bf_hi(w0), fmaf(bf_hi(xv), bf_hi(w1), q[2 * i + 1]));
        }
        wq += NH * DH;
      }
    }
    const uint32_t q0 = pack2(q[0], q[1]), q1 = pack2(q[2], q[3]), q2 = pack2(q[4], q[5]);
    float o[6] = {0.f, 0.f, 0.f, 0.f, 0.f, 0.f}, m = -INFINITY, l = 0.f;
    const uint32_t* kg = (const uint32_t*)(p.kp[blk] + (size_t)(b * NH + h) * SK * DH) + (tid_x() & 31);
    const uint32_t* vg = (const uint32_t*)(p.vp[blk] + (size_t)(b * NH + h) * SK * DH) + (tid_x() & 31);
#pragma unroll 1
    for (int k = 0; k < SK; k++) {
      const uint32_t k0 = kg[0], k1 = kg[32], k2 = kg[64], v0 = vg[0], v1 = vg[32], v2 = vg[64];
      kg += DH / 2; vg += DH / 2;
      float sc = fmaf(bf_lo(q0), bf_lo(k0), bf_hi(q0) * bf_hi(k0));
      sc = fmaf(bf_lo(q1), bf_lo(k1), fmaf(bf_hi(q1), bf_hi(k1), sc));
      sc = fmaf(bf_lo(q2), bf_lo(k2), fmaf(bf_hi(q2), bf_hi(k2), sc));
#pragma unroll
      for (int d = 16; d; d >>= 1) sc += __shfl_xor_sync(0xffffffffu, sc, d);
      sc = bf_rn(bf_rn(sc) * 0.07216878364870322f);
      const float mn = fmaxf(m, sc), a = ex2((m - mn) * 1.4426950408889634f), pr = ex2((sc - mn) * 1.4426950408889634f);
      m = mn;
      l = fmaf(l, a, pr);
      o[0] = fmaf(o[0], a, pr * bf_lo(v0)); o[1] = fmaf(o[1], a, pr * bf_hi(v0));
      o[2] = fmaf(o[2], a, pr * bf_lo(v1)); o[3] = fmaf(o[3], a, pr * bf_hi(v1));
      o[4] = fmaf(o[4], a, pr * bf_lo(v2)); o[5] = fmaf(o[5], a, pr * bf_hi(v2));
    }
    float inv;
    asm("rcp.approx.ftz.f32 %0, %1;" : "=f"(inv) : "f"(l));
    const int lane = tid_x() & 31;
    const int r = n & 15, c = 4 * ((r & 7) >> 1) + 2 * (r >> 3) + (r & 1);
    char* on = o_slot(item) + (lane >> 2) * 256 + (lane & 3) * 64 + (n >> 4) * 2048 +
               (((c >> 3) ^ ((lane >> 1) & 1)) << 4) + (c & 7) * 2;
#pragma unroll
    for (int i = 0; i < 3; i++) {
      *(__nv_bfloat16*)(on + i * B_SLOT) = __float2bfloat16(o[2 * i] * inv);
      *(__nv_bfloat16*)(on + i * B_SLOT + 32) = __float2bfloat16(o[2 * i + 1] * inv);
    }
  }
}
__device__ __forceinline__ void attn_helper(const Params& p, int hw, int item, int epoch) {
  int bud = WAIT_BUDGET;
  if (hw == 2) {
    if (item == 0 && elect_one()) {
      *(volatile int*)&g_ticket = 0;
      asm volatile("red.release.gpu.global.add.s32 [%0], 1;" ::"l"(&g_go) : "memory");
    }
    __syncwarp();
    flag_wait(bud, &g_go, epoch + 1);
  }
  if (item < PF_N && hw < 2) {
    const char* g = (const char*)(hw ? p.vp[0] : p.kp[0]) + (size_t)(((item & 15) * NH + (item >> 4)) * SK) * DH * 2;
    const long long t0 = clock64();
#pragma unroll 1
    for (int i = 0; i < 32; i++) {
      while (clock64() - t0 < PF_WAIT + i * PF_GAP) __nanosleep(50);
      for (int k = 0; k < 6; k++) asm volatile("prefetch.global.L2 [%0];" ::"l"(g + i * 6144 + k * 1024 + (tid_x() & 31) * 32));
      __syncwarp();
    }
  }
#pragma unroll 1
  for (int it = 0; item < NITEMS; it++) {
    const uint32_t par = it & 1;
    int lane = tid_x() & 31;
    const int r = lane >> 1;
    const uint32_t a0 = B_ADDR(3) + (16 * hw + r) * 128 + (lane & 1) * 16 + ((r & 3) << 5);
    float acc[4] = {0.f, 0.f, 0.f, 0.f};
#pragma unroll 1
    for (int j = 0; j < 8; j++) {
      const uint32_t pb = a0 + (j & 1) * B_SLOT, bfull = BAR_PFULL + (j & 1) * 8, pfull = (j >> 1) & 1;
      mbar_wait(bud, j == 7 ? BAR_PMID : bfull, j == 7 ? par : pfull);
      sum_unit(acc[0], pb);
      if (j == 7) mbar_wait(bud, BAR_PMID + 8, par);
      sum_unit(acc[1], pb + 6144);
      if (j == 7) mbar_wait(bud, bfull, pfull);
      sum_unit(acc[2], pb + 2 * 6144);
      if (hw == 0) sum_unit(acc[3], pb + 3 * 6144);
      __syncwarp();
      mbar_arrive_if0(BAR_PFREE + (j & 1) * 8, lane);
      if (j == 5 && hw == 2) {
        if (lane == 0) TLP(60);
        if (item >= ORING && item < OFRESH) flag_wait(bud, &g_done[item - ORING], (epoch + 1) * 2);
        if (lane == 0) TLP(61);
      }
    }
    bool bad = false;
    const uint32_t la = SB + OFF_L + (((r & 7) >> 1) * 40 + 2 * (r >> 3) + (r & 1) + 4 * hw) * 4;
#pragma unroll
    for (int u = 0; u < 4; u++) {
      const float l = acc[u] + __shfl_xor_sync(0xffffffffu, acc[u], 1);
      if (u < 3 || hw == 0) {
        bad |= !(l >= 9.094947017729282e-13f && l <= 1.099511627776e12f);
        float inv;
        asm("rcp.approx.ftz.f32 %0, %1;" : "=f"(inv) : "f"(l));
        asm volatile("st.shared.f32 [%0], %1;" ::"r"(la + u * 48), "f"(inv) : "memory");
      }
    }
    publish_generic(BAR_LFULL, lane);
    if (lane == 0) TLP(40 + hw * 4);
    uint32_t anybad;
    asm volatile("{\n.reg .pred p, q;\nsetp.ne.u32 p, %1, 0;\nbarrier.red.or.pred q, 7, 96, p;\nselp.u32 %0, 1, 0, q;\n}\n"
                 : "=r"(anybad) : "r"((uint32_t)bad) : "memory");
    if (__any_sync(0xffffffffu, anybad)) {
      mbar_wait(bud, BAR_OFULL, par);
      slow_item(p, item, hw);
      bar_sync(7, 96);
    }
    if (hw == 1) {
      mbar_wait(bud, BAR_OFULL, par);
      if ((tid_x() & 31) == 0) {
        TLP(41 + hw * 4);
        asm volatile("red.release.gpu.global.add.s32 [%0], 1;" ::"l"(&g_ready[item]) : "memory");
        TLP(42 + hw * 4);
      }
      __syncwarp();
    }
    item = next_item();
  }
}

__device__ __forceinline__ int attn_producer(const Params& p, int item) {
  int bud = WAIT_BUDGET;
  uint32_t sa = 0, pa = 1;
  const uint64_t pol = evict_first_policy();
  const bool draws = item >= N_OCTA;
  const int delay = start_delay(item);
  {
    const long long t0 = clock64();
    while (clock64() - t0 < delay) __nanosleep(100);
  }
#pragma unroll 1
  for (int it = 0; item < NITEMS; it++) {
    const int blk = item >> 9, h = (item >> 4) & 31, b = item & 15;
    const int row0 = (b * NH + h) * SK;
    if (!(it | delay)) pa = 0;
#pragma unroll 1
    for (int c = (it | delay) ? 0 : NSLOT; c < 10; c++) {
      const uint32_t sx = c < NSLOT ? c : c - NSLOT;
      mbar_wait(bud, BAR_EMPTYA + sa * 8, pa);
      TLP(c);
      mbar_expect(BAR_FULLA + sa * 8, A_SLOT + B_SLOT);
      tma3d(A_ADDR(sa), &p.wq[blk], BAR_FULLA + sa * 8, 0, c * 64, h * 3);
      mbar_wait(bud, BAR_EMPTYB + sx * 8, c < NSLOT);
      TLP(10 + c);
      tma2d(B_ADDR(sx), &p.x[blk], BAR_FULLA + sa * 8, c * 64, b * SQ);
      if (++sa == NSLOT) { sa = 0; pa ^= 1; }
    }
#pragma unroll 1
    for (int i = 0; i < 16; i++) {
      const bool isK = (i == 0) || ((i & 1) && i < 15);
      const int j = i == 0 ? 0 : (i == 15 ? 7 : (isK ? (i + 1) >> 1 : (i - 2) >> 1));
      mbar_wait(bud, BAR_EMPTYA + sa * 8, pa);
      TLP(20 + i);
      mbar_expect(BAR_FULLA + sa * 8, A_SLOT);
      tma3d_hint(A_ADDR(sa), isK ? &p.k[blk] : &p.v[blk], BAR_FULLA + sa * 8, 0, row0 + j * 64, 0, pol);
      if (i == 12) {
        item = draws ? NCTA + atomicAdd(&g_ticket, 1) : NITEMS;
        asm volatile("st.shared.s32 [%0], %1;" ::"r"(NEXT_ITEM), "r"(item) : "memory");
      }
      if (++sa == NSLOT) { sa = 0; pa ^= 1; }
    }
  }
  return item;
}

struct OJob { int tile, part, c0, n; };
__device__ __forceinline__ OJob get_ojob(int cta, int last) {
  if (cta < N_OCTA) return OJob{cta, 0, 0, CHUNK1};
  const int u = last - NITEMS, part = 1 + (u >> 5), tile = part == 3 ? 95 - u : u & 31;
  const int c1 = CHUNK1, c2 = c1 + LEN1 - ((tile * LSLOPE1 + 16) >> 5), c3 = c2 + LEN2 - ((tile * LSLOPE2 + 16) >> 5);
  return OJob{tile, part, part == 1 ? c1 : part == 2 ? c2 : c3, part == 1 ? c2 - c1 + 1 : part == 2 ? c3 - c2 + 1 : part == 3 ? 189 - c3 + 1 : 0};
}
__device__ __forceinline__ int unperm(int c) { return 8 * ((c >> 1) & 1) + 4 * (c >> 3) + 2 * ((c >> 2) & 1) + (c & 1); }
__device__ __forceinline__ uint32_t first_stage(const OJob& job) { return job.part ? (uint32_t)(300 - job.n) % 3 : 0; }

__device__ __forceinline__ void oproj_consumer(const Params& p, const OJob job, const int W) {
  int bud = WAIT_BUDGET;
  const int tid = tid_x() & 127, lane = tid & 31, warp = tid >> 5;
  float a0[80], a1[80], ah[40];
  zero_regs(a0); zero_regs(a1); zero_regs(ah);
  const uint64_t dam = p.dsw + W * (3 * 8192 >> 4), dbh = p.dso + W * (10240 >> 4);
  int left = job.n, step = 0;
  uint32_t st = first_stage(job), ph = 0;
#pragma unroll 1
  while (left) {
    const int nc = left > 3 * NH ? 3 * NH : left;
    left -= nc;
#pragma unroll 1
    for (int c = 0; c < nc; c++) {
      mbar_wait(bud, BAR_GFULL + st * 8, (ph >> st) & 1);
      ph ^= 1 << st;
      bar_sync_if0(11, W | (c + 1 - nc));
      wg_fence();
      const uint32_t la = st, lb = st;
#define O_STEP(ks, sc)                                                        \
  mma80r<1, 1, 2 * 8192 + ks * 2048, SB + O_AB + ks * 512>(ah, p.dsw, la, dbh, lb, sc);   \
  mma160r<1, 1, ks * 2048, SB + O_AB + ks * 512>(a0, dam, la, p.dso, lb, sc);             \
  mma160r<1, 1, 8192 + ks * 2048, SB + O_AB + ks * 512>(a1, dam, la, p.dso, lb, sc);
      O_STEP(0, c != 0) O_STEP(1, 1)
      wg_commit();
      wg_wait<1>();
      mbar_arrive_if0(BAR_GEMPTY + (st == 0 ? 2 : st - 1) * 8, tid | (c == 0));
      wg_fence();
      O_STEP(2, 1) O_STEP(3, 1)
#undef O_STEP
      wg_commit();
      if (++st == 3) {
        st = 0;
        asm volatile("{\n.reg .pred p;\nsetp.eq.u32 p, %1, 0;\n@p red.relaxed.gpu.global.add.s32 [%0], 1;\n}\n"
                     ::"l"(&g_done[step * 16 + (job.tile >> 1)]), "r"(tid | job.part | W) : "memory");
        TLG(step);
        step++;
      }
    }
    if (W) bar_arrive(11, 256);
    wg_wait<0>();
    reg_fence(a0); reg_fence(a1); reg_fence(ah);
    mbar_arrive_if0(BAR_GEMPTY + (st - 1) * 8, tid | (st == 0));
    TLG(63);
    const int prow = (lane & 7) + 8 * (lane >> 4), qrow = left ? unperm(prow) : prow;
    const uint32_t sg = SB + O_OUT + qrow * 128 + (((2 * warp + ((lane >> 3) & 1)) ^ (qrow & 7)) << 4);
    if (W) bar_arrive(3, 256); else bar_arrive(9, 256);
    bar_sync_if0(3, W);
    store_scaled(sg + W * 3 * B_SLOT, a0, 1.0f);
    publish(BAR_GOUT + W * 24, lane);
    store_scaled(sg + W * 3 * B_SLOT + B_SLOT, a1, 1.0f);
    publish(BAR_GOUT + W * 24 + 8, lane);
    bar_sync_if0(9, W - 1);
    store_scaled(sg + 2 * B_SLOT + W * 10240, ah, 1.0f);
    publish(BAR_GOUT + 16, lane);
  }
  TL_FLUSH();
  TLG(0);
  float acc[7][8];
  uint32_t in[7], blk[7], oo[7];
#pragma unroll
  for (int i = 0; i < 7; i++) {
    const int e = min(i * 256 + W * 128 + tid, 1599), r = e / 40, cc = e % 40, R = job.part * 40 + r;
    in[i] = r * 128 + (((cc ^ r) & 7) << 4);
    blk[i] = cc >> 3;
    oo[i] = ((R & ~15) + unperm(R & 15)) * (2 * DM / 8) + cc;
    asm volatile("" : "+r"(oo[i]));
#pragma unroll
    for (int k = 0; k < 8; k++) acc[i][k] = 0.f;
  }
  bar_sync(10, 256);
#pragma unroll 1
  for (int q = 0; q < 4; q++) {
    if (q) mbar_wait(bud, BAR_GRED + (q - 1) * 8, 0);
    if (q == 3) TLG(1);
    const uint32_t base = q ? SB + (q - 1) * 25600 : SB + O_OUT + job.part * 5120, bs = q ? 5120 : B_SLOT;
    uint4 v[7];
#pragma unroll
    for (int i = 0; i < 7; i++) v[i] = lds128(base + blk[i] * bs + in[i]);
#pragma unroll
    for (int i = 0; i < 7; i++) {
      acc[i][0] += bf_lo(v[i].x); acc[i][1] += bf_hi(v[i].x); acc[i][2] += bf_lo(v[i].y); acc[i][3] += bf_hi(v[i].y);
      acc[i][4] += bf_lo(v[i].z); acc[i][5] += bf_hi(v[i].z); acc[i][6] += bf_lo(v[i].w); acc[i][7] += bf_hi(v[i].w);
    }
  }
  uint4* go = (uint4*)p.outp + (job.tile >> 1) * SQ * (2 * DM / 8) + DM / 8 + (job.tile & 1) * 40;
#pragma unroll
  for (int i = 0; i < 7; i++) {
    if (i * 256 + W * 128 + tid < 1600)
      go[oo[i]] = make_uint4(pack2(acc[i][0], acc[i][1]), pack2(acc[i][2], acc[i][3]), pack2(acc[i][4], acc[i][5]), pack2(acc[i][6], acc[i][7]));
  }
  TLG(2);
  TL_FLUSH();
}

__device__ __forceinline__ void oproj_producer(const Params& p, const OJob job, int target) {
  int bud = WAIT_BUDGET;
  const uint64_t polo = evict_first_policy();
  mbar_wait(bud, BAR_FREE, 0);
  uint32_t st = first_stage(job), ph = 7;
  int seen = -1;
#pragma unroll 1
  for (int i = 0; i < job.n; i++) {
    const int c = job.part && i == job.n - 1 ? 188 + job.part : job.c0 + i, step = c / 3, kb = c - 3 * step;
    const int item = step * 16 + (job.tile >> 1);
    if (step != seen) {
      flag_wait(bud, &g_ready[item], target);
      asm volatile("fence.proxy.async.global;" ::: "memory");
      seen = step;
    }
    const uint32_t dst = SB + st * O_STAGE, bar = BAR_GFULL + st * 8;
    const char* og = o_slot(item) + kb * B_SLOT;
    mbar_wait(bud, BAR_GEMPTY + st * 8, (ph >> st) & 1);
    ph ^= 1 << st;
    mbar_expect(bar, O_STAGE);
    tma3d(dst, &p.wo[step >> 5], bar, 0, (c - (step >> 5) * 3 * NH) * 64, (job.tile & 1) * 5);
    bulk_load_hint(dst + O_AB, og, B_SLOT, bar, polo);
    if (++st == 3) st = 0;
  }
  mbar_wait(bud, BAR_GEMPTY, ph & 1);
  mbar_wait(bud, BAR_GEMPTY + 8, (ph >> 1) & 1);
  uint32_t todo = 15 & ~(1 << job.part), dst = SB, bar = BAR_GRED;
  while (todo) {
    int v0, v1, v2, v3;
    asm volatile("ld.acquire.gpu.global.v4.s32 {%0, %1, %2, %3}, [%4];" : "=r"(v0), "=r"(v1), "=r"(v2), "=r"(v3) : "l"(&g_pcnt[job.tile * 4]) : "memory");
    const uint32_t rdy = --bud > 0 ? (v0 - target >= 0) | (v1 - target >= 0) << 1 | (v2 - target >= 0) << 2 | (v3 - target >= 0) << 3 : 15;
    if (!(rdy & todo)) continue;
    asm volatile("fence.proxy.async.global;" ::: "memory");
#pragma unroll 1
    for (int q = 0; q < 4; q++) {
      if (!(((rdy & todo) >> q) & 1)) continue;
      TLE(4 + q);
      mbar_expect(bar, 25600);
      for (int k = 0; k < 5; k++)
        tma2d(dst + k * 5120, &p.part, bar, (job.tile & 1) * 320 + k * 64, q * NB * SQ + (job.tile >> 1) * SQ + job.part * 40);
      todo &= ~(1 << q);
      dst += 25600;
      bar += 8;
    }
  }
}

__device__ __forceinline__ void oproj_storer(const Params& p, const OJob job) {
  int bud = WAIT_BUDGET;
  const int col = (job.tile & 1) * 320, row = (job.tile >> 1) * SQ;
  if (job.part == 0) {
    for (int k = 0; k < 3; k++) {
      mbar_wait(bud, BAR_GOUT + k * 8, 0);
      tma_store2d(&p.out, SB + O_OUT + k * B_SLOT, col + k * 64, row);
    }
    asm volatile("cp.async.bulk.commit_group;" ::: "memory");
    asm volatile("cp.async.bulk.wait_group.read 0;" ::: "memory");
    mbar_arrive2_if0(BAR_GEMPTY + 16, 0);
    mbar_wait(bud, BAR_GFULL + 16, 0);
    for (int k = 3; k < 5; k++) {
      mbar_wait(bud, BAR_GOUT + k * 8, 0);
      tma_store2d(&p.out, SB + O_OUT + k * B_SLOT, col + k * 64, row);
      asm volatile("cp.async.bulk.commit_group;" ::: "memory");
      asm volatile("cp.async.bulk.wait_group.read 0;" ::: "memory");
      __nanosleep(1000);
    }
  }
#pragma unroll 1
  for (int i = 0; i < 5; i++) {
    const int k = (0x21043 >> (4 * i)) & 15;
    mbar_wait(bud, BAR_GOUT + k * 8, job.part == 0);
    if (i == 0) TLE(0);
    for (int q = 1; q < 4; q++) {
      const int sh = (job.part + q) & 3;
      tma_store2d(&p.part, SB + O_OUT + k * B_SLOT + sh * 5120, col + k * 64, job.part * NB * SQ + row + sh * 40);
    }
  }
  asm volatile("cp.async.bulk.commit_group;" ::: "memory");
  TLE(1);
  asm volatile("cp.async.bulk.wait_group 0;" ::: "memory");
  TLE(2);
  asm volatile("fence.proxy.async.global;" ::: "memory");
  asm volatile("red.release.gpu.global.add.s32 [%0], 1;" ::"l"(&g_pcnt[job.tile * 4 + job.part]) : "memory");
  TLE(3);
}

__global__ void __launch_bounds__(384, 1) fused_kernel(const __grid_constant__ Params p) {
  extern __shared__ __align__(1024) char smem_raw[];
  if ((smem_u32(smem_raw) & 0xFFFFFFu) != SB) return;
  const int cta = (((blockIdx.x / PERM_G) * PERM_M) % (NCTA / PERM_G)) * PERM_G + (blockIdx.x % PERM_G);
  const int warp = __shfl_sync(0xffffffffu, threadIdx.x >> 5, 0);
  if (threadIdx.x == 0) {
    for (int i = 0; i < NSLOT; i++) { mbar_init(BAR_FULLA + i * 8, 1); mbar_init(BAR_EMPTYA + i * 8, 2); mbar_init(BAR_EMPTYB + i * 8, 2); }
    proxy_fence();
    if (start_delay(cta) == 0) {
#pragma unroll 1
      for (int c = 0; c < NSLOT; c++) {
        mbar_expect(BAR_FULLA + c * 8, A_SLOT + B_SLOT);
        tma3d(A_ADDR(c), &p.wq[0], BAR_FULLA + c * 8, 0, c * 64, (cta >> 4) * 3);
        tma2d(B_ADDR(c), &p.x[0], BAR_FULLA + c * 8, c * 64, (cta & 15) * SQ);
      }
    }
  }
  if (threadIdx.x == 64) {
    mbar_init(BAR_XDONE, 1); mbar_init(BAR_QH, 4); mbar_init(BAR_QM, 4);
    mbar_init(BAR_PFULL, 4); mbar_init(BAR_PFULL + 8, 4); mbar_init(BAR_PFREE, 3); mbar_init(BAR_PFREE + 8, 3);
    mbar_init(BAR_LFULL, 3); mbar_init(BAR_PMID, 4); mbar_init(BAR_PMID + 8, 4); mbar_init(BAR_OFULL, 8);
  }
  if (threadIdx.x == 96) {
    for (int i = 0; i < O_NST; i++) { mbar_init(BAR_GFULL + i * 8, 1); mbar_init(BAR_GEMPTY + i * 8, 2); }
    for (int i = 0; i < 5; i++) mbar_init(BAR_GOUT + i * 8, i == 2 ? 8 : 4);
    mbar_init(BAR_GRED, 1); mbar_init(BAR_GRED + 8, 1); mbar_init(BAR_GRED + 16, 1); mbar_init(BAR_FREE, 2);
    proxy_fence();
  }
  __syncthreads();
  if (warp >= 8) {
    asm volatile("setmaxnreg.dec.sync.aligned.u32 40;");
    if (warp == 8) {
      if (elect_one()) {
        const OJob job = get_ojob(cta, attn_producer(p, cta));
        const int epoch = *(volatile int*)&g_epoch[cta];
        *(volatile int*)&g_epoch[cta] = epoch + 1;
        if (job.n) oproj_producer(p, job, epoch + 1);
      }
    } else {
      const int epoch = __shfl_sync(0xffffffffu, *(volatile int*)&g_epoch[cta], 0);
      attn_helper(p, warp - 9, cta, epoch);
      if (warp == 9) {
        const OJob job = get_ojob(cta, next_item());
        if (job.n && elect_one()) oproj_storer(p, job);
      }
    }
  } else {
    asm volatile("setmaxnreg.inc.sync.aligned.u32 232;");
    const OJob job = get_ojob(cta, warp < 4 ? attn_consumer<0>(p.dsw, p.zero, cta) : attn_consumer<1>(p.dsw, p.zero, cta));
    if (job.n) oproj_consumer(p, job, warp >> 2);
  }
}

typedef CUresult (*EncodeFn)(CUtensorMap*, CUtensorMapDataType, cuuint32_t, void*, const cuuint64_t*, const cuuint64_t*, const cuuint32_t*,
                             const cuuint32_t*, CUtensorMapInterleave, CUtensorMapSwizzle, CUtensorMapL2promotion, CUtensorMapFloatOOBfill);

void make3d(EncodeFn enc, CUtensorMap* m, const void* ptr, uint64_t rows, uint64_t cols, uint32_t box_rows, uint32_t box_blocks,
            CUtensorMapL2promotion promo = CU_TENSOR_MAP_L2_PROMOTION_L2_128B) {
  cuuint64_t gd[3] = {64, rows, cols / 64};
  cuuint64_t gs[2] = {cols * 2, 128};
  cuuint32_t bd[3] = {64, box_rows, box_blocks}, es[3] = {1, 1, 1};
  enc(m, CU_TENSOR_MAP_DATA_TYPE_BFLOAT16, 3, (void*)ptr, gd, gs, bd, es, CU_TENSOR_MAP_INTERLEAVE_NONE, CU_TENSOR_MAP_SWIZZLE_128B,
      promo, CU_TENSOR_MAP_FLOAT_OOB_FILL_NONE);
}
void make2d(EncodeFn enc, CUtensorMap* m, const void* ptr, uint64_t rows, uint64_t cols, uint32_t box_rows) {
  cuuint64_t gd[2] = {cols, rows};
  cuuint64_t gs[1] = {cols * 2};
  cuuint32_t bd[2] = {64, box_rows}, es[2] = {1, 1};
  enc(m, CU_TENSOR_MAP_DATA_TYPE_BFLOAT16, 2, (void*)ptr, gd, gs, bd, es, CU_TENSOR_MAP_INTERLEAVE_NONE, CU_TENSOR_MAP_SWIZZLE_128B,
      CU_TENSOR_MAP_L2_PROMOTION_L2_128B, CU_TENSOR_MAP_FLOAT_OOB_FILL_NONE);
}

}

extern "C" void kernel_launch(void* const* d_in, const int* in_sizes, int n_in, void* d_out, int out_size) {
  static EncodeFn enc = nullptr;
  static void* part = nullptr;
  if (!enc) {
    cudaGetSymbolAddress(&part, g_part);
    cudaDriverEntryPointQueryResult qr;
    cudaGetDriverEntryPoint("cuTensorMapEncodeTiled", (void**)&enc, cudaEnableDefault, &qr);
    cudaFuncSetAttribute(fused_kernel, cudaFuncAttributeMaxDynamicSharedMemorySize, SMEM_BYTES);
  }
  Params p;
  for (int s = 0; s < 2; s++) {
    make2d(enc, &p.x[s], d_in[5 * s + 0], NB * SQ, DM, SQ);
    make3d(enc, &p.k[s], d_in[5 * s + 1], (uint64_t)NB * NH * SK, DH, 64, 3);
    make3d(enc, &p.v[s], d_in[5 * s + 2], (uint64_t)NB * NH * SK, DH, 64, 3);
    make3d(enc, &p.wq[s], d_in[5 * s + 3], DM, NH * DH, 64, 3);
    make3d(enc, &p.wo[s], d_in[5 * s + 4], NH * DH, DM, 64, 5);
    p.xp[s] = (const __nv_bfloat16*)d_in[5 * s + 0];
    p.wqp[s] = (const __nv_bfloat16*)d_in[5 * s + 3];
    p.kp[s] = (const __nv_bfloat16*)d_in[5 * s + 1];
    p.vp[s] = (const __nv_bfloat16*)d_in[5 * s + 2];
  }
  make2d(enc, &p.out, d_out, NB * SQ, 2 * DM, SQ);
  make2d(enc, &p.part, part, 4 * NB * SQ, DM, 40);
  p.outp = (__nv_bfloat16*)d_out;
  p.dsw = DESC_SW;
  p.dso = DESC_O;
  p.zero = 0;
  fused_kernel<<<NCTA, 384, SMEM_BYTES>>>(p);
}
```

```cpp
#include <cuda_runtime.h>
#include <cuda_bf16.h>
#include <cuda.h>
#include <stdint.h>

#define DEBUG_TIMEOUT 0

namespace {

constexpr int SQ = 160, DM = 640, NH = 32, SK = 512, DH = 192, NB = 16;
constexpr int NITEMS = 2 * NB * NH;
constexpr int NCTA = 132, N_OCTA = 32;
constexpr int ORING = 192, OFRESH = 848, CHUNK1 = 158, LEN1 = 18, LEN2 = 13, LSLOPE1 = 4, LSLOPE2 = 5;
constexpr int STAG_G = 4, PERM_G = 4, STAG_A0 = 19, STAG_SLOPE = 275, PERM_M = 20, PF_N = 32, PF_WAIT = 1500, PF_GAP = 300;
constexpr int OSLOTS = ORING + NITEMS - OFRESH;
constexpr int A_SLOT = 24576, B_SLOT = 20480, NSLOT = 5;
constexpr int OFF_A = 0;
constexpr int OFF_B = NSLOT * A_SLOT;
constexpr int O_STAGE = 61440, O_AB = 40960, O_NST = 3;
constexpr int OFF_L = OFF_B + NSLOT * B_SLOT;
constexpr int OFF_BAR = OFF_L + 160 * 4;
constexpr int SMEM_BYTES = OFF_BAR + 512 + 768;
constexpr int O_OUT = 2 * O_STAGE;
static_assert(O_OUT + 5 * B_SLOT <= OFF_L, "smem layout");
constexpr uint32_t SB = 1024;
constexpr uint32_t BARS = SB + OFF_BAR;
constexpr uint32_t BAR_FULLA = BARS, BAR_EMPTYA = BARS + 40, BAR_PMID = BARS + 80, BAR_EMPTYB = BARS + 120, BAR_XDONE = BARS + 160,
                   BAR_QH = BARS + 168, BAR_QM = BARS + 96, BAR_PFULL = BARS + 184, BAR_PFREE = BARS + 200, BAR_LFULL = BARS + 216,
                   BAR_OFULL = BARS + 224, BAR_GFULL = BARS + 248, BAR_GEMPTY = BARS + 280, BAR_GOUT = BARS + 328, BAR_GRED = BARS + 368,
                   BAR_FREE = BARS + 240, NEXT_ITEM = BARS + 320;
constexpr int O_ITEM_BYTES = SQ * DH * 2;

struct alignas(64) Params {
  CUtensorMap x[2], wq[2], k[2], v[2], wo[2], out, part;
  uint64_t dsw, dso, zero;
  __nv_bfloat16* outp;
  const __nv_bfloat16 *xp[2], *wqp[2], *kp[2], *vp[2];
};

__device__ uint4 g_o[(size_t)OSLOTS * O_ITEM_BYTES / 16];
__device__ uint4 g_part[4 * NB * SQ * DM / 8];
__device__ __align__(16) int g_pcnt[4 * N_OCTA];
__device__ int g_ready[NITEMS];
__device__ int g_done[NITEMS];
__device__ int g_ticket;
__device__ int g_go;
__device__ int g_epoch[NCTA];

#define TLE(id)
#define TLP(id)
#define TLG(id)
#define TL(id)
#define TL_FLUSH()
__device__ __forceinline__ uint32_t smem_u32(const void* p) { return (uint32_t)__cvta_generic_to_shared(p); }
__device__ __forceinline__ void wg_fence() { asm volatile("wgmma.fence.sync.aligned;" ::: "memory"); }
__device__ __forceinline__ void wg_commit() { asm volatile("wgmma.commit_group.sync.aligned;" ::: "memory"); }
template <int N> __device__ __forceinline__ void wg_wait() { asm volatile("wgmma.wait_group.sync.aligned %0;" ::"n"(N) : "memory"); }
template <int N> __device__ __forceinline__ void reg_fence(float (&d)[N]) {
#pragma unroll
  for (int i = 0; i < N; i++) asm volatile("" : "+f"(d[i])::"memory");
}
template <int N> __device__ __forceinline__ void zero_regs(float (&d)[N]) {
#pragma unroll
  for (int i = 0; i < N; i++) d[i] = 0.f;
}
__device__ __forceinline__ void proxy_fence() { asm volatile("fence.proxy.async.shared::cta;" ::: "memory"); }
__device__ __forceinline__ void mbar_init(uint32_t bar, int cnt) { asm volatile("mbarrier.init.shared::cta.b64 [%0], %1;" ::"r"(bar), "r"(cnt) : "memory"); }
__device__ __forceinline__ void mbar_arrive_if0(uint32_t bar, uint32_t sel) {
  asm volatile("{\n.reg .pred p;\nsetp.eq.u32 p, %1, 0;\n@p mbarrier.arrive.shared::cta.b64 _, [%0];\n}\n" ::"r"(bar), "r"(sel) : "memory");
}
__device__ __forceinline__ void mbar_arrive2_if0(uint32_t bar, uint32_t sel) {
  asm volatile("{\n.reg .pred p;\nsetp.eq.u32 p, %1, 0;\n@p mbarrier.arrive.shared::cta.b64 _, [%0], 2;\n}\n" ::"r"(bar), "r"(sel) : "memory");
}
__device__ __forceinline__ void mbar_expect(uint32_t bar, uint32_t bytes) {
  asm volatile("mbarrier.arrive.expect_tx.shared::cta.b64 _, [%0], %1;" ::"r"(bar), "r"(bytes) : "memory");
}
__device__ __forceinline__ void mbar_wait(int& bud, uint32_t bar, uint32_t parity) {
  asm volatile(
      "{\n.reg .pred p;\n"
      "LW:\n"
      "mbarrier.try_wait.parity.shared::cta.b64 p, [%0], %1;\n"
      "@!p bra LW;\n}\n" ::"r"(bar), "r"(parity) : "memory");
}
constexpr int WAIT_BUDGET = 1 << 22;
__device__ __forceinline__ bool elect_one() {
  uint32_t p;
  asm volatile("{\n.reg .pred p;\nelect.sync _|p, 0xffffffff;\nselp.u32 %0, 1, 0, p;\n}\n" : "=r"(p));
  return p;
}
__device__ __forceinline__ void tma2d(uint32_t dst, const CUtensorMap* m, uint32_t bar, int c0, int c1) {
  asm volatile("cp.async.bulk.tensor.2d.shared::cluster.global.mbarrier::complete_tx::bytes [%0], [%1, {%3, %4}], [%2];"
               ::"r"(dst), "l"(m), "r"(bar), "r"(c0), "r"(c1) : "memory");
}
__device__ __forceinline__ void tma3d(uint32_t dst, const CUtensorMap* m, uint32_t bar, int c0, int c1, int c2) {
  asm volatile("cp.async.bulk.tensor.3d.shared::cluster.global.mbarrier::complete_tx::bytes [%0], [%1, {%3, %4, %5}], [%2];"
               ::"r"(dst), "l"(m), "r"(bar), "r"(c0), "r"(c1), "r"(c2) : "memory");
}
__device__ __forceinline__ void tma3d_hint(uint32_t dst, const CUtensorMap* m, uint32_t bar, int c0, int c1, int c2, uint64_t pol) {
  asm volatile("cp.async.bulk.tensor.3d.shared::cluster.global.mbarrier::complete_tx::bytes.L2::cache_hint [%0], [%1, {%3, %4, %5}], [%2], %6;"
               ::"r"(dst), "l"(m), "r"(bar), "r"(c0), "r"(c1), "r"(c2), "l"(pol) : "memory");
}
__device__ __forceinline__ void tma_store2d(const CUtensorMap* m, uint32_t src, int c0, int c1) {
  asm volatile("cp.async.bulk.tensor.2d.global.shared::cta.bulk_group [%0, {%2, %3}], [%1];" ::"l"(m), "r"(src), "r"(c0), "r"(c1) : "memory");
}
__device__ __forceinline__ void bar_sync(int id, int n) { asm volatile("bar.sync %0, %1;" ::"r"(id), "r"(n) : "memory"); }
__device__ __forceinline__ void bar_arrive(int id, int n) { asm volatile("bar.arrive %0, %1;" ::"r"(id), "r"(n) : "memory"); }
__device__ __forceinline__ void bar_sync_if0(int id, int sel) {
  asm volatile("{\n.reg .pred p;\nsetp.eq.s32 p, %1, 0;\n@p bar.sync %0, 256;\n}\n" ::"r"(id), "r"(sel) : "memory");
}
__device__ __forceinline__ float ex2(float x) { float y; asm("ex2.approx.ftz.f32 %0, %1;" : "=f"(y) : "f"(x)); return y; }
__device__ __forceinline__ uint32_t pack2(float lo, float hi) { uint32_t r; asm("cvt.rn.bf16x2.f32 %0, %1, %2;" : "=r"(r) : "f"(hi), "f"(lo)); return r; }
__device__ __forceinline__ void stsm_t(uint32_t a, uint32_t r0, uint32_t r1, uint32_t r2, uint32_t r3) {
  asm volatile("stmatrix.sync.aligned.m8n8.x4.trans.shared.b16 [%0], {%1,%2,%3,%4};" ::"r"(a), "r"(r0), "r"(r1), "r"(r2), "r"(r3) : "memory");
}
__device__ __forceinline__ uint64_t evict_first_policy() {
  uint64_t pol;
  asm volatile("createpolicy.fractional.L2::evict_first.b64 %0, 1.0;" : "=l"(pol));
  return pol;
}
__device__ __forceinline__ void bulk_load_hint(uint32_t dst, const void* src, uint32_t bytes, uint32_t bar, uint64_t pol) {
  asm volatile("cp.async.bulk.shared::cluster.global.mbarrier::complete_tx::bytes.L2::cache_hint [%0], [%1], %2, [%3], %4;"
               ::"r"(dst), "l"(src), "r"(bytes), "r"(bar), "l"(pol) : "memory");
}
__device__ __forceinline__ void flag_wait(int& bud, const int* p, int target) {
  while (true) {
    int v;
    asm volatile("ld.acquire.gpu.global.s32 %0, [%1];" : "=r"(v) : "l"(p) : "memory");
    if (v - target >= 0 || --bud <= 0) break;
    __nanosleep(64);
  }
}
constexpr uint64_t DESC_SW = 0x4000004000010000ull, DESC_O = 0xC000001000800000ull;
__device__ __forceinline__ uint32_t tid_x() { uint32_t t; asm volatile("mov.u32 %0, %tid.x;" : "=r"(t)); return t; }

template <int TA, int TB, uint32_t OA, uint32_t OB>
__device__ __forceinline__ void mma160(float (&d)[80], uint64_t ba, uint32_t la, uint64_t bb, uint32_t lb) {
  asm volatile(
      "{\n.reg .pred p;\n.reg .b64 da, db;\nsetp.eq.b32 p, 0, 0;\n"
      "mad.wide.u32 da, %80, 192, %86;\nadd.s64 da, da, %84;\nmad.wide.u32 db, %81, 1, %87;\nadd.s64 db, db, %85;\n"
      "wgmma.mma_async.sync.aligned.m64n160k16.f32.bf16.bf16 {"
      "%0,%1,%2,%3,%4,%5,%6,%7,%8,%9,%10,%11,%12,%13,%14,%15,%16,%17,%18,%19,%20,%21,%22,%23,%24,%25,%26,%27,%28,%29,%30,%31,%32,%33,%34,%35,%36,"
      "%37,%38,%39,%40,%41,%42,%43,%44,%45,%46,%47,%48,%49,%50,%51,%52,%53,%54,%55,%56,%57,%58,%59,%60,%61,%62,%63,%64,%65,%66,%67,%68,%69,%70,%71,"
      "%72,%73,%74,%75,%76,%77,%78,%79"
      "}, da, db, p, 1, 1, %82, %83;\n}\n"
      :
      "+f"(d[0]),"+f"(d[1]),"+f"(d[2]),"+f"(d[3]),"+f"(d[4]),"+f"(d[5]),"+f"(d[6]),"+f"(d[7]),"+f"(d[8]),"+f"(d[9]),"+f"(d[10]),"+f"(d[11]),
      "+f"(d[12]),"+f"(d[13]),"+f"(d[14]),"+f"(d[15]),"+f"(d[16]),"+f"(d[17]),"+f"(d[18]),"+f"(d[19]),"+f"(d[20]),"+f"(d[21]),"+f"(d[22]),
      "+f"(d[23]),"+f"(d[24]),"+f"(d[25]),"+f"(d[26]),"+f"(d[27]),"+f"(d[28]),"+f"(d[29]),"+f"(d[30]),"+f"(d[31]),"+f"(d[32]),"+f"(d[33]),
      "+f"(d[34]),"+f"(d[35]),"+f"(d[36]),"+f"(d[37]),"+f"(d[38]),"+f"(d[39]),"+f"(d[40]),"+f"(d[41]),"+f"(d[42]),"+f"(d[43]),"+f"(d[44]),
      "+f"(d[45]),"+f"(d[46]),"+f"(d[47]),"+f"(d[48]),"+f"(d[49]),"+f"(d[50]),"+f"(d[51]),"+f"(d[52]),"+f"(d[53]),"+f"(d[54]),"+f"(d[55]),
      "+f"(d[56]),"+f"(d[57]),"+f"(d[58]),"+f"(d[59]),"+f"(d[60]),"+f"(d[61]),"+f"(d[62]),"+f"(d[63]),"+f"(d[64]),"+f"(d[65]),"+f"(d[66]),
      "+f"(d[67]),"+f"(d[68]),"+f"(d[69]),"+f"(d[70]),"+f"(d[71]),"+f"(d[72]),"+f"(d[73]),"+f"(d[74]),"+f"(d[75]),"+f"(d[76]),"+f"(d[77]),
      "+f"(d[78]),"+f"(d[79])
      : "r"(la), "r"(lb), "n"(TA), "n"(TB), "n"((SB + OA) >> 4), "n"(OB >> 4), "l"(ba), "l"(bb));
}

template <int TA, int TB, uint32_t OA, uint32_t OB>
__device__ __forceinline__ void mma160z(float (&d)[80], uint64_t ba, uint32_t la, uint64_t bb, uint32_t lb) {
  asm volatile(
      "{\n.reg .pred p;\n.reg .b64 da, db;\nsetp.ne.b32 p, 0, 0;\n"
      "mad.wide.u32 da, %80, 192, %86;\nadd.s64 da, da, %84;\nmad.wide.u32 db, %81, 1, %87;\nadd.s64 db, db, %85;\n"
      "wgmma.mma_async.sync.aligned.m64n160k16.f32.bf16.bf16 {"
      "%0,%1,%2,%3,%4,%5,%6,%7,%8,%9,%10,%11,%12,%13,%14,%15,%16,%17,%18,%19,%20,%21,%22,%23,%24,%25,%26,%27,%28,%29,%30,%31,%32,%33,%34,%35,%36,"
      "%37,%38,%39,%40,%41,%42,%43,%44,%45,%46,%47,%48,%49,%50,%51,%52,%53,%54,%55,%56,%57,%58,%59,%60,%61,%62,%63,%64,%65,%66,%67,%68,%69,%70,%71,"
      "%72,%73,%74,%75,%76,%77,%78,%79"
      "}, da, db, p, 1, 1, %82, %83;\n}\n"
      :
      "=f"(d[0]),"=f"(d[1]),"=f"(d[2]),"=f"(d[3]),"=f"(d[4]),"=f"(d[5]),"=f"(d[6]),"=f"(d[7]),"=f"(d[8]),"=f"(d[9]),"=f"(d[10]),"=f"(d[11]),
      "=f"(d[12]),"=f"(d[13]),"=f"(d[14]),"=f"(d[15]),"=f"(d[16]),"=f"(d[17]),"=f"(d[18]),"=f"(d[19]),"=f"(d[20]),"=f"(d[21]),"=f"(d[22]),
      "=f"(d[23]),"=f"(d[24]),"=f"(d[25]),"=f"(d[26]),"=f"(d[27]),"=f"(d[28]),"=f"(d[29]),"=f"(d[30]),"=f"(d[31]),"=f"(d[32]),"=f"(d[33]),
      "=f"(d[34]),"=f"(d[35]),"=f"(d[36]),"=f"(d[37]),"=f"(d[38]),"=f"(d[39]),"=f"(d[40]),"=f"(d[41]),"=f"(d[42]),"=f"(d[43]),"=f"(d[44]),
      "=f"(d[45]),"=f"(d[46]),"=f"(d[47]),"=f"(d[48]),"=f"(d[49]),"=f"(d[50]),"=f"(d[51]),"=f"(d[52]),"=f"(d[53]),"=f"(d[54]),"=f"(d[55]),
      "=f"(d[56]),"=f"(d[57]),"=f"(d[58]),"=f"(d[59]),"=f"(d[60]),"=f"(d[61]),"=f"(d[62]),"=f"(d[63]),"=f"(d[64]),"=f"(d[65]),"=f"(d[66]),
      "=f"(d[67]),"=f"(d[68]),"=f"(d[69]),"=f"(d[70]),"=f"(d[71]),"=f"(d[72]),"=f"(d[73]),"=f"(d[74]),"=f"(d[75]),"=f"(d[76]),"=f"(d[77]),
      "=f"(d[78]),"=f"(d[79])
      : "r"(la), "r"(lb), "n"(TA), "n"(TB), "n"((SB + OA) >> 4), "n"(OB >> 4), "l"(ba), "l"(bb));
}

template <int TA, int TB, uint32_t OA, uint32_t OB>
__device__ __forceinline__ void mma80(float (&d)[40], uint64_t ba, uint32_t la, uint64_t bb, uint32_t lb) {
  asm volatile(
      "{\n.reg .pred p;\n.reg .b64 da, db;\nsetp.eq.b32 p, 0, 0;\n"
      "mad.wide.u32 da, %40, 192, %46;\nadd.s64 da, da, %44;\nmad.wide.u32 db, %41, 1, %47;\nadd.s64 db, db, %45;\n"
      "wgmma.mma_async.sync.aligned.m64n80k16.f32.bf16.bf16 {"
      "%0,%1,%2,%3,%4,%5,%6,%7,%8,%9,%10,%11,%12,%13,%14,%15,%16,%17,%18,%19,%20,%21,%22,%23,%24,%25,%26,%27,%28,%29,%30,%31,%32,%33,%34,%35,%36,"
      "%37,%38,%39"
      "}, da, db, p, 1, 1, %42, %43;\n}\n"
      :
      "+f"(d[0]),"+f"(d[1]),"+f"(d[2]),"+f"(d[3]),"+f"(d[4]),"+f"(d[5]),"+f"(d[6]),"+f"(d[7]),"+f"(d[8]),"+f"(d[9]),"+f"(d[10]),"+f"(d[11]),
      "+f"(d[12]),"+f"(d[13]),"+f"(d[14]),"+f"(d[15]),"+f"(d[16]),"+f"(d[17]),"+f"(d[18]),"+f"(d[19]),"+f"(d[20]),"+f"(d[21]),"+f"(d[22]),
      "+f"(d[23]),"+f"(d[24]),"+f"(d[25]),"+f"(d[26]),"+f"(d[27]),"+f"(d[28]),"+f"(d[29]),"+f"(d[30]),"+f"(d[31]),"+f"(d[32]),"+f"(d[33]),
      "+f"(d[34]),"+f"(d[35]),"+f"(d[36]),"+f"(d[37]),"+f"(d[38]),"+f"(d[39])
      : "r"(la), "r"(lb), "n"(TA), "n"(TB), "n"((SB + OA) >> 4), "n"(OB >> 4), "l"(ba), "l"(bb));
}

template <int TA, int TB, uint32_t OA, uint32_t OB>
__device__ __forceinline__ void mma80z(float (&d)[40], uint64_t ba, uint32_t la, uint64_t bb, uint32_t lb) {
  asm volatile(
      "{\n.reg .pred p;\n.reg .b64 da, db;\nsetp.ne.b32 p, 0, 0;\n"
      "mad.wide.u32 da, %40, 192, %46;\nadd.s64 da, da, %44;\nmad.wide.u32 db, %41, 1, %47;\nadd.s64 db, db, %45;\n"
      "wgmma.mma_async.sync.aligned.m64n80k16.f32.bf16.bf16 {"
      "%0,%1,%2,%3,%4,%5,%6,%7,%8,%9,%10,%11,%12,%13,%14,%15,%16,%17,%18,%19,%20,%21,%22,%23,%24,%25,%26,%27,%28,%29,%30,%31,%32,%33,%34,%35,%36,"
      "%37,%38,%39"
      "}, da, db, p, 1, 1, %42, %43;\n}\n"
      :
      "=f"(d[0]),"=f"(d[1]),"=f"(d[2]),"=f"(d[3]),"=f"(d[4]),"=f"(d[5]),"=f"(d[6]),"=f"(d[7]),"=f"(d[8]),"=f"(d[9]),"=f"(d[10]),"=f"(d[11]),
      "=f"(d[12]),"=f"(d[13]),"=f"(d[14]),"=f"(d[15]),"=f"(d[16]),"=f"(d[17]),"=f"(d[18]),"=f"(d[19]),"=f"(d[20]),"=f"(d[21]),"=f"(d[22]),
      "=f"(d[23]),"=f"(d[24]),"=f"(d[25]),"=f"(d[26]),"=f"(d[27]),"=f"(d[28]),"=f"(d[29]),"=f"(d[30]),"=f"(d[31]),"=f"(d[32]),"=f"(d[33]),
      "=f"(d[34]),"=f"(d[35]),"=f"(d[36]),"=f"(d[37]),"=f"(d[38]),"=f"(d[39])
      : "r"(la), "r"(lb), "n"(TA), "n"(TB), "n"((SB + OA) >> 4), "n"(OB >> 4), "l"(ba), "l"(bb));
}

template <int TA, int TB, uint32_t OA, uint32_t OB>
__device__ __forceinline__ void mma160r(float (&d)[80], uint64_t ba, uint32_t la, uint64_t bb, uint32_t lb, int sc) {
  asm volatile(
      "{\n.reg .pred p;\n.reg .b64 da, db;\nsetp.ne.b32 p, %88, 0;\n"
      "mad.wide.u32 da, %80, 3840, %86;\nadd.s64 da, da, %84;\nmad.wide.u32 db, %81, 3840, %87;\nadd.s64 db, db, %85;\n"
      "wgmma.mma_async.sync.aligned.m64n160k16.f32.bf16.bf16 {"
      "%0,%1,%2,%3,%4,%5,%6,%7,%8,%9,%10,%11,%12,%13,%14,%15,%16,%17,%18,%19,%20,%21,%22,%23,%24,%25,%26,%27,%28,%29,%30,%31,%32,%33,%34,%35,%36,"
      "%37,%38,%39,%40,%41,%42,%43,%44,%45,%46,%47,%48,%49,%50,%51,%52,%53,%54,%55,%56,%57,%58,%59,%60,%61,%62,%63,%64,%65,%66,%67,%68,%69,%70,%71,"
      "%72,%73,%74,%75,%76,%77,%78,%79"
      "}, da, db, p, 1, 1, %82, %83;\n}\n"
      :
      "+f"(d[0]),"+f"(d[1]),"+f"(d[2]),"+f"(d[3]),"+f"(d[4]),"+f"(d[5]),"+f"(d[6]),"+f"(d[7]),"+f"(d[8]),"+f"(d[9]),"+f"(d[10]),"+f"(d[11]),
      "+f"(d[12]),"+f"(d[13]),"+f"(d[14]),"+f"(d[15]),"+f"(d[16]),"+f"(d[17]),"+f"(d[18]),"+f"(d[19]),"+f"(d[20]),"+f"(d[21]),"+f"(d[22]),
      "+f"(d[23]),"+f"(d[24]),"+f"(d[25]),"+f"(d[26]),"+f"(d[27]),"+f"(d[28]),"+f"(d[29]),"+f"(d[30]),"+f"(d[31]),"+f"(d[32]),"+f"(d[33]),
      "+f"(d[34]),"+f"(d[35]),"+f"(d[36]),"+f"(d[37]),"+f"(d[38]),"+f"(d[39]),"+f"(d[40]),"+f"(d[41]),"+f"(d[42]),"+f"(d[43]),"+f"(d[44]),
      "+f"(d[45]),"+f"(d[46]),"+f"(d[47]),"+f"(d[48]),"+f"(d[49]),"+f"(d[50]),"+f"(d[51]),"+f"(d[52]),"+f"(d[53]),"+f"(d[54]),"+f"(d[55]),
      "+f"(d[56]),"+f"(d[57]),"+f"(d[58]),"+f"(d[59]),"+f"(d[60]),"+f"(d[61]),"+f"(d[62]),"+f"(d[63]),"+f"(d[64]),"+f"(d[65]),"+f"(d[66]),
      "+f"(d[67]),"+f"(d[68]),"+f"(d[69]),"+f"(d[70]),"+f"(d[71]),"+f"(d[72]),"+f"(d[73]),"+f"(d[74]),"+f"(d[75]),"+f"(d[76]),"+f"(d[77]),
      "+f"(d[78]),"+f"(d[79])
      : "r"(la), "r"(lb), "n"(TA), "n"(TB), "n"((SB + OA) >> 4), "n"(OB >> 4), "l"(ba), "l"(bb), "r"(sc));
}

template <int TA, int TB, uint32_t OA, uint32_t OB>
__device__ __forceinline__ void mma80r(float (&d)[40], uint64_t ba, uint32_t la, uint64_t bb, uint32_t lb, int sc) {
  asm volatile(
      "{\n.reg .pred p;\n.reg .b64 da, db;\nsetp.ne.b32 p, %48, 0;\n"
      "mad.wide.u32 da, %40, 3840, %46;\nadd.s64 da, da, %44;\nmad.wide.u32 db, %41, 3840, %47;\nadd.s64 db, db, %45;\n"
      "wgmma.mma_async.sync.aligned.m64n80k16.f32.bf16.bf16 {"
      "%0,%1,%2,%3,%4,%5,%6,%7,%8,%9,%10,%11,%12,%13,%14,%15,%16,%17,%18,%19,%20,%21,%22,%23,%24,%25,%26,%27,%28,%29,%30,%31,%32,%33,%34,%35,%36,"
      "%37,%38,%39"
      "}, da, db, p, 1, 1, %42, %43;\n}\n"
      :
      "+f"(d[0]),"+f"(d[1]),"+f"(d[2]),"+f"(d[3]),"+f"(d[4]),"+f"(d[5]),"+f"(d[6]),"+f"(d[7]),"+f"(d[8]),"+f"(d[9]),"+f"(d[10]),"+f"(d[11]),
      "+f"(d[12]),"+f"(d[13]),"+f"(d[14]),"+f"(d[15]),"+f"(d[16]),"+f"(d[17]),"+f"(d[18]),"+f"(d[19]),"+f"(d[20]),"+f"(d[21]),"+f"(d[22]),
      "+f"(d[23]),"+f"(d[24]),"+f"(d[25]),"+f"(d[26]),"+f"(d[27]),"+f"(d[28]),"+f"(d[29]),"+f"(d[30]),"+f"(d[31]),"+f"(d[32]),"+f"(d[33]),
      "+f"(d[34]),"+f"(d[35]),"+f"(d[36]),"+f"(d[37]),"+f"(d[38]),"+f"(d[39])
      : "r"(la), "r"(lb), "n"(TA), "n"(TB), "n"((SB + OA) >> 4), "n"(OB >> 4), "l"(ba), "l"(bb), "r"(sc));
}

struct Ring { uint32_t o[NSLOT], m; };
__device__ __forceinline__ void ring_pos(const Ring& r, int i, uint32_t& slot8, uint32_t& ph) {
  slot8 = r.o[i % NSLOT];
  ph = r.m >> (i % (2 * NSLOT));
}
__device__ __forceinline__ void ring_advance(Ring& r, int n) {
  Ring t = r;
#pragma unroll
  for (int k = 0; k < NSLOT; k++) r.o[k] = t.o[(k + n) % NSLOT];
  r.m = ((t.m >> (n % (2 * NSLOT))) & 1023) * 1025;
}
__host__ __device__ constexpr int idxK(int j) { return j == 0 ? 10 : 9 + 2 * j; }
__host__ __device__ constexpr int idxV(int j) { return j == 7 ? 25 : 12 + 2 * j; }
__host__ __device__ constexpr int xs(int c) { return c % NSLOT; }

__device__ __forceinline__ int start_delay(int cta) {
  return max(0, ((cta - N_OCTA) | (STAG_G - 1)) - STAG_A0) * STAG_SLOPE;
}
__device__ __forceinline__ char* o_slot(int item) {
  return (char*)g_o + (size_t)(item < OFRESH ? item % ORING : item - OFRESH + ORING) * O_ITEM_BYTES;
}
__device__ __forceinline__ int next_item(uint32_t a = NEXT_ITEM) {
  int v;
  asm volatile("ld.shared.s32 %0, [%1];" : "=r"(v) : "r"(a) : "memory");
  return __shfl_sync(0xffffffffu, v, 0);
}

template <int W, bool ACC>
__device__ __forceinline__ void mma_main(uint64_t ds, float (&d)[80], uint32_t la, uint32_t baddr) {
  const uint32_t lb = baddr >> 4;
  if (ACC) mma160<1, 0, W * 16384, 0>(d, ds, la, ds, lb); else mma160z<1, 0, W * 16384, 0>(d, ds, la, ds, lb);
  mma160<1, 0, W * 16384 + 1 * 2048, 1 * 32>(d, ds, la, ds, lb);
  mma160<1, 0, W * 16384 + 2 * 2048, 2 * 32>(d, ds, la, ds, lb);
  mma160<1, 0, W * 16384 + 3 * 2048, 3 * 32>(d, ds, la, ds, lb);
}
template <int W, bool ACC>
__device__ __forceinline__ void mma_mid(uint64_t ds, float (&d)[40], uint32_t la, uint32_t baddr) {
  const uint32_t lb = baddr >> 4;
  if (ACC) mma80<1, 0, 8192, W * 10240>(d, ds, la, ds, lb); else mma80z<1, 0, 8192, W * 10240>(d, ds, la, ds, lb);
  mma80<1, 0, 8192 + 1 * 2048, W * 10240 + 1 * 32>(d, ds, la, ds, lb);
  mma80<1, 0, 8192 + 2 * 2048, W * 10240 + 2 * 32>(d, ds, la, ds, lb);
  mma80<1, 0, 8192 + 3 * 2048, W * 10240 + 3 * 32>(d, ds, la, ds, lb);
}
template <int W, bool ACC>
__device__ __forceinline__ void mma_both(uint64_t ds, float (&dm)[80], float (&dh)[40], uint32_t la, uint32_t baddr) {
  mma_mid<W, ACC>(ds, dh, la, baddr);
  mma_main<W, ACC>(ds, dm, la, baddr);
}
template <int KB, bool ACC>
__device__ __forceinline__ void s_mma(uint64_t ds, float (&sacc)[80], uint32_t la) {
  const uint32_t lb = (SB + OFF_B) >> 4;
  if (ACC) mma160<0, 0, KB * 8192, KB * B_SLOT>(sacc, ds, la, ds, lb); else mma160z<0, 0, KB * 8192, KB * B_SLOT>(sacc, ds, la, ds, lb);
  mma160<0, 0, KB * 8192 + 32, KB * B_SLOT + 32>(sacc, ds, la, ds, lb);
  mma160<0, 0, KB * 8192 + 64, KB * B_SLOT + 64>(sacc, ds, la, ds, lb);
  mma160<0, 0, KB * 8192 + 96, KB * B_SLOT + 96>(sacc, ds, la, ds, lb);
}
template <int N>
__device__ __forceinline__ void store_scaled(uint32_t addr, const float (&d)[N], float sc) {
#pragma unroll
  for (int J = 0; J < N / 8; J++)
    stsm_t(addr + J * 2048, pack2(d[8 * J] * sc, d[8 * J + 1] * sc), pack2(d[8 * J + 2] * sc, d[8 * J + 3] * sc),
           pack2(d[8 * J + 4] * sc, d[8 * J + 5] * sc), pack2(d[8 * J + 6] * sc, d[8 * J + 7] * sc));
}
__device__ __forceinline__ float4 lds_f4(uint32_t a) {
  float4 v;
  asm volatile("ld.shared.v4.f32 {%0,%1,%2,%3}, [%4];" : "=f"(v.x), "=f"(v.y), "=f"(v.z), "=f"(v.w) : "r"(a) : "memory");
  return v;
}
__device__ __forceinline__ void norm_pack(uint32_t* p, const float* d, const float4& i) {
  p[0] = pack2(d[0] * i.x, d[1] * i.y); p[1] = pack2(d[4] * i.z, d[5] * i.w);
  p[2] = pack2(d[2] * i.x, d[3] * i.y); p[3] = pack2(d[6] * i.z, d[7] * i.w);
  asm volatile("" : "+r"(p[0]), "+r"(p[1]), "+r"(p[2]), "+r"(p[3])::"memory");
}
template <int W>
__device__ __forceinline__ void pack_first(uint32_t (&pk)[60], const float (&om)[80], const float (&oh)[40], uint32_t laddr) {
  float4 n0 = lds_f4(laddr + W * 80), n1 = lds_f4(laddr + W * 80 + 16);
#pragma unroll
  for (int J = 0; J < 5; J++) {
    const float4 i = n0;
    n0 = n1;
    if (J + 2 < 5) n1 = lds_f4(laddr + W * 80 + (J + 2) * 16);
    norm_pack(&pk[20 + 4 * J], &om[8 * (5 * W + J)], i);
    norm_pack(&pk[4 * J], &oh[8 * J], i);
  }
}
template <int W, int J0, int J1>
__device__ __forceinline__ void pack_second(uint32_t (&pk)[60], const float (&om)[80], uint32_t laddr) {
  float4 n[J1 - J0];
#pragma unroll
  for (int J = J0; J < J1; J++) n[J - J0] = lds_f4(laddr + (1 - W) * 80 + J * 16);
#pragma unroll
  for (int J = J0; J < J1; J++) norm_pack(&pk[40 + 4 * J], &om[8 * (5 * (1 - W) + J)], n[J - J0]);
}
__device__ __forceinline__ char* o_ptr(int item) {
  const uint32_t t = tid_x();
  return o_slot(item) + ((t & 96) * 16 + (t & 28) * 8 + ((((t >> 1) ^ (t >> 4)) & 1) << 4) + (t & 1) * 8);
}
template <int W, int G0, int G1>
__device__ __forceinline__ void store_groups(char* op, const uint32_t (&pk)[60], uint32_t on) {
#pragma unroll
  for (int G = G0; G < G1; G++) {
    const int off = (G < 5 ? 1 : 2 * W) * B_SLOT + (5 * (G < 10 ? W : 1 - W) + G % 5) * 2048;
    asm volatile("{\n.reg .pred p;\nsetp.ne.u32 p, %5, 0;\n@p st.global.v2.b32 [%0], {%1, %2};\n@p st.global.v2.b32 [%0+256], {%3, %4};\n}\n"
                 ::"l"(op + off), "r"(pk[4 * G]), "r"(pk[4 * G + 1]), "r"(pk[4 * G + 2]), "r"(pk[4 * G + 3]), "r"(on) : "memory");
  }
}
__device__ __forceinline__ void publish_generic(uint32_t bar, int lane) {
  __syncwarp();
  mbar_arrive_if0(bar, lane);
}
__device__ __forceinline__ void publish(uint32_t bar, int lane) {
  proxy_fence();
  __syncwarp();
  mbar_arrive_if0(bar, lane);
}

#define MMA_BEGIN()                                                 \
  asm volatile("add.s64 %0, %0, %1;" : "+l"(ds) : "l"(zero));       \
  wg_fence()
#define A_ADDR(s) (SB + OFF_A + (s) * A_SLOT)
#define B_ADDR(s) (SB + OFF_B + (s) * B_SLOT)
#define WAIT_CHUNK(c, ro, sA)                \
  uint32_t sA;                               \
  {                                          \
    uint32_t pA_;                            \
    ring_pos(ring, (ro) + (c), sA, pA_);     \
    mbar_wait(bud, BAR_FULLA + sA, pA_); \
  }
#define RELEASE_CHUNK(c, sA)                                  \
  mbar_arrive_if0(BAR_EMPTYA + sA, tid);                \
  if ((c) < NSLOT) mbar_arrive_if0(BAR_EMPTYB + xs(c) * 8, tid);

template <int W>
__device__ __forceinline__ int attn_consumer(uint64_t ds, const uint64_t zero, int item) {
  int bud = WAIT_BUDGET;
  const int tid = threadIdx.x & 127, lane = tid & 31;
  const uint32_t laddr = SB + OFF_L + (lane & 3) * 160;
  float om[80], oh[40], sacc[80];
  uint32_t pk[60];
#pragma unroll
  for (int i = 0; i < 40; i++) pk[i] = 0;
  zero_regs(om);
  Ring ring{{0u, 8u, 16u, 24u, 32u}, 0x3E0u * 1025};
  uint32_t par = 0;
  int prev = 0;
  const float qscale = 0.07216878364870322f * 1.4426950408889634f;
  constexpr uint32_t pown = B_ADDR(3 + W), poth = B_ADDR(4 - W);
  TL(0); TLG(62);
  {
    WAIT_CHUNK(0, 0, s0)
    MMA_BEGIN();
    mma_both<W, false>(ds, sacc, oh, s0, B_ADDR(xs(0)));
    wg_commit();
    WAIT_CHUNK(1, 0, s1)
    MMA_BEGIN();
    mma_both<W, true>(ds, sacc, oh, s1, B_ADDR(xs(1)));
    wg_commit();
    wg_wait<1>();
    RELEASE_CHUNK(0, s0)
  }
#pragma unroll 1
  for (int it = 0;; it++) {
    char* op = o_ptr(prev);
#pragma unroll
    for (int c = 2; c < 8 - W; c++) {
      WAIT_CHUNK(c, 0, sA)
      TL(40 + c);
      MMA_BEGIN();
      mma_both<W, true>(ds, sacc, oh, sA, B_ADDR(xs(c)));
      wg_commit();
      wg_wait<1>();
      uint32_t sP, pP;
      ring_pos(ring, c - 1, sP, pP);
      RELEASE_CHUNK(c - 1, sP)
      constexpr int NG = 3;
      if (c == 2) { pack_second<W, 0, 1>(pk, om, laddr); store_groups<W, 0 * NG, 1 * NG>(op, pk, it); }
      if (c == 3) { pack_second<W, 1, 2>(pk, om, laddr); store_groups<W, 1 * NG, 2 * NG>(op, pk, it); }
      if (c == 4) { pack_second<W, 2, 3>(pk, om, laddr); store_groups<W, 2 * NG, 3 * NG>(op, pk, it); }
      if (c == 5) { pack_second<W, 3, 4>(pk, om, laddr); store_groups<W, 3 * NG, 4 * NG>(op, pk, it); }
      if (c == 6) {
        pack_second<W, 4, 5>(pk, om, laddr);
        if (W == 1) {
          wg_wait<0>();
          RELEASE_CHUNK(6, sA)
          mbar_arrive_if0(BAR_XDONE, tid);
        }
        store_groups<W, 4 * NG, 15>(op, pk, it);
        __syncwarp();
        mbar_arrive_if0(BAR_OFULL, lane | (it == 0));
      }
    }
    const uint32_t t_ = tid_x(), st_off = ((t_ & 7) + ((t_ & 16) >> 1)) * 128 + (((((t_ & 96) >> 4) + ((t_ >> 3) & 1)) ^ (t_ & 7)) << 4);
    uint32_t sK0, pK0, s7, p7;
    ring_pos(ring, idxK(W), sK0, pK0);
    ring_pos(ring, 7, s7, p7);
    if (W == 1) mbar_wait(bud, BAR_FULLA + s7, p7);
    WAIT_CHUNK(8, 0, s8)
    if (W == 0) {
      MMA_BEGIN();
      mma_both<W, true>(ds, sacc, oh, s8, B_ADDR(xs(8)));
      wg_commit();
      wg_wait<1>();
      RELEASE_CHUNK(7, s7)
    }
    WAIT_CHUNK(9, 0, s9)
    TL(48);
    if (W == 0) {
      MMA_BEGIN();
      mma_mid<W, true>(ds, oh, s9, B_ADDR(xs(9)));
      wg_commit();
      mma_main<W, true>(ds, sacc, s9, B_ADDR(xs(9)));
      wg_commit();
      bar_arrive(5, 256);
      TL(49);
      wg_wait<1>();
      reg_fence(oh);
      mbar_wait(bud, BAR_XDONE, par);
      store_scaled(B_ADDR(1) + st_off, oh, qscale);
    } else {
      bar_sync(5, 256);
      MMA_BEGIN();
      mma_mid<W, true>(ds, oh, s7, B_ADDR(xs(7)));
      mma_mid<W, true>(ds, oh, s8, B_ADDR(xs(8)));
      mma_mid<W, true>(ds, oh, s9, B_ADDR(xs(9)));
      wg_commit();
      mma_main<W, true>(ds, sacc, s7, B_ADDR(xs(7)));
      wg_commit();
      mma_main<W, true>(ds, sacc, s8, B_ADDR(xs(8)));
      wg_commit();
      wg_wait<2>();
      reg_fence(oh);
      store_scaled(B_ADDR(1) + 10240 + st_off, oh, qscale);
      MMA_BEGIN();
      mma_main<W, true>(ds, sacc, s9, B_ADDR(xs(9)));
      wg_commit();
      bar_arrive(8, 256);
      TL(49);
      wg_wait<2>();
      RELEASE_CHUNK(7, s7)
      publish(BAR_QH, lane);
    }
    wg_wait<0>();
    reg_fence(sacc);
    TL(1);
    RELEASE_CHUNK(8, s8)
    RELEASE_CHUNK(9, s9)
    store_scaled(B_ADDR(2 * W) + st_off, sacc, qscale);
    if (W == 1) publish(BAR_QM, lane); else proxy_fence();
    TL(2);
    uint32_t sK = sK0, sV1 = 0;
    if (W == 0) {
      zero_regs(om); zero_regs(oh);
      reg_fence(om); reg_fence(oh);
      mbar_wait(bud, BAR_FULLA + sK0, pK0);
      bar_sync(8, 256);
      MMA_BEGIN();
      s_mma<0, false>(ds, sacc, sK);
      mbar_wait(bud, BAR_QH, par);
      TL(3);
      MMA_BEGIN();
      s_mma<1, true>(ds, sacc, sK);
      mbar_wait(bud, BAR_QM, par);
      TL(5);
      MMA_BEGIN();
      s_mma<2, true>(ds, sacc, sK);
      wg_commit();
      wg_commit();
      bar_arrive(2, 256);
    } else {
      uint32_t pV1;
      ring_pos(ring, idxV(0), sV1, pV1);
      mbar_wait(bud, BAR_FULLA + sK, pK0);
      bar_sync(2, 256);
      MMA_BEGIN();
      s_mma<0, false>(ds, sacc, sK);
      s_mma<1, true>(ds, sacc, sK);
      s_mma<2, true>(ds, sacc, sK);
      wg_commit();
      TL(6);
      mbar_wait(bud, BAR_FULLA + sV1, pV1);
      mbar_wait(bud, BAR_PFULL, 0);
      TL(7);
      MMA_BEGIN();
      mma_both<W, false>(ds, om, oh, sV1, poth);
      wg_commit();
      bar_arrive(1, 256);
    }
#pragma unroll 1
    for (int jj = 0;; jj++) {
      wg_wait<1>();
      reg_fence(sacc);
      TL(8 + jj * 7);
      mbar_arrive2_if0(BAR_EMPTYA + sK, tid);
      mbar_arrive_if0(BAR_EMPTYB + W * 8 + tid * 8, (tid >= 3 - W) | (jj != 3));
#pragma unroll
      for (int J = 0; J < 10; J++) {
        stsm_t(pown + st_off + J * 2048, pack2(ex2(sacc[8 * J]), ex2(sacc[8 * J + 1])), pack2(ex2(sacc[8 * J + 2]), ex2(sacc[8 * J + 3])),
               pack2(ex2(sacc[8 * J + 4]), ex2(sacc[8 * J + 5])), pack2(ex2(sacc[8 * J + 6]), ex2(sacc[8 * J + 7])));
        if (W == 1 && J == 5) publish_generic(BAR_PMID, lane | (jj != 3));
        if (J == 4) {
          wg_wait<0>();
          mbar_arrive_if0(BAR_EMPTYA + sV1, tid | (W == 0 && jj == 0));
        }
      }
      publish(BAR_PFULL + W * 8, lane);
      TL(10 + jj * 7);
      if (jj == 3) break;
      uint32_t sV, pV, pK, pV1;
      ring_pos(ring, idxV(W), sV, pV);
      ring_pos(ring, idxV(W) + 1, sK, pK);
      ring_pos(ring, idxV(W) + 2, sV1, pV1);
      mbar_wait(bud, BAR_FULLA + sV, pV);
      bar_sync(1 + W, 256);
      MMA_BEGIN();
      mma_both<W, true>(ds, om, oh, sV, pown);
      wg_commit();
      mbar_wait(bud, BAR_FULLA + sK, pK);
      TL(11 + jj * 7);
      MMA_BEGIN();
      s_mma<0, false>(ds, sacc, sK);
      if (W == 1) wg_commit();
      s_mma<1, true>(ds, sacc, sK);
      wg_commit();
      wg_wait<1 + W>();
      mbar_arrive_if0(BAR_EMPTYA + sV, tid);
      if (W == 1) {
        wg_wait<1>();
        mbar_arrive_if0(BAR_EMPTYB, tid | (jj != 2));
      }
      MMA_BEGIN();
      s_mma<2, true>(ds, sacc, sK);
      wg_commit();
      TL(13 + jj * 7);
      mbar_wait(bud, BAR_FULLA + sV1, pV1);
      mbar_wait(bud, BAR_PFREE + W * 8, jj & 1);
      mbar_wait(bud, BAR_PFULL + (1 - W) * 8, (jj + W) & 1);
      TL(14 + jj * 7);
      MMA_BEGIN();
      mma_both<W, true>(ds, om, oh, sV1, poth);
      wg_commit();
      bar_arrive(2 - W, 256);
      ring_advance(ring, 4);
    }
    uint32_t sV6, pV6, sV7, pV7;
    ring_pos(ring, idxV(6) - 12, sV6, pV6);
    ring_pos(ring, idxV(7) - 12, sV7, pV7);
    prev = item;
    mbar_wait(bud, BAR_FULLA + (W == 0 ? sV6 : sV7), W == 0 ? pV6 : pV7);
    if (!DEBUG_TIMEOUT) item = next_item();
    bar_sync(W == 0 ? 1 : 6, 256);
    if (DEBUG_TIMEOUT) item = next_item(NEXT_ITEM + 4);
    if (item >= NITEMS) {
      MMA_BEGIN();
      if (W == 0) {
        mma_both<0, true>(ds, om, oh, sV6, pown);
        wg_commit();
        mbar_wait(bud, BAR_FULLA + sV7, pV7);
        mbar_wait(bud, BAR_PFULL + 8, 1);
        MMA_BEGIN();
      }
      mma_both<W, true>(ds, om, oh, sV7, B_ADDR(4));
      wg_commit();
      if (W == 0) bar_arrive(6, 256);
      TL(32);
      wg_wait<0>();
      reg_fence(om); reg_fence(oh);
      TL(33);
      mbar_wait(bud, BAR_LFULL, par);
      mbar_arrive_if0(BAR_FREE, tid);
      TL(34);
      pack_first<W>(pk, om, oh, laddr);
      op = o_ptr(prev);
      store_groups<W, 0, 10>(op, pk, 1);
      pack_second<W, 0, 5>(pk, om, laddr);
      store_groups<W, 10, 15>(op, pk, 1);
      publish_generic(BAR_OFULL, lane);
      TL(35); TLG(63);
      TL_FLUSH();
      return item;
    }
    {
      MMA_BEGIN();
      mma_both<W, true>(ds, om, oh, W == 0 ? sV6 : sV7, pown);
      wg_commit();
      if (W == 0) mbar_wait(bud, BAR_FULLA + sV7, pV7);
      WAIT_CHUNK(0, 26 - 12, s0)
      TL(38);
      MMA_BEGIN();
      mma_main<W, false>(ds, sacc, s0, B_ADDR(xs(0)));
      wg_commit();
      if (W == 0) {
        wg_wait<1>();
        mbar_arrive_if0(BAR_EMPTYA + sV6, tid);
        mbar_wait(bud, BAR_PFULL + 8, 1);
        MMA_BEGIN();
        mma_both<0, true>(ds, om, oh, sV7, poth);
        wg_commit();
        bar_arrive(6, 256);
      }
      TL(32);
      WAIT_CHUNK(1, 26 - 12, s1)
      if (W == 0) wg_wait<0>(); else wg_wait<1>();
      reg_fence(om); reg_fence(oh);
      mbar_arrive_if0(BAR_EMPTYA + sV7, tid);
      TL(33);
      MMA_BEGIN();
      mma_main<W, true>(ds, sacc, s1, B_ADDR(xs(1)));
      wg_commit();
      mbar_wait(bud, BAR_LFULL, par);
      mbar_arrive_if0(BAR_EMPTYB + 24 + tid * 8, tid >= 2);
      TL(34);
      pack_first<W>(pk, om, oh, laddr);
      TL(36);
      MMA_BEGIN();
      mma_mid<W, false>(ds, oh, s0, B_ADDR(xs(0)));
      wg_commit();
      mma_mid<W, true>(ds, oh, s1, B_ADDR(xs(1)));
      wg_commit();
      TL(37);
      wg_wait<1>();
      RELEASE_CHUNK(0, s0)
      TL(35); TLG(63);
    }
    TL_FLUSH();
    TL(0); TLG(62);
    ring_advance(ring, 26 - 12);
    par ^= 1;
  }
}

__device__ __forceinline__ uint4 lds128(uint32_t a) {
  uint4 v;
  asm volatile("ld.shared.v4.b32 {%0,%1,%2,%3}, [%4];" : "=r"(v.x), "=r"(v.y), "=r"(v.z), "=r"(v.w) : "r"(a) : "memory");
  return v;
}
__device__ __forceinline__ void acc2(float& s, float& t, uint32_t w) {
  s += __uint_as_float(w << 16);
  t += __uint_as_float(w & 0xffff0000u);
}
__device__ __forceinline__ uint32_t badd2(uint32_t a, uint32_t b) { uint32_t r; asm("add.rn.bf16x2 %0, %1, %2;" : "=r"(r) : "r"(a), "r"(b)); return r; }
__device__ __forceinline__ void sum_unit(float& acc, uint32_t pb) {
  const uint4 v0 = lds128(pb), v1 = lds128(pb ^ 32), v2 = lds128(pb ^ 64), v3 = lds128(pb ^ 96);
  const uint32_t w0 = badd2(badd2(v0.x, v0.y), badd2(v0.z, v0.w));
  float s = acc + __uint_as_float(w0 << 16), t = __uint_as_float(w0 & 0xffff0000u);
  acc2(s, t, badd2(badd2(v1.x, v1.y), badd2(v1.z, v1.w)));
  acc2(s, t, badd2(badd2(v2.x, v2.y), badd2(v2.z, v2.w)));
  acc2(s, t, badd2(badd2(v3.x, v3.y), badd2(v3.z, v3.w)));
  acc = s + t;
}
__device__ __forceinline__ float bf_lo(uint32_t w) { return __uint_as_float(w << 16); }
__device__ __forceinline__ float bf_hi(uint32_t w) { return __uint_as_float(w & 0xffff0000u); }
__device__ __forceinline__ float bf_rn(float x) { return __bfloat162float(__float2bfloat16(x)); }
__device__ __forceinline__ void slow_item(const Params& p, int item, int hw) {
  const int blk = item >> 9, h = (item >> 4) & 31, b = item & 15;
#pragma unroll 1
  for (int n = hw; n < SQ; n += 3) {
    float q[6] = {0.f, 0.f, 0.f, 0.f, 0.f, 0.f};
    {
      const uint32_t* xr = (const uint32_t*)(p.xp[blk] + (size_t)(b * SQ + n) * DM);
      const uint32_t* wq = (const uint32_t*)(p.wqp[blk] + h * DH) + (tid_x() & 31);
#pragma unroll 2
      for (int k = 0; k < DM / 2; k++) {
        const uint32_t xv = xr[k];
#pragma unroll
        for (int i = 0; i < 3; i++) {
          const uint32_t w0 = wq[i * 32], w1 = wq[NH * DH / 2 + i * 32];
          q[2 * i] = fmaf(bf_lo(xv), bf_lo(w0), fmaf(bf_hi(xv), bf_lo(w1), q[2 * i]));
          q[2 * i + 1] = fmaf(bf_lo(xv), bf_hi(w0), fmaf(bf_hi(xv), bf_hi(w1), q[2 * i + 1]));
        }
        wq += NH * DH;
      }
    }
    const uint32_t q0 = pack2(q[0], q[1]), q1 = pack2(q[2], q[3]), q2 = pack2(q[4], q[5]);
    float o[6] = {0.f, 0.f, 0.f, 0.f, 0.f, 0.f}, m = -INFINITY, l = 0.f;
    const uint32_t* kg = (const uint32_t*)(p.kp[blk] + (size_t)(b * NH + h) * SK * DH) + (tid_x() & 31);
    const uint32_t* vg = (const uint32_t*)(p.vp[blk] + (size_t)(b * NH + h) * SK * DH) + (tid_x() & 31);
#pragma unroll 1
    for (int k = 0; k < SK; k++) {
      const uint32_t k0 = kg[0], k1 = kg[32], k2 = kg[64], v0 = vg[0], v1 = vg[32], v2 = vg[64];
      kg += DH / 2; vg += DH / 2;
      float sc = fmaf(bf_lo(q0), bf_lo(k0), bf_hi(q0) * bf_hi(k0));
      sc = fmaf(bf_lo(q1), bf_lo(k1), fmaf(bf_hi(q1), bf_hi(k1), sc));
      sc = fmaf(bf_lo(q2), bf_lo(k2), fmaf(bf_hi(q2), bf_hi(k2), sc));
#pragma unroll
      for (int d = 16; d; d >>= 1) sc += __shfl_xor_sync(0xffffffffu, sc, d);
      sc = bf_rn(bf_rn(sc) * 0.07216878364870322f);
      const float mn = fmaxf(m, sc), a = ex2((m - mn) * 1.4426950408889634f), pr = ex2((sc - mn) * 1.4426950408889634f);
      m = mn;
      l = fmaf(l, a, pr);
      o[0] = fmaf(o[0], a, pr * bf_lo(v0)); o[1] = fmaf(o[1], a, pr * bf_hi(v0));
      o[2] = fmaf(o[2], a, pr * bf_lo(v1)); o[3] = fmaf(o[3], a, pr * bf_hi(v1));
      o[4] = fmaf(o[4], a, pr * bf_lo(v2)); o[5] = fmaf(o[5], a, pr * bf_hi(v2));
    }
    float inv;
    asm("rcp.approx.ftz.f32 %0, %1;" : "=f"(inv) : "f"(l));
    const int lane = tid_x() & 31;
    const int r = n & 15, c = 4 * ((r & 7) >> 1) + 2 * (r >> 3) + (r & 1);
    char* on = o_slot(item) + (lane >> 2) * 256 + (lane & 3) * 64 + (n >> 4) * 2048 +
               (((c >> 3) ^ ((lane >> 1) & 1)) << 4) + (c & 7) * 2;
#pragma unroll
    for (int i = 0; i < 3; i++) {
      *(__nv_bfloat16*)(on + i * B_SLOT) = __float2bfloat16(o[2 * i] * inv);
      *(__nv_bfloat16*)(on + i * B_SLOT + 32) = __float2bfloat16(o[2 * i + 1] * inv);
    }
  }
}
__device__ __forceinline__ void attn_helper(const Params& p, int hw, int item, int epoch) {
  int bud = WAIT_BUDGET;
  if (hw == 2) {
    if (item == 0 && elect_one()) {
      *(volatile int*)&g_ticket = 0;
      asm volatile("red.release.gpu.global.add.s32 [%0], 1;" ::"l"(&g_go) : "memory");
    }
    __syncwarp();
    flag_wait(bud, &g_go, epoch + 1);
  }
  if (item < PF_N && hw < 2) {
    const char* g = (const char*)(hw ? p.vp[0] : p.kp[0]) + (size_t)(((item & 15) * NH + (item >> 4)) * SK) * DH * 2;
    const long long t0 = clock64();
#pragma unroll 1
    for (int i = 0; i < 32; i++) {
      while (clock64() - t0 < PF_WAIT + i * PF_GAP) __nanosleep(50);
      for (int k = 0; k < 6; k++) asm volatile("prefetch.global.L2 [%0];" ::"l"(g + i * 6144 + k * 1024 + (tid_x() & 31) * 32));
      __syncwarp();
    }
  }
#pragma unroll 1
  for (int it = 0; item < NITEMS; it++) {
    const uint32_t par = it & 1;
    int lane = tid_x() & 31;
    const int r = lane >> 1;
    const uint32_t a0 = B_ADDR(3) + (16 * hw + r) * 128 + (lane & 1) * 16 + ((r & 3) << 5);
    float acc[4] = {0.f, 0.f, 0.f, 0.f};
#pragma unroll 1
    for (int j = 0; j < 8; j++) {
      const uint32_t pb = a0 + (j & 1) * B_SLOT, bfull = BAR_PFULL + (j & 1) * 8, pfull = (j >> 1) & 1;
      mbar_wait(bud, j == 7 ? BAR_PMID : bfull, j == 7 ? par : pfull);
      sum_unit(acc[0], pb);
      sum_unit(acc[1], pb + 6144);
      if (j == 7) mbar_wait(bud, bfull, pfull);
      sum_unit(acc[2], pb + 2 * 6144);
      if (hw == 0) sum_unit(acc[3], pb + 3 * 6144);
      __syncwarp();
      mbar_arrive_if0(BAR_PFREE + (j & 1) * 8, lane);
      if (j == 5 && hw == 2) {
        if (lane == 0) TLP(60);
        if (item >= ORING && item < OFRESH) flag_wait(bud, &g_done[item - ORING], (epoch + 1) * 2);
        if (lane == 0) TLP(61);
      }
    }
    bool bad = false;
    const uint32_t la = SB + OFF_L + (((r & 7) >> 1) * 40 + 2 * (r >> 3) + (r & 1) + 4 * hw) * 4;
#pragma unroll
    for (int u = 0; u < 4; u++) {
      const float l = acc[u] + __shfl_xor_sync(0xffffffffu, acc[u], 1);
      if (u < 3 || hw == 0) {
        bad |= !(l >= 9.094947017729282e-13f && l <= 1.099511627776e12f);
        float inv;
        asm("rcp.approx.ftz.f32 %0, %1;" : "=f"(inv) : "f"(l));
        asm volatile("st.shared.f32 [%0], %1;" ::"r"(la + u * 48), "f"(inv) : "memory");
      }
    }
    publish_generic(BAR_LFULL, lane);
    if (lane == 0) TLP(40 + hw * 4);
    uint32_t anybad;
    asm volatile("{\n.reg .pred p, q;\nsetp.ne.u32 p, %1, 0;\nbarrier.red.or.pred q, 7, 96, p;\nselp.u32 %0, 1, 0, q;\n}\n"
                 : "=r"(anybad) : "r"((uint32_t)bad) : "memory");
    if (__any_sync(0xffffffffu, anybad)) {
      mbar_wait(bud, BAR_OFULL, par);
      slow_item(p, item, hw);
      bar_sync(7, 96);
    }
    if (hw == 1) {
      mbar_wait(bud, BAR_OFULL, par);
      if ((tid_x() & 31) == 0) {
        TLP(41 + hw * 4);
        asm volatile("red.release.gpu.global.add.s32 [%0], 1;" ::"l"(&g_ready[item]) : "memory");
        TLP(42 + hw * 4);
      }
      __syncwarp();
    }
    item = next_item();
  }
}

__device__ __forceinline__ int attn_producer(const Params& p, int item) {
  int bud = WAIT_BUDGET;
  uint32_t sa = 0, pa = 1;
  const uint64_t pol = evict_first_policy();
  const bool draws = item >= N_OCTA;
  const int delay = start_delay(item);
  {
    const long long t0 = clock64();
    while (clock64() - t0 < delay) __nanosleep(100);
  }
#pragma unroll 1
  for (int it = 0; item < NITEMS; it++) {
    const int blk = item >> 9, h = (item >> 4) & 31, b = item & 15;
    const int row0 = (b * NH + h) * SK;
    if (!(it | delay)) pa = 0;
#pragma unroll 1
    for (int c = (it | delay) ? 0 : NSLOT; c < 10; c++) {
      const uint32_t sx = c < NSLOT ? c : c - NSLOT;
      mbar_wait(bud, BAR_EMPTYA + sa * 8, pa);
      TLP(c);
      mbar_expect(BAR_FULLA + sa * 8, A_SLOT + B_SLOT);
      tma3d(A_ADDR(sa), &p.wq[blk], BAR_FULLA + sa * 8, 0, c * 64, h * 3);
      mbar_wait(bud, BAR_EMPTYB + sx * 8, c < NSLOT);
      TLP(10 + c);
      tma2d(B_ADDR(sx), &p.x[blk], BAR_FULLA + sa * 8, c * 64, b * SQ);
      if (++sa == NSLOT) { sa = 0; pa ^= 1; }
    }
#pragma unroll 1
    for (int i = 0; i < 16; i++) {
      const bool isK = (i == 0) || ((i & 1) && i < 15);
      const int j = i == 0 ? 0 : (i == 15 ? 7 : (isK ? (i + 1) >> 1 : (i - 2) >> 1));
      mbar_wait(bud, BAR_EMPTYA + sa * 8, pa);
      TLP(20 + i);
      mbar_expect(BAR_FULLA + sa * 8, A_SLOT);
      tma3d_hint(A_ADDR(sa), isK ? &p.k[blk] : &p.v[blk], BAR_FULLA + sa * 8, 0, row0 + j * 64, 0, pol);
      if (i == 12) {
        item = draws ? NCTA + atomicAdd(&g_ticket, 1) : NITEMS;
        asm volatile("st.shared.s32 [%0], %1;" ::"r"(NEXT_ITEM), "r"(item) : "memory");
      }
      if (++sa == NSLOT) { sa = 0; pa ^= 1; }
    }
  }
  return item;
}

struct OJob { int tile, part, c0, n; };
__device__ __forceinline__ OJob get_ojob(int cta, int last) {
  if (cta < N_OCTA) return OJob{cta, 0, 0, CHUNK1};
  const int u = last - NITEMS, part = 1 + (u >> 5), tile = part == 3 ? 95 - u : u & 31;
  const int c1 = CHUNK1, c2 = c1 + LEN1 - ((tile * LSLOPE1 + 16) >> 5), c3 = c2 + LEN2 - ((tile * LSLOPE2 + 16) >> 5);
  return OJob{tile, part, part == 1 ? c1 : part == 2 ? c2 : c3, part == 1 ? c2 - c1 + 1 : part == 2 ? c3 - c2 + 1 : part == 3 ? 189 - c3 + 1 : 0};
}
__device__ __forceinline__ int unperm(int c) { return 8 * ((c >> 1) & 1) + 4 * (c >> 3) + 2 * ((c >> 2) & 1) + (c & 1); }
__device__ __forceinline__ uint32_t first_stage(const OJob& job) { return job.part ? (uint32_t)(300 - job.n) % 3 : 0; }

__device__ __forceinline__ void oproj_consumer(const Params& p, const OJob job, const int W) {
  int bud = WAIT_BUDGET;
  const int tid = tid_x() & 127, lane = tid & 31, warp = tid >> 5;
  float a0[80], a1[80], ah[40];
  zero_regs(a0); zero_regs(a1); zero_regs(ah);
  const uint64_t dam = p.dsw + W * (3 * 8192 >> 4), dbh = p.dso + W * (10240 >> 4);
  int left = job.n, step = 0;
  uint32_t st = first_stage(job), ph = 0;
#pragma unroll 1
  while (left) {
    const int nc = left > 3 * NH ? 3 * NH : left;
    left -= nc;
#pragma unroll 1
    for (int c = 0; c < nc; c++) {
      mbar_wait(bud, BAR_GFULL + st * 8, (ph >> st) & 1);
      ph ^= 1 << st;
      bar_sync_if0(11, W | (c + 1 - nc));
      wg_fence();
      const uint32_t la = st, lb = st;
#define O_STEP(ks, sc)                                                        \
  mma80r<1, 1, 2 * 8192 + ks * 2048, SB + O_AB + ks * 512>(ah, p.dsw, la, dbh, lb, sc);   \
  mma160r<1, 1, ks * 2048, SB + O_AB + ks * 512>(a0, dam, la, p.dso, lb, sc);             \
  mma160r<1, 1, 8192 + ks * 2048, SB + O_AB + ks * 512>(a1, dam, la, p.dso, lb, sc);
      O_STEP(0, c != 0) O_STEP(1, 1)
      wg_commit();
      wg_wait<1>();
      mbar_arrive_if0(BAR_GEMPTY + (st == 0 ? 2 : st - 1) * 8, tid | (c == 0));
      wg_fence();
      O_STEP(2, 1) O_STEP(3, 1)
#undef O_STEP
      wg_commit();
      if (++st == 3) {
        st = 0;
        asm volatile("{\n.reg .pred p;\nsetp.eq.u32 p, %1, 0;\n@p red.relaxed.gpu.global.add.s32 [%0], 1;\n}\n"
                     ::"l"(&g_done[step * 16 + (job.tile >> 1)]), "r"(tid | job.part | W) : "memory");
        TLG(step);
        step++;
      }
    }
    if (W) bar_arrive(11, 256);
    wg_wait<0>();
    reg_fence(a0); reg_fence(a1); reg_fence(ah);
    mbar_arrive_if0(BAR_GEMPTY + (st - 1) * 8, tid | (st == 0));
    TLG(63);
    const int prow = (lane & 7) + 8 * (lane >> 4), qrow = left ? unperm(prow) : prow;
    const uint32_t sg = SB + O_OUT + qrow * 128 + (((2 * warp + ((lane >> 3) & 1)) ^ (qrow & 7)) << 4);
    if (W) bar_arrive(3, 256); else bar_arrive(9, 256);
    bar_sync_if0(3, W);
    store_scaled(sg + W * 3 * B_SLOT, a0, 1.0f);
    publish(BAR_GOUT + W * 24, lane);
    store_scaled(sg + W * 3 * B_SLOT + B_SLOT, a1, 1.0f);
    publish(BAR_GOUT + W * 24 + 8, lane);
    bar_sync_if0(9, W - 1);
    store_scaled(sg + 2 * B_SLOT + W * 10240, ah, 1.0f);
    publish(BAR_GOUT + 16, lane);
  }
  TL_FLUSH();
  TLG(0);
  float acc[7][8];
  uint32_t in[7], blk[7], oo[7];
#pragma unroll
  for (int i = 0; i < 7; i++) {
    const int e = min(i * 256 + W * 128 + tid, 1599), r = e / 40, cc = e % 40, R = job.part * 40 + r;
    in[i] = r * 128 + (((cc ^ r) & 7) << 4);
    blk[i] = cc >> 3;
    oo[i] = ((R & ~15) + unperm(R & 15)) * (2 * DM / 8) + cc;
    asm volatile("" : "+r"(oo[i]));
#pragma unroll
    for (int k = 0; k < 8; k++) acc[i][k] = 0.f;
  }
  bar_sync(10, 256);
#pragma unroll 1
  for (int q = 0; q < 4; q++) {
    if (q) mbar_wait(bud, BAR_GRED + (q - 1) * 8, 0);
    if (q == 3) TLG(1);
    const uint32_t base = q ? SB + (q - 1) * 25600 : SB + O_OUT + job.part * 5120, bs = q ? 5120 : B_SLOT;
    uint4 v[7];
#pragma unroll
    for (int i = 0; i < 7; i++) v[i] = lds128(base + blk[i] * bs + in[i]);
#pragma unroll
    for (int i = 0; i < 7; i++) {
      acc[i][0] += bf_lo(v[i].x); acc[i][1] += bf_hi(v[i].x); acc[i][2] += bf_lo(v[i].y); acc[i][3] += bf_hi(v[i].y);
      acc[i][4] += bf_lo(v[i].z); acc[i][5] += bf_hi(v[i].z); acc[i][6] += bf_lo(v[i].w); acc[i][7] += bf_hi(v[i].w);
    }
  }
  uint4* go = (uint4*)p.outp + (job.tile >> 1) * SQ * (2 * DM / 8) + DM / 8 + (job.tile & 1) * 40;
#pragma unroll
  for (int i = 0; i < 7; i++) {
    if (i * 256 + W * 128 + tid < 1600)
      go[oo[i]] = make_uint4(pack2(acc[i][0], acc[i][1]), pack2(acc[i][2], acc[i][3]), pack2(acc[i][4], acc[i][5]), pack2(acc[i][6], acc[i][7]));
  }
  TLG(2);
  TL_FLUSH();
}

__device__ __forceinline__ void oproj_producer(const Params& p, const OJob job, int target) {
  int bud = WAIT_BUDGET;
  const uint64_t polo = evict_first_policy();
  mbar_wait(bud, BAR_FREE, 0);
  uint32_t st = first_stage(job), ph = 7;
  int seen = -1;
#pragma unroll 1
  for (int i = 0; i < job.n; i++) {
    const int c = job.part && i == job.n - 1 ? 188 + job.part : job.c0 + i, step = c / 3, kb = c - 3 * step;
    const int item = step * 16 + (job.tile >> 1);
    if (step != seen) {
      flag_wait(bud, &g_ready[item], target);
      asm volatile("fence.proxy.async.global;" ::: "memory");
      seen = step;
    }
    const uint32_t dst = SB + st * O_STAGE, bar = BAR_GFULL + st * 8;
    const char* og = o_slot(item) + kb * B_SLOT;
    mbar_wait(bud, BAR_GEMPTY + st * 8, (ph >> st) & 1);
    ph ^= 1 << st;
    mbar_expect(bar, O_STAGE);
    tma3d(dst, &p.wo[step >> 5], bar, 0, (c - (step >> 5) * 3 * NH) * 64, (job.tile & 1) * 5);
    bulk_load_hint(dst + O_AB, og, B_SLOT, bar, polo);
    if (++st == 3) st = 0;
  }
  mbar_wait(bud, BAR_GEMPTY, ph & 1);
  mbar_wait(bud, BAR_GEMPTY + 8, (ph >> 1) & 1);
  uint32_t todo = 15 & ~(1 << job.part), dst = SB, bar = BAR_GRED;
  while (todo) {
    int v0, v1, v2, v3;
    asm volatile("ld.acquire.gpu.global.v4.s32 {%0, %1, %2, %3}, [%4];" : "=r"(v0), "=r"(v1), "=r"(v2), "=r"(v3) : "l"(&g_pcnt[job.tile * 4]) : "memory");
    const uint32_t rdy = --bud > 0 ? (v0 - target >= 0) | (v1 - target >= 0) << 1 | (v2 - target >= 0) << 2 | (v3 - target >= 0) << 3 : 15;
    if (!(rdy & todo)) continue;
    asm volatile("fence.proxy.async.global;" ::: "memory");
#pragma unroll 1
    for (int q = 0; q < 4; q++) {
      if (!(((rdy & todo) >> q) & 1)) continue;
      TLE(4 + q);
      mbar_expect(bar, 25600);
      for (int k = 0; k < 5; k++)
        tma2d(dst + k * 5120, &p.part, bar, (job.tile & 1) * 320 + k * 64, q * NB * SQ + (job.tile >> 1) * SQ + job.part * 40);
      todo &= ~(1 << q);
      dst += 25600;
      bar += 8;
    }
  }
}

__device__ __forceinline__ void oproj_storer(const Params& p, const OJob job) {
  int bud = WAIT_BUDGET;
  const int col = (job.tile & 1) * 320, row = (job.tile >> 1) * SQ;
  if (job.part == 0) {
    for (int k = 0; k < 3; k++) {
      mbar_wait(bud, BAR_GOUT + k * 8, 0);
      tma_store2d(&p.out, SB + O_OUT + k * B_SLOT, col + k * 64, row);
    }
    asm volatile("cp.async.bulk.commit_group;" ::: "memory");
    asm volatile("cp.async.bulk.wait_group.read 0;" ::: "memory");
    mbar_arrive2_if0(BAR_GEMPTY + 16, 0);
    mbar_wait(bud, BAR_GFULL + 16, 0);
    for (int k = 3; k < 5; k++) {
      mbar_wait(bud, BAR_GOUT + k * 8, 0);
      tma_store2d(&p.out, SB + O_OUT + k * B_SLOT, col + k * 64, row);
      asm volatile("cp.async.bulk.commit_group;" ::: "memory");
      asm volatile("cp.async.bulk.wait_group.read 0;" ::: "memory");
      __nanosleep(1000);
    }
  }
#pragma unroll 1
  for (int i = 0; i < 5; i++) {
    const int k = (0x21043 >> (4 * i)) & 15;
    mbar_wait(bud, BAR_GOUT + k * 8, job.part == 0);
    if (i == 0) TLE(0);
    for (int q = 1; q < 4; q++) {
      const int sh = (job.part + q) & 3;
      tma_store2d(&p.part, SB + O_OUT + k * B_SLOT + sh * 5120, col + k * 64, job.part * NB * SQ + row + sh * 40);
    }
  }
  asm volatile("cp.async.bulk.commit_group;" ::: "memory");
  TLE(1);
  asm volatile("cp.async.bulk.wait_group 0;" ::: "memory");
  TLE(2);
  asm volatile("fence.proxy.async.global;" ::: "memory");
  asm volatile("red.release.gpu.global.add.s32 [%0], 1;" ::"l"(&g_pcnt[job.tile * 4 + job.part]) : "memory");
  TLE(3);
}

__global__ void __launch_bounds__(384, 1) fused_kernel(const __grid_constant__ Params p) {
  extern __shared__ __align__(1024) char smem_raw[];
  if ((smem_u32(smem_raw) & 0xFFFFFFu) != SB) return;
  const int cta = (((blockIdx.x / PERM_G) * PERM_M) % (NCTA / PERM_G)) * PERM_G + (blockIdx.x % PERM_G);
  const int warp = __shfl_sync(0xffffffffu, threadIdx.x >> 5, 0);
  if (threadIdx.x == 0) {
    for (int i = 0; i < NSLOT; i++) { mbar_init(BAR_FULLA + i * 8, 1); mbar_init(BAR_EMPTYA + i * 8, 2); mbar_init(BAR_EMPTYB + i * 8, 2); }
    proxy_fence();
    if (start_delay(cta) == 0) {
#pragma unroll 1
      for (int c = 0; c < NSLOT; c++) {
        mbar_expect(BAR_FULLA + c * 8, A_SLOT + B_SLOT);
        tma3d(A_ADDR(c), &p.wq[0], BAR_FULLA + c * 8, 0, c * 64, (cta >> 4) * 3);
        tma2d(B_ADDR(c), &p.x[0], BAR_FULLA + c * 8, c * 64, (cta & 15) * SQ);
      }
    }
  }
  if (threadIdx.x == 64) {
    mbar_init(BAR_XDONE, 1); mbar_init(BAR_QH, 4); mbar_init(BAR_QM, 4);
    mbar_init(BAR_PFULL, 4); mbar_init(BAR_PFULL + 8, 4); mbar_init(BAR_PFREE, 3); mbar_init(BAR_PFREE + 8, 3);
    mbar_init(BAR_LFULL, 3); mbar_init(BAR_PMID, 4); mbar_init(BAR_OFULL, 8);
  }
  if (threadIdx.x == 96) {
    for (int i = 0; i < O_NST; i++) { mbar_init(BAR_GFULL + i * 8, 1); mbar_init(BAR_GEMPTY + i * 8, 2); }
    for (int i = 0; i < 5; i++) mbar_init(BAR_GOUT + i * 8, i == 2 ? 8 : 4);
    mbar_init(BAR_GRED, 1); mbar_init(BAR_GRED + 8, 1); mbar_init(BAR_GRED + 16, 1); mbar_init(BAR_FREE, 2);
    proxy_fence();
  }
  __syncthreads();
  if (warp >= 8) {
    asm volatile("setmaxnreg.dec.sync.aligned.u32 40;");
    if (warp == 8) {
      if (elect_one()) {
        const OJob job = get_ojob(cta, attn_producer(p, cta));
        const int epoch = *(volatile int*)&g_epoch[cta];
        *(volatile int*)&g_epoch[cta] = epoch + 1;
        if (job.n) oproj_producer(p, job, epoch + 1);
      }
    } else {
      const int epoch = __shfl_sync(0xffffffffu, *(volatile int*)&g_epoch[cta], 0);
      attn_helper(p, warp - 9, cta, epoch);
      if (warp == 9) {
        const OJob job = get_ojob(cta, next_item());
        if (job.n && elect_one()) oproj_storer(p, job);
      }
    }
  } else {
    asm volatile("setmaxnreg.inc.sync.aligned.u32 232;");
    const OJob job = get_ojob(cta, warp < 4 ? attn_consumer<0>(p.dsw, p.zero, cta) : attn_consumer<1>(p.dsw, p.zero, cta));
    if (job.n) oproj_consumer(p, job, warp >> 2);
  }
}

typedef CUresult (*EncodeFn)(CUtensorMap*, CUtensorMapDataType, cuuint32_t, void*, const cuuint64_t*, const cuuint64_t*, const cuuint32_t*,
                             const cuuint32_t*, CUtensorMapInterleave, CUtensorMapSwizzle, CUtensorMapL2promotion, CUtensorMapFloatOOBfill);

void make3d(EncodeFn enc, CUtensorMap* m, const void* ptr, uint64_t rows, uint64_t cols, uint32_t box_rows, uint32_t box_blocks,
            CUtensorMapL2promotion promo = CU_TENSOR_MAP_L2_PROMOTION_L2_128B) {
  cuuint64_t gd[3] = {64, rows, cols / 64};
  cuuint64_t gs[2] = {cols * 2, 128};
  cuuint32_t bd[3] = {64, box_rows, box_blocks}, es[3] = {1, 1, 1};
  enc(m, CU_TENSOR_MAP_DATA_TYPE_BFLOAT16, 3, (void*)ptr, gd, gs, bd, es, CU_TENSOR_MAP_INTERLEAVE_NONE, CU_TENSOR_MAP_SWIZZLE_128B,
      promo, CU_TENSOR_MAP_FLOAT_OOB_FILL_NONE);
}
void make2d(EncodeFn enc, CUtensorMap* m, const void* ptr, uint64_t rows, uint64_t cols, uint32_t box_rows) {
  cuuint64_t gd[2] = {cols, rows};
  cuuint64_t gs[1] = {cols * 2};
  cuuint32_t bd[2] = {64, box_rows}, es[2] = {1, 1};
  enc(m, CU_TENSOR_MAP_DATA_TYPE_BFLOAT16, 2, (void*)ptr, gd, gs, bd, es, CU_TENSOR_MAP_INTERLEAVE_NONE, CU_TENSOR_MAP_SWIZZLE_128B,
      CU_TENSOR_MAP_L2_PROMOTION_L2_128B, CU_TENSOR_MAP_FLOAT_OOB_FILL_NONE);
}

}

extern "C" void kernel_launch(void* const* d_in, const int* in_sizes, int n_in, void* d_out, int out_size) {
  static EncodeFn enc = nullptr;
  static void* part = nullptr;
  if (!enc) {
    cudaGetSymbolAddress(&part, g_part);
    cudaDriverEntryPointQueryResult qr;
    cudaGetDriverEntryPoint("cuTensorMapEncodeTiled", (void**)&enc, cudaEnableDefault, &qr);
    cudaFuncSetAttribute(fused_kernel, cudaFuncAttributeMaxDynamicSharedMemorySize, SMEM_BYTES);
  }
  Params p;
  for (int s = 0; s < 2; s++) {
    make2d(enc, &p.x[s], d_in[5 * s + 0], NB * SQ, DM, SQ);
    make3d(enc, &p.k[s], d_in[5 * s + 1], (uint64_t)NB * NH * SK, DH, 64, 3);
    make3d(enc, &p.v[s], d_in[5 * s + 2], (uint64_t)NB * NH * SK, DH, 64, 3);
    make3d(enc, &p.wq[s], d_in[5 * s + 3], DM, NH * DH, 64, 3);
    make3d(enc, &p.wo[s], d_in[5 * s + 4], NH * DH, DM, 64, 5);
    p.xp[s] = (const __nv_bfloat16*)d_in[5 * s + 0];
    p.wqp[s] = (const __nv_bfloat16*)d_in[5 * s + 3];
    p.kp[s] = (const __nv_bfloat16*)d_in[5 * s + 1];
    p.vp[s] = (const __nv_bfloat16*)d_in[5 * s + 2];
  }
  make2d(enc, &p.out, d_out, NB * SQ, 2 * DM, SQ);
  make2d(enc, &p.part, part, 4 * NB * SQ, DM, 40);
  p.outp = (__nv_bfloat16*)d_out;
  p.dsw = DESC_SW;
  p.dso = DESC_O;
  p.zero = 0;
  fused_kernel<<<NCTA, 384, SMEM_BYTES>>>(p);
}
```

```cpp
#include <cuda_runtime.h>
#include <cuda_bf16.h>
#include <cuda.h>
#include <stdint.h>

#define DEBUG_TIMEOUT 0

namespace {

constexpr int SQ = 160, DM = 640, NH = 32, SK = 512, DH = 192, NB = 16;
constexpr int NITEMS = 2 * NB * NH;
constexpr int NCTA = 132, N_OCTA = 32;
constexpr int ORING = 192, OFRESH = 848, CHUNK1 = 158, LEN1 = 18, LEN2 = 13, LSLOPE1 = 4, LSLOPE2 = 5;
constexpr int STAG_G = 4, PERM_G = 4, STAG_A0 = 19, STAG_SLOPE = 275, PERM_M = 20, PF_N = 32, PF_WAIT = 1500, PF_GAP = 300;
constexpr int OSLOTS = ORING + NITEMS - OFRESH;
constexpr int A_SLOT = 24576, B_SLOT = 20480, NSLOT = 5;
constexpr int OFF_A = 0;
constexpr int OFF_B = NSLOT * A_SLOT;
constexpr int O_STAGE = 61440, O_AB = 40960, O_NST = 3;
constexpr int OFF_L = OFF_B + NSLOT * B_SLOT;
constexpr int OFF_BAR = OFF_L + 160 * 4;
constexpr int SMEM_BYTES = OFF_BAR + 512 + 768;
constexpr int O_OUT = 2 * O_STAGE;
static_assert(O_OUT + 5 * B_SLOT <= OFF_L, "smem layout");
constexpr uint32_t SB = 1024;
constexpr uint32_t BARS = SB + OFF_BAR;
constexpr uint32_t BAR_FULLA = BARS, BAR_EMPTYA = BARS + 40, BAR_PMID = BARS + 80, BAR_EMPTYB = BARS + 120, BAR_XDONE = BARS + 160,
                   BAR_QH = BARS + 168, BAR_QM = BARS + 96, BAR_PFULL = BARS + 184, BAR_PFREE = BARS + 200, BAR_LFULL = BARS + 216,
                   BAR_OFULL = BARS + 224, BAR_GFULL = BARS + 248, BAR_GEMPTY = BARS + 280, BAR_GOUT = BARS + 328, BAR_GRED = BARS + 368,
                   BAR_FREE = BARS + 240, NEXT_ITEM = BARS + 320;
constexpr int O_ITEM_BYTES = SQ * DH * 2;

struct alignas(64) Params {
  CUtensorMap x[2], wq[2], k[2], v[2], wo[2], out, part;
  uint64_t dsw, dso, zero;
  __nv_bfloat16* outp;
  const __nv_bfloat16 *xp[2], *wqp[2], *kp[2], *vp[2];
};

__device__ uint4 g_o[(size_t)OSLOTS * O_ITEM_BYTES / 16];
__device__ uint4 g_part[4 * NB * SQ * DM / 8];
__device__ __align__(16) int g_pcnt[4 * N_OCTA];
__device__ int g_ready[NITEMS];
__device__ int g_done[NITEMS];
__device__ int g_ticket;
__device__ int g_go;
__device__ int g_epoch[NCTA];

#define TLE(id)
#define TLP(id)
#define TLG(id)
#define TL(id)
#define TL_FLUSH()
__device__ __forceinline__ uint32_t smem_u32(const void* p) { return (uint32_t)__cvta_generic_to_shared(p); }
__device__ __forceinline__ void wg_fence() { asm volatile("wgmma.fence.sync.aligned;" ::: "memory"); }
__device__ __forceinline__ void wg_commit() { asm volatile("wgmma.commit_group.sync.aligned;" ::: "memory"); }
template <int N> __device__ __forceinline__ void wg_wait() { asm volatile("wgmma.wait_group.sync.aligned %0;" ::"n"(N) : "memory"); }
template <int N> __device__ __forceinline__ void reg_fence(float (&d)[N]) {
#pragma unroll
  for (int i = 0; i < N; i++) asm volatile("" : "+f"(d[i])::"memory");
}
template <int N> __device__ __forceinline__ void zero_regs(float (&d)[N]) {
#pragma unroll
  for (int i = 0; i < N; i++) d[i] = 0.f;
}
__device__ __forceinline__ void proxy_fence() { asm volatile("fence.proxy.async.shared::cta;" ::: "memory"); }
__device__ __forceinline__ void mbar_init(uint32_t bar, int cnt) { asm volatile("mbarrier.init.shared::cta.b64 [%0], %1;" ::"r"(bar), "r"(cnt) : "memory"); }
__device__ __forceinline__ void mbar_arrive_if0(uint32_t bar, uint32_t sel) {
  asm volatile("{\n.reg .pred p;\nsetp.eq.u32 p, %1, 0;\n@p mbarrier.arrive.shared::cta.b64 _, [%0];\n}\n" ::"r"(bar), "r"(sel) : "memory");
}
__device__ __forceinline__ void mbar_arrive2_if0(uint32_t bar, uint32_t sel) {
  asm volatile("{\n.reg .pred p;\nsetp.eq.u32 p, %1, 0;\n@p mbarrier.arrive.shared::cta.b64 _, [%0], 2;\n}\n" ::"r"(bar), "r"(sel) : "memory");
}
__device__ __forceinline__ void mbar_expect(uint32_t bar, uint32_t bytes) {
  asm volatile("mbarrier.arrive.expect_tx.shared::cta.b64 _, [%0], %1;" ::"r"(bar), "r"(bytes) : "memory");
}
__device__ __forceinline__ void mbar_wait(int& bud, uint32_t bar, uint32_t parity) {
  asm volatile(
      "{\n.reg .pred p;\n"
      "LW:\n"
      "mbarrier.try_wait.parity.shared::cta.b64 p, [%0], %1;\n"
      "@!p bra LW;\n}\n" ::"r"(bar), "r"(parity) : "memory");
}
constexpr int WAIT_BUDGET = 1 << 22;
__device__ __forceinline__ bool elect_one() {
  uint32_t p;
  asm volatile("{\n.reg .pred p;\nelect.sync _|p, 0xffffffff;\nselp.u32 %0, 1, 0, p;\n}\n" : "=r"(p));
  return p;
}
__device__ __forceinline__ void tma2d(uint32_t dst, const CUtensorMap* m, uint32_t bar, int c0, int c1) {
  asm volatile("cp.async.bulk.tensor.2d.shared::cluster.global.mbarrier::complete_tx::bytes [%0], [%1, {%3, %4}], [%2];"
               ::"r"(dst), "l"(m), "r"(bar), "r"(c0), "r"(c1) : "memory");
}
__device__ __forceinline__ void tma3d(uint32_t dst, const CUtensorMap* m, uint32_t bar, int c0, int c1, int c2) {
  asm volatile("cp.async.bulk.tensor.3d.shared::cluster.global.mbarrier::complete_tx::bytes [%0], [%1, {%3, %4, %5}], [%2];"
               ::"r"(dst), "l"(m), "r"(bar), "r"(c0), "r"(c1), "r"(c2) : "memory");
}
__device__ __forceinline__ void tma3d_hint(uint32_t dst, const CUtensorMap* m, uint32_t bar, int c0, int c1, int c2, uint64_t pol) {
  asm volatile("cp.async.bulk.tensor.3d.shared::cluster.global.mbarrier::complete_tx::bytes.L2::cache_hint [%0], [%1, {%3, %4, %5}], [%2], %6;"
               ::"r"(dst), "l"(m), "r"(bar), "r"(c0), "r"(c1), "r"(c2), "l"(pol) : "memory");
}
__device__ __forceinline__ void tma_store2d(const CUtensorMap* m, uint32_t src, int c0, int c1) {
  asm volatile("cp.async.bulk.tensor.2d.global.shared::cta.bulk_group [%0, {%2, %3}], [%1];" ::"l"(m), "r"(src), "r"(c0), "r"(c1) : "memory");
}
__device__ __forceinline__ void bar_sync(int id, int n) { asm volatile("bar.sync %0, %1;" ::"r"(id), "r"(n) : "memory"); }
__device__ __forceinline__ void bar_arrive(int id, int n) { asm volatile("bar.arrive %0, %1;" ::"r"(id), "r"(n) : "memory"); }
__device__ __forceinline__ void bar_sync_if0(int id, int sel) {
  asm volatile("{\n.reg .pred p;\nsetp.eq.s32 p, %1, 0;\n@p bar.sync %0, 256;\n}\n" ::"r"(id), "r"(sel) : "memory");
}
__device__ __forceinline__ float ex2(float x) { float y; asm("ex2.approx.ftz.f32 %0, %1;" : "=f"(y) : "f"(x)); return y; }
__device__ __forceinline__ uint32_t pack2(float lo, float hi) { uint32_t r; asm("cvt.rn.bf16x2.f32 %0, %1, %2;" : "=r"(r) : "f"(hi), "f"(lo)); return r; }
__device__ __forceinline__ void stsm_t(uint32_t a, uint32_t r0, uint32_t r1, uint32_t r2, uint32_t r3) {
  asm volatile("stmatrix.sync.aligned.m8n8.x4.trans.shared.b16 [%0], {%1,%2,%3,%4};" ::"r"(a), "r"(r0), "r"(r1), "r"(r2), "r"(r3) : "memory");
}
__device__ __forceinline__ uint64_t evict_first_policy() {
  uint64_t pol;
  asm volatile("createpolicy.fractional.L2::evict_first.b64 %0, 1.0;" : "=l"(pol));
  return pol;
}
__device__ __forceinline__ void bulk_load_hint(uint32_t dst, const void* src, uint32_t bytes, uint32_t bar, uint64_t pol) {
  asm volatile("cp.async.bulk.shared::cluster.global.mbarrier::complete_tx::bytes.L2::cache_hint [%0], [%1], %2, [%3], %4;"
               ::"r"(dst), "l"(src), "r"(bytes), "r"(bar), "l"(pol) : "memory");
}
__device__ __forceinline__ void flag_wait(int& bud, const int* p, int target) {
  while (true) {
    int v;
    asm volatile("ld.acquire.gpu.global.s32 %0, [%1];" : "=r"(v) : "l"(p) : "memory");
    if (v - target >= 0 || --bud <= 0) break;
    __nanosleep(64);
  }
}
constexpr uint64_t DESC_SW = 0x4000004000010000ull, DESC_O = 0xC000001000800000ull;
__device__ __forceinline__ uint32_t tid_x() { uint32_t t; asm volatile("mov.u32 %0, %tid.x;" : "=r"(t)); return t; }

template <int TA, int TB, uint32_t OA, uint32_t OB>
__device__ __forceinline__ void mma160(float (&d)[80], uint64_t ba, uint32_t la, uint64_t bb, uint32_t lb) {
  asm volatile(
      "{\n.reg .pred p;\n.reg .b64 da, db;\nsetp.eq.b32 p, 0, 0;\n"
      "mad.wide.u32 da, %80, 192, %86;\nadd.s64 da, da, %84;\nmad.wide.u32 db, %81, 1, %87;\nadd.s64 db, db, %85;\n"
      "wgmma.mma_async.sync.aligned.m64n160k16.f32.bf16.bf16 {"
      "%0,%1,%2,%3,%4,%5,%6,%7,%8,%9,%10,%11,%12,%13,%14,%15,%16,%17,%18,%19,%20,%21,%22,%23,%24,%25,%26,%27,%28,%29,%30,%31,%32,%33,%34,%35,%36,"
      "%37,%38,%39,%40,%41,%42,%43,%44,%45,%46,%47,%48,%49,%50,%51,%52,%53,%54,%55,%56,%57,%58,%59,%60,%61,%62,%63,%64,%65,%66,%67,%68,%69,%70,%71,"
      "%72,%73,%74,%75,%76,%77,%78,%79"
      "}, da, db, p, 1, 1, %82, %83;\n}\n"
      :
      "+f"(d[0]),"+f"(d[1]),"+f"(d[2]),"+f"(d[3]),"+f"(d[4]),"+f"(d[5]),"+f"(d[6]),"+f"(d[7]),"+f"(d[8]),"+f"(d[9]),"+f"(d[10]),"+f"(d[11]),
      "+f"(d[12]),"+f"(d[13]),"+f"(d[14]),"+f"(d[15]),"+f"(d[16]),"+f"(d[17]),"+f"(d[18]),"+f"(d[19]),"+f"(d[20]),"+f"(d[21]),"+f"(d[22]),
      "+f"(d[23]),"+f"(d[24]),"+f"(d[25]),"+f"(d[26]),"+f"(d[27]),"+f"(d[28]),"+f"(d[29]),"+f"(d[30]),"+f"(d[31]),"+f"(d[32]),"+f"(d[33]),
      "+f"(d[34]),"+f"(d[35]),"+f"(d[36]),"+f"(d[37]),"+f"(d[38]),"+f"(d[39]),"+f"(d[40]),"+f"(d[41]),"+f"(d[42]),"+f"(d[43]),"+f"(d[44]),
      "+f"(d[45]),"+f"(d[46]),"+f"(d[47]),"+f"(d[48]),"+f"(d[49]),"+f"(d[50]),"+f"(d[51]),"+f"(d[52]),"+f"(d[53]),"+f"(d[54]),"+f"(d[55]),
      "+f"(d[56]),"+f"(d[57]),"+f"(d[58]),"+f"(d[59]),"+f"(d[60]),"+f"(d[61]),"+f"(d[62]),"+f"(d[63]),"+f"(d[64]),"+f"(d[65]),"+f"(d[66]),
      "+f"(d[67]),"+f"(d[68]),"+f"(d[69]),"+f"(d[70]),"+f"(d[71]),"+f"(d[72]),"+f"(d[73]),"+f"(d[74]),"+f"(d[75]),"+f"(d[76]),"+f"(d[77]),
      "+f"(d[78]),"+f"(d[79])
      : "r"(la), "r"(lb), "n"(TA), "n"(TB), "n"((SB + OA) >> 4), "n"(OB >> 4), "l"(ba), "l"(bb));
}

template <int TA, int TB, uint32_t OA, uint32_t OB>
__device__ __forceinline__ void mma160z(float (&d)[80], uint64_t ba, uint32_t la, uint64_t bb, uint32_t lb) {
  asm volatile(
      "{\n.reg .pred p;\n.reg .b64 da, db;\nsetp.ne.b32 p, 0, 0;\n"
      "mad.wide.u32 da, %80, 192, %86;\nadd.s64 da, da, %84;\nmad.wide.u32 db, %81, 1, %87;\nadd.s64 db, db, %85;\n"
      "wgmma.mma_async.sync.aligned.m64n160k16.f32.bf16.bf16 {"
      "%0,%1,%2,%3,%4,%5,%6,%7,%8,%9,%10,%11,%12,%13,%14,%15,%16,%17,%18,%19,%20,%21,%22,%23,%24,%25,%26,%27,%28,%29,%30,%31,%32,%33,%34,%35,%36,"
      "%37,%38,%39,%40,%41,%42,%43,%44,%45,%46,%47,%48,%49,%50,%51,%52,%53,%54,%55,%56,%57,%58,%59,%60,%61,%62,%63,%64,%65,%66,%67,%68,%69,%70,%71,"
      "%72,%73,%74,%75,%76,%77,%78,%79"
      "}, da, db, p, 1, 1, %82, %83;\n}\n"
      :
      "=f"(d[0]),"=f"(d[1]),"=f"(d[2]),"=f"(d[3]),"=f"(d[4]),"=f"(d[5]),"=f"(d[6]),"=f"(d[7]),"=f"(d[8]),"=f"(d[9]),"=f"(d[10]),"=f"(d[11]),
      "=f"(d[12]),"=f"(d[13]),"=f"(d[14]),"=f"(d[15]),"=f"(d[16]),"=f"(d[17]),"=f"(d[18]),"=f"(d[19]),"=f"(d[20]),"=f"(d[21]),"=f"(d[22]),
      "=f"(d[23]),"=f"(d[24]),"=f"(d[25]),"=f"(d[26]),"=f"(d[27]),"=f"(d[28]),"=f"(d[29]),"=f"(d[30]),"=f"(d[31]),"=f"(d[32]),"=f"(d[33]),
      "=f"(d[34]),"=f"(d[35]),"=f"(d[36]),"=f"(d[37]),"=f"(d[38]),"=f"(d[39]),"=f"(d[40]),"=f"(d[41]),"=f"(d[42]),"=f"(d[43]),"=f"(d[44]),
      "=f"(d[45]),"=f"(d[46]),"=f"(d[47]),"=f"(d[48]),"=f"(d[49]),"=f"(d[50]),"=f"(d[51]),"=f"(d[52]),"=f"(d[53]),"=f"(d[54]),"=f"(d[55]),
      "=f"(d[56]),"=f"(d[57]),"=f"(d[58]),"=f"(d[59]),"=f"(d[60]),"=f"(d[61]),"=f"(d[62]),"=f"(d[63]),"=f"(d[64]),"=f"(d[65]),"=f"(d[66]),
      "=f"(d[67]),"=f"(d[68]),"=f"(d[69]),"=f"(d[70]),"=f"(d[71]),"=f"(d[72]),"=f"(d[73]),"=f"(d[74]),"=f"(d[75]),"=f"(d[76]),"=f"(d[77]),
      "=f"(d[78]),"=f"(d[79])
      : "r"(la), "r"(lb), "n"(TA), "n"(TB), "n"((SB + OA) >> 4), "n"(OB >> 4), "l"(ba), "l"(bb));
}

template <int TA, int TB, uint32_t OA, uint32_t OB>
__device__ __forceinline__ void mma80(float (&d)[40], uint64_t ba, uint32_t la, uint64_t bb, uint32_t lb) {
  asm volatile(
      "{\n.reg .pred p;\n.reg .b64 da, db;\nsetp.eq.b32 p, 0, 0;\n"
      "mad.wide.u32 da, %40, 192, %46;\nadd.s64 da, da, %44;\nmad.wide.u32 db, %41, 1, %47;\nadd.s64 db, db, %45;\n"
      "wgmma.mma_async.sync.aligned.m64n80k16.f32.bf16.bf16 {"
      "%0,%1,%2,%3,%4,%5,%6,%7,%8,%9,%10,%11,%12,%13,%14,%15,%16,%17,%18,%19,%20,%21,%22,%23,%24,%25,%26,%27,%28,%29,%30,%31,%32,%33,%34,%35,%36,"
      "%37,%38,%39"
      "}, da, db, p, 1, 1, %42, %43;\n}\n"
      :
      "+f"(d[0]),"+f"(d[1]),"+f"(d[2]),"+f"(d[3]),"+f"(d[4]),"+f"(d[5]),"+f"(d[6]),"+f"(d[7]),"+f"(d[8]),"+f"(d[9]),"+f"(d[10]),"+f"(d[11]),
      "+f"(d[12]),"+f"(d[13]),"+f"(d[14]),"+f"(d[15]),"+f"(d[16]),"+f"(d[17]),"+f"(d[18]),"+f"(d[19]),"+f"(d[20]),"+f"(d[21]),"+f"(d[22]),
      "+f"(d[23]),"+f"(d[24]),"+f"(d[25]),"+f"(d[26]),"+f"(d[27]),"+f"(d[28]),"+f"(d[29]),"+f"(d[30]),"+f"(d[31]),"+f"(d[32]),"+f"(d[33]),
      "+f"(d[34]),"+f"(d[35]),"+f"(d[36]),"+f"(d[37]),"+f"(d[38]),"+f"(d[39])
      : "r"(la), "r"(lb), "n"(TA), "n"(TB), "n"((SB + OA) >> 4), "n"(OB >> 4), "l"(ba), "l"(bb));
}

template <int TA, int TB, uint32_t OA, uint32_t OB>
__device__ __forceinline__ void mma80z(float (&d)[40], uint64_t ba, uint32_t la, uint64_t bb, uint32_t lb) {
  asm volatile(
      "{\n.reg .pred p;\n.reg .b64 da, db;\nsetp.ne.b32 p, 0, 0;\n"
      "mad.wide.u32 da, %40, 192, %46;\nadd.s64 da, da, %44;\nmad.wide.u32 db, %41, 1, %47;\nadd.s64 db, db, %45;\n"
      "wgmma.mma_async.sync.aligned.m64n80k16.f32.bf16.bf16 {"
      "%0,%1,%2,%3,%4,%5,%6,%7,%8,%9,%10,%11,%12,%13,%14,%15,%16,%17,%18,%19,%20,%21,%22,%23,%24,%25,%26,%27,%28,%29,%30,%31,%32,%33,%34,%35,%36,"
      "%37,%38,%39"
      "}, da, db, p, 1, 1, %42, %43;\n}\n"
      :
      "=f"(d[0]),"=f"(d[1]),"=f"(d[2]),"=f"(d[3]),"=f"(d[4]),"=f"(d[5]),"=f"(d[6]),"=f"(d[7]),"=f"(d[8]),"=f"(d[9]),"=f"(d[10]),"=f"(d[11]),
      "=f"(d[12]),"=f"(d[13]),"=f"(d[14]),"=f"(d[15]),"=f"(d[16]),"=f"(d[17]),"=f"(d[18]),"=f"(d[19]),"=f"(d[20]),"=f"(d[21]),"=f"(d[22]),
      "=f"(d[23]),"=f"(d[24]),"=f"(d[25]),"=f"(d[26]),"=f"(d[27]),"=f"(d[28]),"=f"(d[29]),"=f"(d[30]),"=f"(d[31]),"=f"(d[32]),"=f"(d[33]),
      "=f"(d[34]),"=f"(d[35]),"=f"(d[36]),"=f"(d[37]),"=f"(d[38]),"=f"(d[39])
      : "r"(la), "r"(lb), "n"(TA), "n"(TB), "n"((SB + OA) >> 4), "n"(OB >> 4), "l"(ba), "l"(bb));
}

template <int TA, int TB, uint32_t OA, uint32_t OB>
__device__ __forceinline__ void mma160r(float (&d)[80], uint64_t ba, uint32_t la, uint64_t bb, uint32_t lb, int sc) {
  asm volatile(
      "{\n.reg .pred p;\n.reg .b64 da, db;\nsetp.ne.b32 p, %88, 0;\n"
      "mad.wide.u32 da, %80, 3840, %86;\nadd.s64 da, da, %84;\nmad.wide.u32 db, %81, 3840, %87;\nadd.s64 db, db, %85;\n"
      "wgmma.mma_async.sync.aligned.m64n160k16.f32.bf16.bf16 {"
      "%0,%1,%2,%3,%4,%5,%6,%7,%8,%9,%10,%11,%12,%13,%14,%15,%16,%17,%18,%19,%20,%21,%22,%23,%24,%25,%26,%27,%28,%29,%30,%31,%32,%33,%34,%35,%36,"
      "%37,%38,%39,%40,%41,%42,%43,%44,%45,%46,%47,%48,%49,%50,%51,%52,%53,%54,%55,%56,%57,%58,%59,%60,%61,%62,%63,%64,%65,%66,%67,%68,%69,%70,%71,"
      "%72,%73,%74,%75,%76,%77,%78,%79"
      "}, da, db, p, 1, 1, %82, %83;\n}\n"
      :
      "+f"(d[0]),"+f"(d[1]),"+f"(d[2]),"+f"(d[3]),"+f"(d[4]),"+f"(d[5]),"+f"(d[6]),"+f"(d[7]),"+f"(d[8]),"+f"(d[9]),"+f"(d[10]),"+f"(d[11]),
      "+f"(d[12]),"+f"(d[13]),"+f"(d[14]),"+f"(d[15]),"+f"(d[16]),"+f"(d[17]),"+f"(d[18]),"+f"(d[19]),"+f"(d[20]),"+f"(d[21]),"+f"(d[22]),
      "+f"(d[23]),"+f"(d[24]),"+f"(d[25]),"+f"(d[26]),"+f"(d[27]),"+f"(d[28]),"+f"(d[29]),"+f"(d[30]),"+f"(d[31]),"+f"(d[32]),"+f"(d[33]),
      "+f"(d[34]),"+f"(d[35]),"+f"(d[36]),"+f"(d[37]),"+f"(d[38]),"+f"(d[39]),"+f"(d[40]),"+f"(d[41]),"+f"(d[42]),"+f"(d[43]),"+f"(d[44]),
      "+f"(d[45]),"+f"(d[46]),"+f"(d[47]),"+f"(d[48]),"+f"(d[49]),"+f"(d[50]),"+f"(d[51]),"+f"(d[52]),"+f"(d[53]),"+f"(d[54]),"+f"(d[55]),
      "+f"(d[56]),"+f"(d[57]),"+f"(d[58]),"+f"(d[59]),"+f"(d[60]),"+f"(d[61]),"+f"(d[62]),"+f"(d[63]),"+f"(d[64]),"+f"(d[65]),"+f"(d[66]),
      "+f"(d[67]),"+f"(d[68]),"+f"(d[69]),"+f"(d[70]),"+f"(d[71]),"+f"(d[72]),"+f"(d[73]),"+f"(d[74]),"+f"(d[75]),"+f"(d[76]),"+f"(d[77]),
      "+f"(d[78]),"+f"(d[79])
      : "r"(la), "r"(lb), "n"(TA), "n"(TB), "n"((SB + OA) >> 4), "n"(OB >> 4), "l"(ba), "l"(bb), "r"(sc));
}

template <int TA, int TB, uint32_t OA, uint32_t OB>
__device__ __forceinline__ void mma80r(float (&d)[40], uint64_t ba, uint32_t la, uint64_t bb, uint32_t lb, int sc) {
  asm volatile(
      "{\n.reg .pred p;\n.reg .b64 da, db;\nsetp.ne.b32 p, %48, 0;\n"
      "mad.wide.u32 da, %40, 3840, %46;\nadd.s64 da, da, %44;\nmad.wide.u32 db, %41, 3840, %47;\nadd.s64 db, db, %45;\n"
      "wgmma.mma_async.sync.aligned.m64n80k16.f32.bf16.bf16 {"
      "%0,%1,%2,%3,%4,%5,%6,%7,%8,%9,%10,%11,%12,%13,%14,%15,%16,%17,%18,%19,%20,%21,%22,%23,%24,%25,%26,%27,%28,%29,%30,%31,%32,%33,%34,%35,%36,"
      "%37,%38,%39"
      "}, da, db, p, 1, 1, %42, %43;\n}\n"
      :
      "+f"(d[0]),"+f"(d[1]),"+f"(d[2]),"+f"(d[3]),"+f"(d[4]),"+f"(d[5]),"+f"(d[6]),"+f"(d[7]),"+f"(d[8]),"+f"(d[9]),"+f"(d[10]),"+f"(d[11]),
      "+f"(d[12]),"+f"(d[13]),"+f"(d[14]),"+f"(d[15]),"+f"(d[16]),"+f"(d[17]),"+f"(d[18]),"+f"(d[19]),"+f"(d[20]),"+f"(d[21]),"+f"(d[22]),
      "+f"(d[23]),"+f"(d[24]),"+f"(d[25]),"+f"(d[26]),"+f"(d[27]),"+f"(d[28]),"+f"(d[29]),"+f"(d[30]),"+f"(d[31]),"+f"(d[32]),"+f"(d[33]),
      "+f"(d[34]),"+f"(d[35]),"+f"(d[36]),"+f"(d[37]),"+f"(d[38]),"+f"(d[39])
      : "r"(la), "r"(lb), "n"(TA), "n"(TB), "n"((SB + OA) >> 4), "n"(OB >> 4), "l"(ba), "l"(bb), "r"(sc));
}

struct Ring { uint32_t o[NSLOT], m; };
__device__ __forceinline__ void ring_pos(const Ring& r, int i, uint32_t& slot8, uint32_t& ph) {
  slot8 = r.o[i % NSLOT];
  ph = r.m >> (i % (2 * NSLOT));
}
__device__ __forceinline__ void ring_advance(Ring& r, int n) {
  Ring t = r;
#pragma unroll
  for (int k = 0; k < NSLOT; k++) r.o[k] = t.o[(k + n) % NSLOT];
  r.m = ((t.m >> (n % (2 * NSLOT))) & 1023) * 1025;
}
__host__ __device__ constexpr int idxK(int j) { return j == 0 ? 10 : 9 + 2 * j; }
__host__ __device__ constexpr int idxV(int j) { return j == 7 ? 25 : 12 + 2 * j; }
__host__ __device__ constexpr int xs(int c) { return c % NSLOT; }

__device__ __forceinline__ int first_item(int cta) { return cta < N_OCTA ? (cta & 1) * 16 + (cta >> 1) : cta; }
__device__ __forceinline__ int start_delay(int cta) {
  return max(0, ((cta - N_OCTA) | (STAG_G - 1)) - STAG_A0) * STAG_SLOPE;
}
__device__ __forceinline__ char* o_slot(int item) {
  return (char*)g_o + (size_t)(item < OFRESH ? item % ORING : item - OFRESH + ORING) * O_ITEM_BYTES;
}
__device__ __forceinline__ int next_item(uint32_t a = NEXT_ITEM) {
  int v;
  asm volatile("ld.shared.s32 %0, [%1];" : "=r"(v) : "r"(a) : "memory");
  return __shfl_sync(0xffffffffu, v, 0);
}

template <int W, bool ACC>
__device__ __forceinline__ void mma_main(uint64_t ds, float (&d)[80], uint32_t la, uint32_t baddr) {
  const uint32_t lb = baddr >> 4;
  if (ACC) mma160<1, 0, W * 16384, 0>(d, ds, la, ds, lb); else mma160z<1, 0, W * 16384, 0>(d, ds, la, ds, lb);
  mma160<1, 0, W * 16384 + 1 * 2048, 1 * 32>(d, ds, la, ds, lb);
  mma160<1, 0, W * 16384 + 2 * 2048, 2 * 32>(d, ds, la, ds, lb);
  mma160<1, 0, W * 16384 + 3 * 2048, 3 * 32>(d, ds, la, ds, lb);
}
template <int W, bool ACC>
__device__ __forceinline__ void mma_mid(uint64_t ds, float (&d)[40], uint32_t la, uint32_t baddr) {
  const uint32_t lb = baddr >> 4;
  if (ACC) mma80<1, 0, 8192, W * 10240>(d, ds, la, ds, lb); else mma80z<1, 0, 8192, W * 10240>(d, ds, la, ds, lb);
  mma80<1, 0, 8192 + 1 * 2048, W * 10240 + 1 * 32>(d, ds, la, ds, lb);
  mma80<1, 0, 8192 + 2 * 2048, W * 10240 + 2 * 32>(d, ds, la, ds, lb);
  mma80<1, 0, 8192 + 3 * 2048, W * 10240 + 3 * 32>(d, ds, la, ds, lb);
}
template <int W, bool ACC>
__device__ __forceinline__ void mma_both(uint64_t ds, float (&dm)[80], float (&dh)[40], uint32_t la, uint32_t baddr) {
  mma_mid<W, ACC>(ds, dh, la, baddr);
  mma_main<W, ACC>(ds, dm, la, baddr);
}
template <int KB, bool ACC>
__device__ __forceinline__ void s_mma(uint64_t ds, float (&sacc)[80], uint32_t la) {
  const uint32_t lb = (SB + OFF_B) >> 4;
  if (ACC) mma160<0, 0, KB * 8192, KB * B_SLOT>(sacc, ds, la, ds, lb); else mma160z<0, 0, KB * 8192, KB * B_SLOT>(sacc, ds, la, ds, lb);
  mma160<0, 0, KB * 8192 + 32, KB * B_SLOT + 32>(sacc, ds, la, ds, lb);
  mma160<0, 0, KB * 8192 + 64, KB * B_SLOT + 64>(sacc, ds, la, ds, lb);
  mma160<0, 0, KB * 8192 + 96, KB * B_SLOT + 96>(sacc, ds, la, ds, lb);
}
template <int N>
__device__ __forceinline__ void store_scaled(uint32_t addr, const float (&d)[N], float sc) {
#pragma unroll
  for (int J = 0; J < N / 8; J++)
    stsm_t(addr + J * 2048, pack2(d[8 * J] * sc, d[8 * J + 1] * sc), pack2(d[8 * J + 2] * sc, d[8 * J + 3] * sc),
           pack2(d[8 * J + 4] * sc, d[8 * J + 5] * sc), pack2(d[8 * J + 6] * sc, d[8 * J + 7] * sc));
}
__device__ __forceinline__ float4 lds_f4(uint32_t a) {
  float4 v;
  asm volatile("ld.shared.v4.f32 {%0,%1,%2,%3}, [%4];" : "=f"(v.x), "=f"(v.y), "=f"(v.z), "=f"(v.w) : "r"(a) : "memory");
  return v;
}
__device__ __forceinline__ void norm_pack(uint32_t* p, const float* d, const float4& i) {
  p[0] = pack2(d[0] * i.x, d[1] * i.y); p[1] = pack2(d[4] * i.z, d[5] * i.w);
  p[2] = pack2(d[2] * i.x, d[3] * i.y); p[3] = pack2(d[6] * i.z, d[7] * i.w);
  asm volatile("" : "+r"(p[0]), "+r"(p[1]), "+r"(p[2]), "+r"(p[3])::"memory");
}
template <int W>
__device__ __forceinline__ void pack_first(uint32_t (&pk)[60], const float (&om)[80], const float (&oh)[40], uint32_t laddr) {
  float4 n0 = lds_f4(laddr + W * 80), n1 = lds_f4(laddr + W * 80 + 16);
#pragma unroll
  for (int J = 0; J < 5; J++) {
    const float4 i = n0;
    n0 = n1;
    if (J + 2 < 5) n1 = lds_f4(laddr + W * 80 + (J + 2) * 16);
    norm_pack(&pk[20 + 4 * J], &om[8 * (5 * W + J)], i);
    norm_pack(&pk[4 * J], &oh[8 * J], i);
  }
}
template <int W, int J0, int J1>
__device__ __forceinline__ void pack_second(uint32_t (&pk)[60], const float (&om)[80], uint32_t laddr) {
  float4 n[J1 - J0];
#pragma unroll
  for (int J = J0; J < J1; J++) n[J - J0] = lds_f4(laddr + (1 - W) * 80 + J * 16);
#pragma unroll
  for (int J = J0; J < J1; J++) norm_pack(&pk[40 + 4 * J], &om[8 * (5 * (1 - W) + J)], n[J - J0]);
}
__device__ __forceinline__ char* o_ptr(int item) {
  const uint32_t t = tid_x();
  return o_slot(item) + ((t & 96) * 16 + (t & 28) * 8 + ((((t >> 1) ^ (t >> 4)) & 1) << 4) + (t & 1) * 8);
}
template <int W, int G0, int G1>
__device__ __forceinline__ void store_groups(char* op, const uint32_t (&pk)[60], uint32_t on) {
#pragma unroll
  for (int G = G0; G < G1; G++) {
    const int off = (G < 5 ? 1 : 2 * W) * B_SLOT + (5 * (G < 10 ? W : 1 - W) + G % 5) * 2048;
    asm volatile("{\n.reg .pred p;\nsetp.ne.u32 p, %5, 0;\n@p st.global.v2.b32 [%0], {%1, %2};\n@p st.global.v2.b32 [%0+256], {%3, %4};\n}\n"
                 ::"l"(op + off), "r"(pk[4 * G]), "r"(pk[4 * G + 1]), "r"(pk[4 * G + 2]), "r"(pk[4 * G + 3]), "r"(on) : "memory");
  }
}
__device__ __forceinline__ void publish_generic(uint32_t bar, int lane) {
  __syncwarp();
  mbar_arrive_if0(bar, lane);
}
__device__ __forceinline__ void publish(uint32_t bar, int lane) {
  proxy_fence();
  __syncwarp();
  mbar_arrive_if0(bar, lane);
}

#define MMA_BEGIN()                                                 \
  asm volatile("add.s64 %0, %0, %1;" : "+l"(ds) : "l"(zero));       \
  wg_fence()
#define A_ADDR(s) (SB + OFF_A + (s) * A_SLOT)
#define B_ADDR(s) (SB + OFF_B + (s) * B_SLOT)
#define WAIT_CHUNK(c, ro, sA)                \
  uint32_t sA;                               \
  {                                          \
    uint32_t pA_;                            \
    ring_pos(ring, (ro) + (c), sA, pA_);     \
    mbar_wait(bud, BAR_FULLA + sA, pA_); \
  }
#define RELEASE_CHUNK(c, sA)                                  \
  mbar_arrive_if0(BAR_EMPTYA + sA, tid);                \
  if ((c) < NSLOT) mbar_arrive_if0(BAR_EMPTYB + xs(c) * 8, tid);

template <int W>
__device__ __forceinline__ int attn_consumer(uint64_t ds, const uint64_t zero, int item) {
  int bud = WAIT_BUDGET;
  const int tid = threadIdx.x & 127, lane = tid & 31;
  const uint32_t laddr = SB + OFF_L + (lane & 3) * 160;
  float om[80], oh[40], sacc[80];
  uint32_t pk[60];
#pragma unroll
  for (int i = 0; i < 40; i++) pk[i] = 0;
  zero_regs(om);
  Ring ring{{0u, 8u, 16u, 24u, 32u}, 0x3E0u * 1025};
  uint32_t par = 0;
  int prev = 0;
  const float qscale = 0.07216878364870322f * 1.4426950408889634f;
  constexpr uint32_t pown = B_ADDR(3 + W), poth = B_ADDR(4 - W);
  TL(0); TLG(62);
  {
    WAIT_CHUNK(0, 0, s0)
    MMA_BEGIN();
    mma_both<W, false>(ds, sacc, oh, s0, B_ADDR(xs(0)));
    wg_commit();
    WAIT_CHUNK(1, 0, s1)
    MMA_BEGIN();
    mma_both<W, true>(ds, sacc, oh, s1, B_ADDR(xs(1)));
    wg_commit();
    wg_wait<1>();
    RELEASE_CHUNK(0, s0)
  }
#pragma unroll 1
  for (int it = 0;; it++) {
    char* op = o_ptr(prev);
#pragma unroll
    for (int c = 2; c < 8 - W; c++) {
      WAIT_CHUNK(c, 0, sA)
      TL(40 + c);
      MMA_BEGIN();
      mma_both<W, true>(ds, sacc, oh, sA, B_ADDR(xs(c)));
      wg_commit();
      wg_wait<1>();
      uint32_t sP, pP;
      ring_pos(ring, c - 1, sP, pP);
      RELEASE_CHUNK(c - 1, sP)
      constexpr int NG = 3;
      if (c == 2) { pack_second<W, 0, 1>(pk, om, laddr); store_groups<W, 0 * NG, 1 * NG>(op, pk, it); }
      if (c == 3) { pack_second<W, 1, 2>(pk, om, laddr); store_groups<W, 1 * NG, 2 * NG>(op, pk, it); }
      if (c == 4) { pack_second<W, 2, 3>(pk, om, laddr); store_groups<W, 2 * NG, 3 * NG>(op, pk, it); }
      if (c == 5) { pack_second<W, 3, 4>(pk, om, laddr); store_groups<W, 3 * NG, 4 * NG>(op, pk, it); }
      if (c == 6) {
        pack_second<W, 4, 5>(pk, om, laddr);
        if (W == 1) {
          wg_wait<0>();
          RELEASE_CHUNK(6, sA)
          mbar_arrive_if0(BAR_XDONE, tid);
        }
        store_groups<W, 4 * NG, 15>(op, pk, it);
        __syncwarp();
        mbar_arrive_if0(BAR_OFULL, lane | (it == 0));
      }
    }
    const uint32_t t_ = tid_x(), st_off = ((t_ & 7) + ((t_ & 16) >> 1)) * 128 + (((((t_ & 96) >> 4) + ((t_ >> 3) & 1)) ^ (t_ & 7)) << 4);
    uint32_t sK0, pK0, s7, p7;
    ring_pos(ring, idxK(W), sK0, pK0);
    ring_pos(ring, 7, s7, p7);
    if (W == 1) mbar_wait(bud, BAR_FULLA + s7, p7);
    WAIT_CHUNK(8, 0, s8)
    if (W == 0) {
      MMA_BEGIN();
      mma_both<W, true>(ds, sacc, oh, s8, B_ADDR(xs(8)));
      wg_commit();
      wg_wait<1>();
      RELEASE_CHUNK(7, s7)
    }
    WAIT_CHUNK(9, 0, s9)
    TL(48);
    if (W == 0) {
      MMA_BEGIN();
      mma_mid<W, true>(ds, oh, s9, B_ADDR(xs(9)));
      wg_commit();
      mma_main<W, true>(ds, sacc, s9, B_ADDR(xs(9)));
      wg_commit();
      bar_arrive(5, 256);
      TL(49);
      wg_wait<1>();
      reg_fence(oh);
      mbar_wait(bud, BAR_XDONE, par);
      store_scaled(B_ADDR(1) + st_off, oh, qscale);
    } else {
      bar_sync(5, 256);
      MMA_BEGIN();
      mma_mid<W, true>(ds, oh, s7, B_ADDR(xs(7)));
      mma_mid<W, true>(ds, oh, s8, B_ADDR(xs(8)));
      mma_mid<W, true>(ds, oh, s9, B_ADDR(xs(9)));
      wg_commit();
      mma_main<W, true>(ds, sacc, s7, B_ADDR(xs(7)));
      wg_commit();
      mma_main<W, true>(ds, sacc, s8, B_ADDR(xs(8)));
      wg_commit();
      wg_wait<2>();
      reg_fence(oh);
      store_scaled(B_ADDR(1) + 10240 + st_off, oh, qscale);
      MMA_BEGIN();
      mma_main<W, true>(ds, sacc, s9, B_ADDR(xs(9)));
      wg_commit();
      bar_arrive(8, 256);
      TL(49);
      wg_wait<2>();
      RELEASE_CHUNK(7, s7)
      publish(BAR_QH, lane);
    }
    wg_wait<0>();
    reg_fence(sacc);
    TL(1);
    RELEASE_CHUNK(8, s8)
    RELEASE_CHUNK(9, s9)
    store_scaled(B_ADDR(2 * W) + st_off, sacc, qscale);
    if (W == 1) publish(BAR_QM, lane); else proxy_fence();
    TL(2);
    uint32_t sK = sK0, sV1 = 0;
    if (W == 0) {
      zero_regs(om); zero_regs(oh);
      reg_fence(om); reg_fence(oh);
      mbar_wait(bud, BAR_FULLA + sK0, pK0);
      bar_sync(8, 256);
      MMA_BEGIN();
      s_mma<0, false>(ds, sacc, sK);
      mbar_wait(bud, BAR_QH, par);
      TL(3);
      MMA_BEGIN();
      s_mma<1, true>(ds, sacc, sK);
      mbar_wait(bud, BAR_QM, par);
      TL(5);
      MMA_BEGIN();
      s_mma<2, true>(ds, sacc, sK);
      wg_commit();
      wg_commit();
      bar_arrive(2, 256);
    } else {
      uint32_t pV1;
      ring_pos(ring, idxV(0), sV1, pV1);
      mbar_wait(bud, BAR_FULLA + sK, pK0);
      bar_sync(2, 256);
      MMA_BEGIN();
      s_mma<0, false>(ds, sacc, sK);
      s_mma<1, true>(ds, sacc, sK);
      s_mma<2, true>(ds, sacc, sK);
      wg_commit();
      TL(6);
      mbar_wait(bud, BAR_FULLA + sV1, pV1);
      mbar_wait(bud, BAR_PFULL, 0);
      TL(7);
      MMA_BEGIN();
      mma_both<W, false>(ds, om, oh, sV1, poth);
      wg_commit();
      bar_arrive(1, 256);
    }
#pragma unroll 1
    for (int jj = 0;; jj++) {
      wg_wait<1>();
      reg_fence(sacc);
      TL(8 + jj * 7);
      mbar_arrive2_if0(BAR_EMPTYA + sK, tid);
      mbar_arrive_if0(BAR_EMPTYB + W * 8 + tid * 8, (tid >= 3 - W) | (jj != 3));
#pragma unroll
      for (int J = 0; J < 10; J++) {
        stsm_t(pown + st_off + J * 2048, pack2(ex2(sacc[8 * J]), ex2(sacc[8 * J + 1])), pack2(ex2(sacc[8 * J + 2]), ex2(sacc[8 * J + 3])),
               pack2(ex2(sacc[8 * J + 4]), ex2(sacc[8 * J + 5])), pack2(ex2(sacc[8 * J + 6]), ex2(sacc[8 * J + 7])));
        if (W == 1 && J == 5) publish_generic(BAR_PMID, lane | (jj != 3));
        if (J == 4) {
          wg_wait<0>();
          mbar_arrive_if0(BAR_EMPTYA + sV1, tid | (W == 0 && jj == 0));
        }
      }
      publish(BAR_PFULL + W * 8, lane);
      TL(10 + jj * 7);
      if (jj == 3) break;
      uint32_t sV, pV, pK, pV1;
      ring_pos(ring, idxV(W), sV, pV);
      ring_pos(ring, idxV(W) + 1, sK, pK);
      ring_pos(ring, idxV(W) + 2, sV1, pV1);
      mbar_wait(bud, BAR_FULLA + sV, pV);
      bar_sync(1 + W, 256);
      MMA_BEGIN();
      mma_both<W, true>(ds, om, oh, sV, pown);
      wg_commit();
      mbar_wait(bud, BAR_FULLA + sK, pK);
      TL(11 + jj * 7);
      MMA_BEGIN();
      s_mma<0, false>(ds, sacc, sK);
      if (W == 1) wg_commit();
      s_mma<1, true>(ds, sacc, sK);
      wg_commit();
      wg_wait<1 + W>();
      mbar_arrive_if0(BAR_EMPTYA + sV, tid);
      if (W == 1) {
        wg_wait<1>();
        mbar_arrive_if0(BAR_EMPTYB, tid | (jj != 2));
      }
      MMA_BEGIN();
      s_mma<2, true>(ds, sacc, sK);
      wg_commit();
      TL(13 + jj * 7);
      mbar_wait(bud, BAR_FULLA + sV1, pV1);
      mbar_wait(bud, BAR_PFREE + W * 8, jj & 1);
      mbar_wait(bud, BAR_PFULL + (1 - W) * 8, (jj + W) & 1);
      TL(14 + jj * 7);
      MMA_BEGIN();
      mma_both<W, true>(ds, om, oh, sV1, poth);
      wg_commit();
      bar_arrive(2 - W, 256);
      ring_advance(ring, 4);
    }
    uint32_t sV6, pV6, sV7, pV7;
    ring_pos(ring, idxV(6) - 12, sV6, pV6);
    ring_pos(ring, idxV(7) - 12, sV7, pV7);
    prev = item;
    mbar_wait(bud, BAR_FULLA + (W == 0 ? sV6 : sV7), W == 0 ? pV6 : pV7);
    if (!DEBUG_TIMEOUT) item = next_item();
    bar_sync(W == 0 ? 1 : 6, 256);
    if (DEBUG_TIMEOUT) item = next_item(NEXT_ITEM + 4);
    if (item >= NITEMS) {
      MMA_BEGIN();
      if (W == 0) {
        mma_both<0, true>(ds, om, oh, sV6, pown);
        wg_commit();
        mbar_wait(bud, BAR_FULLA + sV7, pV7);
        mbar_wait(bud, BAR_PFULL + 8, 1);
        MMA_BEGIN();
      }
      mma_both<W, true>(ds, om, oh, sV7, B_ADDR(4));
      wg_commit();
      if (W == 0) bar_arrive(6, 256);
      TL(32);
      wg_wait<0>();
      reg_fence(om); reg_fence(oh);
      TL(33);
      mbar_wait(bud, BAR_LFULL, par);
      mbar_arrive_if0(BAR_FREE, tid);
      TL(34);
      pack_first<W>(pk, om, oh, laddr);
      op = o_ptr(prev);
      store_groups<W, 0, 10>(op, pk, 1);
      pack_second<W, 0, 5>(pk, om, laddr);
      store_groups<W, 10, 15>(op, pk, 1);
      publish_generic(BAR_OFULL, lane);
      TL(35); TLG(63);
      TL_FLUSH();
      return item;
    }
    {
      MMA_BEGIN();
      mma_both<W, true>(ds, om, oh, W == 0 ? sV6 : sV7, pown);
      wg_commit();
      if (W == 0) mbar_wait(bud, BAR_FULLA + sV7, pV7);
      WAIT_CHUNK(0, 26 - 12, s0)
      TL(38);
      MMA_BEGIN();
      mma_main<W, false>(ds, sacc, s0, B_ADDR(xs(0)));
      wg_commit();
      if (W == 0) {
        wg_wait<1>();
        mbar_arrive_if0(BAR_EMPTYA + sV6, tid);
        mbar_wait(bud, BAR_PFULL + 8, 1);
        MMA_BEGIN();
        mma_both<0, true>(ds, om, oh, sV7, poth);
        wg_commit();
        bar_arrive(6, 256);
      }
      TL(32);
      WAIT_CHUNK(1, 26 - 12, s1)
      if (W == 0) wg_wait<0>(); else wg_wait<1>();
      reg_fence(om); reg_fence(oh);
      mbar_arrive_if0(BAR_EMPTYA + sV7, tid);
      TL(33);
      MMA_BEGIN();
      mma_main<W, true>(ds, sacc, s1, B_ADDR(xs(1)));
      wg_commit();
      mbar_wait(bud, BAR_LFULL, par);
      mbar_arrive_if0(BAR_EMPTYB + 24 + tid * 8, tid >= 2);
      TL(34);
      pack_first<W>(pk, om, oh, laddr);
      TL(36);
      MMA_BEGIN();
      mma_mid<W, false>(ds, oh, s0, B_ADDR(xs(0)));
      wg_commit();
      mma_mid<W, true>(ds, oh, s1, B_ADDR(xs(1)));
      wg_commit();
      TL(37);
      wg_wait<1>();
      RELEASE_CHUNK(0, s0)
      TL(35); TLG(63);
    }
    TL_FLUSH();
    TL(0); TLG(62);
    ring_advance(ring, 26 - 12);
    par ^= 1;
  }
}

__device__ __forceinline__ uint4 lds128(uint32_t a) {
  uint4 v;
  asm volatile("ld.shared.v4.b32 {%0,%1,%2,%3}, [%4];" : "=r"(v.x), "=r"(v.y), "=r"(v.z), "=r"(v.w) : "r"(a) : "memory");
  return v;
}
__device__ __forceinline__ void acc2(float& s, float& t, uint32_t w) {
  s += __uint_as_float(w << 16);
  t += __uint_as_float(w & 0xffff0000u);
}
__device__ __forceinline__ uint32_t badd2(uint32_t a, uint32_t b) { uint32_t r; asm("add.rn.bf16x2 %0, %1, %2;" : "=r"(r) : "r"(a), "r"(b)); return r; }
__device__ __forceinline__ void sum_unit(float& acc, uint32_t pb) {
  const uint4 v0 = lds128(pb), v1 = lds128(pb ^ 32), v2 = lds128(pb ^ 64), v3 = lds128(pb ^ 96);
  const uint32_t w0 = badd2(badd2(v0.x, v0.y), badd2(v0.z, v0.w));
  float s = acc + __uint_as_float(w0 << 16), t = __uint_as_float(w0 & 0xffff0000u);
  acc2(s, t, badd2(badd2(v1.x, v1.y), badd2(v1.z, v1.w)));
  acc2(s, t, badd2(badd2(v2.x, v2.y), badd2(v2.z, v2.w)));
  acc2(s, t, badd2(badd2(v3.x, v3.y), badd2(v3.z, v3.w)));
  acc = s + t;
}
__device__ __forceinline__ float bf_lo(uint32_t w) { return __uint_as_float(w << 16); }
__device__ __forceinline__ float bf_hi(uint32_t w) { return __uint_as_float(w & 0xffff0000u); }
__device__ __forceinline__ float bf_rn(float x) { return __bfloat162float(__float2bfloat16(x)); }
__device__ __forceinline__ void slow_item(const Params& p, int item, int hw) {
  const int blk = item >> 9, h = (item >> 4) & 31, b = item & 15;
#pragma unroll 1
  for (int n = hw; n < SQ; n += 3) {
    float q[6] = {0.f, 0.f, 0.f, 0.f, 0.f, 0.f};
    {
      const uint32_t* xr = (const uint32_t*)(p.xp[blk] + (size_t)(b * SQ + n) * DM);
      const uint32_t* wq = (const uint32_t*)(p.wqp[blk] + h * DH) + (tid_x() & 31);
#pragma unroll 2
      for (int k = 0; k < DM / 2; k++) {
        const uint32_t xv = xr[k];
#pragma unroll
        for (int i = 0; i < 3; i++) {
          const uint32_t w0 = wq[i * 32], w1 = wq[NH * DH / 2 + i * 32];
          q[2 * i] = fmaf(bf_lo(xv), bf_lo(w0), fmaf(bf_hi(xv), bf_lo(w1), q[2 * i]));
          q[2 * i + 1] = fmaf(bf_lo(xv), bf_hi(w0), fmaf(bf_hi(xv), bf_hi(w1), q[2 * i + 1]));
        }
        wq += NH * DH;
      }
    }
    const uint32_t q0 = pack2(q[0], q[1]), q1 = pack2(q[2], q[3]), q2 = pack2(q[4], q[5]);
    float o[6] = {0.f, 0.f, 0.f, 0.f, 0.f, 0.f}, m = -INFINITY, l = 0.f;
    const uint32_t* kg = (const uint32_t*)(p.kp[blk] + (size_t)(b * NH + h) * SK * DH) + (tid_x() & 31);
    const uint32_t* vg = (const uint32_t*)(p.vp[blk] + (size_t)(b * NH + h) * SK * DH) + (tid_x() & 31);
#pragma unroll 1
    for (int k = 0; k < SK; k++) {
      const uint32_t k0 = kg[0], k1 = kg[32], k2 = kg[64], v0 = vg[0], v1 = vg[32], v2 = vg[64];
      kg += DH / 2; vg += DH / 2;
      float sc = fmaf(bf_lo(q0), bf_lo(k0), bf_hi(q0) * bf_hi(k0));
      sc = fmaf(bf_lo(q1), bf_lo(k1), fmaf(bf_hi(q1), bf_hi(k1), sc));
      sc = fmaf(bf_lo(q2), bf_lo(k2), fmaf(bf_hi(q2), bf_hi(k2), sc));
#pragma unroll
      for (int d = 16; d; d >>= 1) sc += __shfl_xor_sync(0xffffffffu, sc, d);
      sc = bf_rn(bf_rn(sc) * 0.07216878364870322f);
      const float mn = fmaxf(m, sc), a = ex2((m - mn) * 1.4426950408889634f), pr = ex2((sc - mn) * 1.4426950408889634f);
      m = mn;
      l = fmaf(l, a, pr);
      o[0] = fmaf(o[0], a, pr * bf_lo(v0)); o[1] = fmaf(o[1], a, pr * bf_hi(v0));
      o[2] = fmaf(o[2], a, pr * bf_lo(v1)); o[3] = fmaf(o[3], a, pr * bf_hi(v1));
      o[4] = fmaf(o[4], a, pr * bf_lo(v2)); o[5] = fmaf(o[5], a, pr * bf_hi(v2));
    }
    float inv;
    asm("rcp.approx.ftz.f32 %0, %1;" : "=f"(inv) : "f"(l));
    const int lane = tid_x() & 31;
    const int r = n & 15, c = 4 * ((r & 7) >> 1) + 2 * (r >> 3) + (r & 1);
    char* on = o_slot(item) + (lane >> 2) * 256 + (lane & 3) * 64 + (n >> 4) * 2048 +
               (((c >> 3) ^ ((lane >> 1) & 1)) << 4) + (c & 7) * 2;
#pragma unroll
    for (int i = 0; i < 3; i++) {
      *(__nv_bfloat16*)(on + i * B_SLOT) = __float2bfloat16(o[2 * i] * inv);
      *(__nv_bfloat16*)(on + i * B_SLOT + 32) = __float2bfloat16(o[2 * i + 1] * inv);
    }
  }
}
__device__ __forceinline__ void attn_helper(const Params& p, int hw, int item, int epoch) {
  int bud = WAIT_BUDGET;
  if (hw == 2) {
    if (item == 0 && elect_one()) {
      *(volatile int*)&g_ticket = 0;
      asm volatile("red.release.gpu.global.add.s32 [%0], 1;" ::"l"(&g_go) : "memory");
    }
    __syncwarp();
    flag_wait(bud, &g_go, epoch + 1);
  }
  if (item < PF_N && hw < 2) {
    const char* g = (const char*)(hw ? p.vp[0] : p.kp[0]) + (size_t)(((item & 15) * NH + (item >> 4)) * SK) * DH * 2;
    const long long t0 = clock64();
#pragma unroll 1
    for (int i = 0; i < 32; i++) {
      while (clock64() - t0 < PF_WAIT + i * PF_GAP) __nanosleep(50);
      for (int k = 0; k < 6; k++) asm volatile("prefetch.global.L2 [%0];" ::"l"(g + i * 6144 + k * 1024 + (tid_x() & 31) * 32));
      __syncwarp();
    }
  }
#pragma unroll 1
  for (int it = 0; item < NITEMS; it++) {
    const uint32_t par = it & 1;
    int lane = tid_x() & 31;
    const int r = lane >> 1;
    const uint32_t a0 = B_ADDR(3) + (16 * hw + r) * 128 + (lane & 1) * 16 + ((r & 3) << 5);
    float acc[4] = {0.f, 0.f, 0.f, 0.f};
#pragma unroll 1
    for (int j = 0; j < 8; j++) {
      const uint32_t pb = a0 + (j & 1) * B_SLOT, bfull = BAR_PFULL + (j & 1) * 8, pfull = (j >> 1) & 1;
      mbar_wait(bud, j == 7 ? BAR_PMID : bfull, j == 7 ? par : pfull);
      sum_unit(acc[0], pb);
      sum_unit(acc[1], pb + 6144);
      if (j == 7) mbar_wait(bud, bfull, pfull);
      sum_unit(acc[2], pb + 2 * 6144);
      if (hw == 0) sum_unit(acc[3], pb + 3 * 6144);
      __syncwarp();
      mbar_arrive_if0(BAR_PFREE + (j & 1) * 8, lane);
      if (j == 5 && hw == 2) {
        if (lane == 0) TLP(60);
        if (item >= ORING && item < OFRESH) flag_wait(bud, &g_done[item - ORING], (epoch + 1) * 2);
        if (lane == 0) TLP(61);
      }
    }
    bool bad = false;
    const uint32_t la = SB + OFF_L + (((r & 7) >> 1) * 40 + 2 * (r >> 3) + (r & 1) + 4 * hw) * 4;
#pragma unroll
    for (int u = 0; u < 4; u++) {
      const float l = acc[u] + __shfl_xor_sync(0xffffffffu, acc[u], 1);
      if (u < 3 || hw == 0) {
        bad |= !(l >= 9.094947017729282e-13f && l <= 1.099511627776e12f);
        float inv;
        asm("rcp.approx.ftz.f32 %0, %1;" : "=f"(inv) : "f"(l));
        asm volatile("st.shared.f32 [%0], %1;" ::"r"(la + u * 48), "f"(inv) : "memory");
      }
    }
    publish_generic(BAR_LFULL, lane);
    if (lane == 0) TLP(40 + hw * 4);
    uint32_t anybad;
    asm volatile("{\n.reg .pred p, q;\nsetp.ne.u32 p, %1, 0;\nbarrier.red.or.pred q, 7, 96, p;\nselp.u32 %0, 1, 0, q;\n}\n"
                 : "=r"(anybad) : "r"((uint32_t)bad) : "memory");
    if (__any_sync(0xffffffffu, anybad)) {
      mbar_wait(bud, BAR_OFULL, par);
      slow_item(p, item, hw);
      bar_sync(7, 96);
    }
    if (hw == 1) {
      mbar_wait(bud, BAR_OFULL, par);
      if ((tid_x() & 31) == 0) {
        TLP(41 + hw * 4);
        asm volatile("red.release.gpu.global.add.s32 [%0], 1;" ::"l"(&g_ready[item]) : "memory");
        TLP(42 + hw * 4);
      }
      __syncwarp();
    }
    item = next_item();
  }
}

__device__ __forceinline__ int attn_producer(const Params& p, int item) {
  int bud = WAIT_BUDGET;
  uint32_t sa = 0, pa = 1;
  const uint64_t pol = evict_first_policy();
  const bool draws = item >= N_OCTA;
  const int delay = start_delay(item);
  {
    const long long t0 = clock64();
    while (clock64() - t0 < delay) __nanosleep(100);
  }
#pragma unroll 1
  for (int it = 0; item < NITEMS; it++) {
    const int blk = item >> 9, h = (item >> 4) & 31, b = item & 15;
    const int row0 = (b * NH + h) * SK;
    if (!(it | delay)) pa = 0;
#pragma unroll 1
    for (int c = (it | delay) ? 0 : NSLOT; c < 10; c++) {
      const uint32_t sx = c < NSLOT ? c : c - NSLOT;
      mbar_wait(bud, BAR_EMPTYA + sa * 8, pa);
      TLP(c);
      mbar_expect(BAR_FULLA + sa * 8, A_SLOT + B_SLOT);
      tma3d(A_ADDR(sa), &p.wq[blk], BAR_FULLA + sa * 8, 0, c * 64, h * 3);
      mbar_wait(bud, BAR_EMPTYB + sx * 8, c < NSLOT);
      TLP(10 + c);
      tma2d(B_ADDR(sx), &p.x[blk], BAR_FULLA + sa * 8, c * 64, b * SQ);
      if (++sa == NSLOT) { sa = 0; pa ^= 1; }
    }
#pragma unroll 1
    for (int i = 0; i < 16; i++) {
      const bool isK = (i == 0) || ((i & 1) && i < 15);
      const int j = i == 0 ? 0 : (i == 15 ? 7 : (isK ? (i + 1) >> 1 : (i - 2) >> 1));
      mbar_wait(bud, BAR_EMPTYA + sa * 8, pa);
      TLP(20 + i);
      mbar_expect(BAR_FULLA + sa * 8, A_SLOT);
      tma3d_hint(A_ADDR(sa), isK ? &p.k[blk] : &p.v[blk], BAR_FULLA + sa * 8, 0, row0 + j * 64, 0, pol);
      if (i == 12) {
        item = draws ? NCTA + atomicAdd(&g_ticket, 1) : NITEMS;
        asm volatile("st.shared.s32 [%0], %1;" ::"r"(NEXT_ITEM), "r"(item) : "memory");
      }
      if (++sa == NSLOT) { sa = 0; pa ^= 1; }
    }
  }
  return item;
}

struct OJob { int tile, part, c0, n; };
__device__ __forceinline__ OJob get_ojob(int cta, int last) {
  if (cta < N_OCTA) return OJob{cta, 0, 0, CHUNK1};
  const int u = last - NITEMS, part = 1 + (u >> 5), tile = part == 3 ? 95 - u : u & 31;
  const int c1 = CHUNK1, c2 = c1 + LEN1 - ((tile * LSLOPE1 + 16) >> 5), c3 = c2 + LEN2 - ((tile * LSLOPE2 + 16) >> 5);
  return OJob{tile, part, part == 1 ? c1 : part == 2 ? c2 : c3, part == 1 ? c2 - c1 + 1 : part == 2 ? c3 - c2 + 1 : part == 3 ? 189 - c3 + 1 : 0};
}
__device__ __forceinline__ int unperm(int c) { return 8 * ((c >> 1) & 1) + 4 * (c >> 3) + 2 * ((c >> 2) & 1) + (c & 1); }
__device__ __forceinline__ uint32_t first_stage(const OJob& job) { return job.part ? (uint32_t)(300 - job.n) % 3 : 0; }

__device__ __forceinline__ void oproj_consumer(const Params& p, const OJob job, const int W) {
  int bud = WAIT_BUDGET;
  const int tid = tid_x() & 127, lane = tid & 31, warp = tid >> 5;
  float a0[80], a1[80], ah[40];
  zero_regs(a0); zero_regs(a1); zero_regs(ah);
  const uint64_t dam = p.dsw + W * (3 * 8192 >> 4), dbh = p.dso + W * (10240 >> 4);
  int left = job.n, step = 0;
  uint32_t st = first_stage(job), ph = 0;
#pragma unroll 1
  while (left) {
    const int nc = left > 3 * NH ? 3 * NH : left;
    left -= nc;
#pragma unroll 1
    for (int c = 0; c < nc; c++) {
      mbar_wait(bud, BAR_GFULL + st * 8, (ph >> st) & 1);
      ph ^= 1 << st;
      bar_sync_if0(11, W | (c - max(nc - 2, 0)));
      wg_fence();
      const uint32_t la = st, lb = st;
#define O_STEP(ks, sc)                                                        \
  mma80r<1, 1, 2 * 8192 + ks * 2048, SB + O_AB + ks * 512>(ah, p.dsw, la, dbh, lb, sc);   \
  mma160r<1, 1, ks * 2048, SB + O_AB + ks * 512>(a0, dam, la, p.dso, lb, sc);             \
  mma160r<1, 1, 8192 + ks * 2048, SB + O_AB + ks * 512>(a1, dam, la, p.dso, lb, sc);
      O_STEP(0, c != 0) O_STEP(1, 1)
      wg_commit();
      wg_wait<1>();
      mbar_arrive_if0(BAR_GEMPTY + (st == 0 ? 2 : st - 1) * 8, tid | (c == 0));
      wg_fence();
      O_STEP(2, 1) O_STEP(3, 1)
#undef O_STEP
      wg_commit();
      if (++st == 3) {
        st = 0;
        asm volatile("{\n.reg .pred p;\nsetp.eq.u32 p, %1, 0;\n@p red.relaxed.gpu.global.add.s32 [%0], 1;\n}\n"
                     ::"l"(&g_done[(step < 2 ? step ^ (job.tile & 1) : step) * 16 + (job.tile >> 1)]), "r"(tid | job.part | W) : "memory");
        TLG(step);
        step++;
      }
    }
    if (W) bar_arrive(11, 256);
    wg_wait<0>();
    reg_fence(a0); reg_fence(a1); reg_fence(ah);
    mbar_arrive_if0(BAR_GEMPTY + (st - 1) * 8, tid | (st == 0));
    TLG(63);
    const int prow = (lane & 7) + 8 * (lane >> 4), qrow = left ? unperm(prow) : prow;
    const uint32_t sg = SB + O_OUT + qrow * 128 + (((2 * warp + ((lane >> 3) & 1)) ^ (qrow & 7)) << 4);
    if (W) bar_arrive(3, 256); else bar_arrive(9, 256);
    bar_sync_if0(3, W);
    store_scaled(sg + W * 3 * B_SLOT, a0, 1.0f);
    publish(BAR_GOUT + W * 24, lane);
    store_scaled(sg + W * 3 * B_SLOT + B_SLOT, a1, 1.0f);
    publish(BAR_GOUT + W * 24 + 8, lane);
    bar_sync_if0(9, W - 1);
    store_scaled(sg + 2 * B_SLOT + W * 10240, ah, 1.0f);
    publish(BAR_GOUT + 16, lane);
  }
  TL_FLUSH();
  TLG(0);
  float acc[7][8];
  uint32_t in[7], blk[7], oo[7];
#pragma unroll
  for (int i = 0; i < 7; i++) {
    const int e = min(i * 256 + W * 128 + tid, 1599), r = e / 40, cc = e % 40, R = job.part * 40 + r;
    in[i] = r * 128 + (((cc ^ r) & 7) << 4);
    blk[i] = cc >> 3;
    oo[i] = ((R & ~15) + unperm(R & 15)) * (2 * DM / 8) + cc;
    asm volatile("" : "+r"(oo[i]));
#pragma unroll
    for (int k = 0; k < 8; k++) acc[i][k] = 0.f;
  }
  bar_sync(10, 256);
#pragma unroll 1
  for (int q = 0; q < 4; q++) {
    if (q) mbar_wait(bud, BAR_GRED + (q - 1) * 8, 0);
    if (q == 3) TLG(1);
    const uint32_t base = q ? SB + (q - 1) * 25600 : SB + O_OUT + job.part * 5120, bs = q ? 5120 : B_SLOT;
    uint4 v[7];
#pragma unroll
    for (int i = 0; i < 7; i++) v[i] = lds128(base + blk[i] * bs + in[i]);
#pragma unroll
    for (int i = 0; i < 7; i++) {
      acc[i][0] += bf_lo(v[i].x); acc[i][1] += bf_hi(v[i].x); acc[i][2] += bf_lo(v[i].y); acc[i][3] += bf_hi(v[i].y);
      acc[i][4] += bf_lo(v[i].z); acc[i][5] += bf_hi(v[i].z); acc[i][6] += bf_lo(v[i].w); acc[i][7] += bf_hi(v[i].w);
    }
  }
  uint4* go = (uint4*)p.outp + (job.tile >> 1) * SQ * (2 * DM / 8) + DM / 8 + (job.tile & 1) * 40;
#pragma unroll
  for (int i = 0; i < 7; i++) {
    if (i * 256 + W * 128 + tid < 1600)
      go[oo[i]] = make_uint4(pack2(acc[i][0], acc[i][1]), pack2(acc[i][2], acc[i][3]), pack2(acc[i][4], acc[i][5]), pack2(acc[i][6], acc[i][7]));
  }
  TLG(2);
  TL_FLUSH();
}

__device__ __forceinline__ void oproj_producer(const Params& p, const OJob job, int target) {
  int bud = WAIT_BUDGET;
  const uint64_t polo = evict_first_policy();
  mbar_wait(bud, BAR_FREE, 0);
  uint32_t st = first_stage(job), ph = 7;
  int seen = -1;
#pragma unroll 1
  for (int i = 0; i < job.n; i++) {
    const int c = job.part ? (i == job.n - 1 ? 188 + job.part : job.c0 + i) : (i < 6 && (job.tile & 1) ? (i < 3 ? i + 3 : i - 3) : i), step = c / 3, kb = c - 3 * step;
    const int item = step * 16 + (job.tile >> 1);
    int v = target;
    if (step != seen) asm volatile("ld.acquire.gpu.global.s32 %0, [%1];" : "=r"(v) : "l"(&g_ready[item]) : "memory");
    const uint32_t dst = SB + st * O_STAGE, bar = BAR_GFULL + st * 8;
    const char* og = o_slot(item) + kb * B_SLOT;
    mbar_wait(bud, BAR_GEMPTY + st * 8, (ph >> st) & 1);
    ph ^= 1 << st;
    mbar_expect(bar, O_STAGE);
    tma3d(dst, &p.wo[step >> 5], bar, 0, (c - (step >> 5) * 3 * NH) * 64, (job.tile & 1) * 5);
    if (step != seen) {
      if (v - target < 0) flag_wait(bud, &g_ready[item], target);
      asm volatile("fence.proxy.async.global;" ::: "memory");
      seen = step;
    }
    bulk_load_hint(dst + O_AB, og, B_SLOT, bar, polo);
    if (++st == 3) st = 0;
  }
  mbar_wait(bud, BAR_GEMPTY, ph & 1);
  mbar_wait(bud, BAR_GEMPTY + 8, (ph >> 1) & 1);
  uint32_t todo = 15 & ~(1 << job.part), dst = SB, bar = BAR_GRED;
  while (todo) {
    int v0, v1, v2, v3;
    asm volatile("ld.acquire.gpu.global.v4.s32 {%0, %1, %2, %3}, [%4];" : "=r"(v0), "=r"(v1), "=r"(v2), "=r"(v3) : "l"(&g_pcnt[job.tile * 4]) : "memory");
    const uint32_t rdy = --bud > 0 ? (v0 - target >= 0) | (v1 - target >= 0) << 1 | (v2 - target >= 0) << 2 | (v3 - target >= 0) << 3 : 15;
    if (!(rdy & todo)) continue;
    asm volatile("fence.proxy.async.global;" ::: "memory");
#pragma unroll 1
    for (int q = 0; q < 4; q++) {
      if (!(((rdy & todo) >> q) & 1)) continue;
      TLE(4 + q);
      mbar_expect(bar, 25600);
      for (int k = 0; k < 5; k++)
        tma2d(dst + k * 5120, &p.part, bar, (job.tile & 1) * 320 + k * 64, q * NB * SQ + (job.tile >> 1) * SQ + job.part * 40);
      todo &= ~(1 << q);
      dst += 25600;
      bar += 8;
    }
  }
}

__device__ __forceinline__ void oproj_storer(const Params& p, const OJob job) {
  int bud = WAIT_BUDGET;
  const int col = (job.tile & 1) * 320, row = (job.tile >> 1) * SQ;
  if (job.part == 0) {
    for (int k = 0; k < 3; k++) {
      mbar_wait(bud, BAR_GOUT + k * 8, 0);
      tma_store2d(&p.out, SB + O_OUT + k * B_SLOT, col + k * 64, row);
    }
    asm volatile("cp.async.bulk.commit_group;" ::: "memory");
    asm volatile("cp.async.bulk.wait_group.read 0;" ::: "memory");
    mbar_arrive2_if0(BAR_GEMPTY + 16, 0);
    mbar_wait(bud, BAR_GFULL + 16, 0);
    for (int k = 3; k < 5; k++) {
      mbar_wait(bud, BAR_GOUT + k * 8, 0);
      tma_store2d(&p.out, SB + O_OUT + k * B_SLOT, col + k * 64, row);
      asm volatile("cp.async.bulk.commit_group;" ::: "memory");
      asm volatile("cp.async.bulk.wait_group.read 0;" ::: "memory");
      __nanosleep(1000);
    }
  }
#pragma unroll 1
  for (int i = 0; i < 5; i++) {
    const int k = (0x21043 >> (4 * i)) & 15;
    mbar_wait(bud, BAR_GOUT + k * 8, job.part == 0);
    if (i == 0) TLE(0);
    for (int q = 1; q < 4; q++) {
      const int sh = (job.part + q) & 3;
      tma_store2d(&p.part, SB + O_OUT + k * B_SLOT + sh * 5120, col + k * 64, job.part * NB * SQ + row + sh * 40);
    }
  }
  asm volatile("cp.async.bulk.commit_group;" ::: "memory");
  TLE(1);
  asm volatile("cp.async.bulk.wait_group 0;" ::: "memory");
  TLE(2);
  asm volatile("fence.proxy.async.global;" ::: "memory");
  asm volatile("red.release.gpu.global.add.s32 [%0], 1;" ::"l"(&g_pcnt[job.tile * 4 + job.part]) : "memory");
  TLE(3);
}

__global__ void __launch_bounds__(384, 1) fused_kernel(const __grid_constant__ Params p) {
  extern __shared__ __align__(1024) char smem_raw[];
  if ((smem_u32(smem_raw) & 0xFFFFFFu) != SB) return;
  const int cta = (((blockIdx.x / PERM_G) * PERM_M) % (NCTA / PERM_G)) * PERM_G + (blockIdx.x % PERM_G);
  const int warp = __shfl_sync(0xffffffffu, threadIdx.x >> 5, 0);
  if (threadIdx.x == 0) {
    for (int i = 0; i < NSLOT; i++) { mbar_init(BAR_FULLA + i * 8, 1); mbar_init(BAR_EMPTYA + i * 8, 2); mbar_init(BAR_EMPTYB + i * 8, 2); }
    proxy_fence();
    if (start_delay(cta) == 0) {
#pragma unroll 1
      for (int c = 0; c < NSLOT; c++) {
        mbar_expect(BAR_FULLA + c * 8, A_SLOT + B_SLOT);
        tma3d(A_ADDR(c), &p.wq[0], BAR_FULLA + c * 8, 0, c * 64, (first_item(cta) >> 4) * 3);
        tma2d(B_ADDR(c), &p.x[0], BAR_FULLA + c * 8, c * 64, (first_item(cta) & 15) * SQ);
      }
    }
  }
  if (threadIdx.x == 64) {
    mbar_init(BAR_XDONE, 1); mbar_init(BAR_QH, 4); mbar_init(BAR_QM, 4);
    mbar_init(BAR_PFULL, 4); mbar_init(BAR_PFULL + 8, 4); mbar_init(BAR_PFREE, 3); mbar_init(BAR_PFREE + 8, 3);
    mbar_init(BAR_LFULL, 3); mbar_init(BAR_PMID, 4); mbar_init(BAR_OFULL, 8);
  }
  if (threadIdx.x == 96) {
    for (int i = 0; i < O_NST; i++) { mbar_init(BAR_GFULL + i * 8, 1); mbar_init(BAR_GEMPTY + i * 8, 2); }
    for (int i = 0; i < 5; i++) mbar_init(BAR_GOUT + i * 8, i == 2 ? 8 : 4);
    mbar_init(BAR_GRED, 1); mbar_init(BAR_GRED + 8, 1); mbar_init(BAR_GRED + 16, 1); mbar_init(BAR_FREE, 2);
    proxy_fence();
  }
  __syncthreads();
  if (warp >= 8) {
    asm volatile("setmaxnreg.dec.sync.aligned.u32 40;");
    if (warp == 8) {
      if (elect_one()) {
        const OJob job = get_ojob(cta, attn_producer(p, first_item(cta)));
        const int epoch = *(volatile int*)&g_epoch[cta];
        *(volatile int*)&g_epoch[cta] = epoch + 1;
        if (job.n) oproj_producer(p, job, epoch + 1);
      }
    } else {
      const int epoch = __shfl_sync(0xffffffffu, *(volatile int*)&g_epoch[cta], 0);
      attn_helper(p, warp - 9, first_item(cta), epoch);
      if (warp == 9) {
        const OJob job = get_ojob(cta, next_item());
        if (job.n && elect_one()) oproj_storer(p, job);
      }
    }
  } else {
    asm volatile("setmaxnreg.inc.sync.aligned.u32 232;");
    const OJob job = get_ojob(cta, warp < 4 ? attn_consumer<0>(p.dsw, p.zero, first_item(cta)) : attn_consumer<1>(p.dsw, p.zero, first_item(cta)));
    if (job.n) oproj_consumer(p, job, warp >> 2);
  }
}

typedef CUresult (*EncodeFn)(CUtensorMap*, CUtensorMapDataType, cuuint32_t, void*, const cuuint64_t*, const cuuint64_t*, const cuuint32_t*,
                             const cuuint32_t*, CUtensorMapInterleave, CUtensorMapSwizzle, CUtensorMapL2promotion, CUtensorMapFloatOOBfill);

void make3d(EncodeFn enc, CUtensorMap* m, const void* ptr, uint64_t rows, uint64_t cols, uint32_t box_rows, uint32_t box_blocks,
            CUtensorMapL2promotion promo = CU_TENSOR_MAP_L2_PROMOTION_L2_128B) {
  cuuint64_t gd[3] = {64, rows, cols / 64};
  cuuint64_t gs[2] = {cols * 2, 128};
  cuuint32_t bd[3] = {64, box_rows, box_blocks}, es[3] = {1, 1, 1};
  enc(m, CU_TENSOR_MAP_DATA_TYPE_BFLOAT16, 3, (void*)ptr, gd, gs, bd, es, CU_TENSOR_MAP_INTERLEAVE_NONE, CU_TENSOR_MAP_SWIZZLE_128B,
      promo, CU_TENSOR_MAP_FLOAT_OOB_FILL_NONE);
}
void make2d(EncodeFn enc, CUtensorMap* m, const void* ptr, uint64_t rows, uint64_t cols, uint32_t box_rows) {
  cuuint64_t gd[2] = {cols, rows};
  cuuint64_t gs[1] = {cols * 2};
  cuuint32_t bd[2] = {64, box_rows}, es[2] = {1, 1};
  enc(m, CU_TENSOR_MAP_DATA_TYPE_BFLOAT16, 2, (void*)ptr, gd, gs, bd, es, CU_TENSOR_MAP_INTERLEAVE_NONE, CU_TENSOR_MAP_SWIZZLE_128B,
      CU_TENSOR_MAP_L2_PROMOTION_L2_128B, CU_TENSOR_MAP_FLOAT_OOB_FILL_NONE);
}

}

extern "C" void kernel_launch(void* const* d_in, const int* in_sizes, int n_in, void* d_out, int out_size) {
  static EncodeFn enc = nullptr;
  static void* part = nullptr;
  if (!enc) {
    cudaGetSymbolAddress(&part, g_part);
    cudaDriverEntryPointQueryResult qr;
    cudaGetDriverEntryPoint("cuTensorMapEncodeTiled", (void**)&enc, cudaEnableDefault, &qr);
    cudaFuncSetAttribute(fused_kernel, cudaFuncAttributeMaxDynamicSharedMemorySize, SMEM_BYTES);
  }
  Params p;
  for (int s = 0; s < 2; s++) {
    make2d(enc, &p.x[s], d_in[5 * s + 0], NB * SQ, DM, SQ);
    make3d(enc, &p.k[s], d_in[5 * s + 1], (uint64_t)NB * NH * SK, DH, 64, 3);
    make3d(enc, &p.v[s], d_in[5 * s + 2], (uint64_t)NB * NH * SK, DH, 64, 3);
    make3d(enc, &p.wq[s], d_in[5 * s + 3], DM, NH * DH, 64, 3);
    make3d(enc, &p.wo[s], d_in[5 * s + 4], NH * DH, DM, 64, 5);
    p.xp[s] = (const __nv_bfloat16*)d_in[5 * s + 0];
    p.wqp[s] = (const __nv_bfloat16*)d_in[5 * s + 3];
    p.kp[s] = (const __nv_bfloat16*)d_in[5 * s + 1];
    p.vp[s] = (const __nv_bfloat16*)d_in[5 * s + 2];
  }
  make2d(enc, &p.out, d_out, NB * SQ, 2 * DM, SQ);
  make2d(enc, &p.part, part, 4 * NB * SQ, DM, 40);
  p.outp = (__nv_bfloat16*)d_out;
  p.dsw = DESC_SW;
  p.dso = DESC_O;
  p.zero = 0;
  fused_kernel<<<NCTA, 384, SMEM_BYTES>>>(p);
}
```

```cpp
#include <cuda_runtime.h>
#include <cuda_bf16.h>
#include <cuda.h>
#include <stdint.h>

#define DEBUG_TIMEOUT 0

namespace {

constexpr int SQ = 160, DM = 640, NH = 32, SK = 512, DH = 192, NB = 16;
constexpr int NITEMS = 2 * NB * NH;
constexpr int NCTA = 132, N_OCTA = 32;
constexpr int ORING = 208, OFRESH = 880, CHUNK1 = 158, LEN1 = 18, LEN2 = 13, LSLOPE1 = 4, LSLOPE2 = 5;
constexpr int STAG_G = 4, PERM_G = 4, STAG_A0 = 19, STAG_SLOPE = 275, PERM_M = 20, PF_N = 32, PF_WAIT = 1500, PF_GAP = 300;
constexpr int OSLOTS = ORING + NITEMS - OFRESH;
static_assert(ORING % NB == 0 && OFRESH - ORING <= CHUNK1 / 3 * NB, "ring slots are only drained by the tile owners");
static_assert(CHUNK1 > 3 * NH + 3 && CHUNK1 + LEN1 + LEN2 <= 189 && LEN1 > LSLOPE1 && LEN2 > LSLOPE2, "helper ranges");
constexpr int A_SLOT = 24576, B_SLOT = 20480, NSLOT = 5;
constexpr int OFF_A = 0;
constexpr int OFF_B = NSLOT * A_SLOT;
constexpr int O_STAGE = 61440, O_AB = 40960, O_NST = 3;
constexpr int OFF_L = OFF_B + NSLOT * B_SLOT;
constexpr int OFF_BAR = OFF_L + 160 * 4;
constexpr int SMEM_BYTES = OFF_BAR + 512 + 768;
constexpr int O_OUT = 2 * O_STAGE;
static_assert(O_OUT == OFF_B && O_OUT + 5 * B_SLOT <= OFF_L, "smem layout");
constexpr uint32_t SB = 1024;
constexpr uint32_t BARS = SB + OFF_BAR;
constexpr uint32_t BAR_FULLA = BARS, BAR_EMPTYA = BARS + 40, BAR_PMID = BARS + 80, BAR_EMPTYB = BARS + 120, BAR_XDONE = BARS + 160,
                   BAR_QH = BARS + 168, BAR_QM = BARS + 96, BAR_PFULL = BARS + 184, BAR_PFREE = BARS + 200, BAR_LFULL = BARS + 216,
                   BAR_OFULL = BARS + 224, BAR_GFULL = BARS + 248, BAR_GEMPTY = BARS + 280, BAR_GOUT = BARS + 328, BAR_GRED = BARS + 368,
                   BAR_FREE = BARS + 240, NEXT_ITEM = BARS + 320;
constexpr int O_ITEM_BYTES = SQ * DH * 2;

struct alignas(64) Params {
  CUtensorMap x[2], wq[2], k[2], v[2], wo[2], out, part;
  uint64_t dsw, dso, zero;
  __nv_bfloat16* outp;
  const __nv_bfloat16 *xp[2], *wqp[2], *kp[2], *vp[2];
};

__device__ uint4 g_o[(size_t)OSLOTS * O_ITEM_BYTES / 16];
__device__ uint4 g_part[4 * NB * SQ * DM / 8];
__device__ __align__(16) int g_pcnt[4 * N_OCTA];
__device__ int g_ready[NITEMS];
__device__ int g_done[NITEMS];
__device__ int g_ticket;
__device__ int g_go;
__device__ int g_epoch[NCTA];

#define TLE(id)
#define TLP(id)
#define TLG(id)
#define TL(id)
#define TL_FLUSH()
__device__ __forceinline__ uint32_t smem_u32(const void* p) { return (uint32_t)__cvta_generic_to_shared(p); }
__device__ __forceinline__ void wg_fence() { asm volatile("wgmma.fence.sync.aligned;" ::: "memory"); }
__device__ __forceinline__ void wg_commit() { asm volatile("wgmma.commit_group.sync.aligned;" ::: "memory"); }
template <int N> __device__ __forceinline__ void wg_wait() { asm volatile("wgmma.wait_group.sync.aligned %0;" ::"n"(N) : "memory"); }
template <int N> __device__ __forceinline__ void reg_fence(float (&d)[N]) {
#pragma unroll
  for (int i = 0; i < N; i++) asm volatile("" : "+f"(d[i])::"memory");
}
template <int N> __device__ __forceinline__ void zero_regs(float (&d)[N]) {
#pragma unroll
  for (int i = 0; i < N; i++) d[i] = 0.f;
}
__device__ __forceinline__ void proxy_fence() { asm volatile("fence.proxy.async.shared::cta;" ::: "memory"); }
__device__ __forceinline__ void mbar_init(uint32_t bar, int cnt) { asm volatile("mbarrier.init.shared::cta.b64 [%0], %1;" ::"r"(bar), "r"(cnt) : "memory"); }
__device__ __forceinline__ void mbar_arrive_if0(uint32_t bar, uint32_t sel) {
  asm volatile("{\n.reg .pred p;\nsetp.eq.u32 p, %1, 0;\n@p mbarrier.arrive.shared::cta.b64 _, [%0];\n}\n" ::"r"(bar), "r"(sel) : "memory");
}
__device__ __forceinline__ void mbar_arrive2_if0(uint32_t bar, uint32_t sel) {
  asm volatile("{\n.reg .pred p;\nsetp.eq.u32 p, %1, 0;\n@p mbarrier.arrive.shared::cta.b64 _, [%0], 2;\n}\n" ::"r"(bar), "r"(sel) : "memory");
}
__device__ __forceinline__ void mbar_expect(uint32_t bar, uint32_t bytes) {
  asm volatile("mbarrier.arrive.expect_tx.shared::cta.b64 _, [%0], %1;" ::"r"(bar), "r"(bytes) : "memory");
}
__device__ __forceinline__ void mbar_wait(int& bud, uint32_t bar, uint32_t parity) {
  asm volatile(
      "{\n.reg .pred p;\n"
      "LW:\n"
      "mbarrier.try_wait.parity.shared::cta.b64 p, [%0], %1;\n"
      "@!p bra LW;\n}\n" ::"r"(bar), "r"(parity) : "memory");
}
constexpr int WAIT_BUDGET = 1 << 22;
__device__ __forceinline__ bool elect_one() {
  uint32_t p;
  asm volatile("{\n.reg .pred p;\nelect.sync _|p, 0xffffffff;\nselp.u32 %0, 1, 0, p;\n}\n" : "=r"(p));
  return p;
}
__device__ __forceinline__ void tma2d(uint32_t dst, const CUtensorMap* m, uint32_t bar, int c0, int c1) {
  asm volatile("cp.async.bulk.tensor.2d.shared::cluster.global.mbarrier::complete_tx::bytes [%0], [%1, {%3, %4}], [%2];"
               ::"r"(dst), "l"(m), "r"(bar), "r"(c0), "r"(c1) : "memory");
}
__device__ __forceinline__ void tma3d(uint32_t dst, const CUtensorMap* m, uint32_t bar, int c0, int c1, int c2) {
  asm volatile("cp.async.bulk.tensor.3d.shared::cluster.global.mbarrier::complete_tx::bytes [%0], [%1, {%3, %4, %5}], [%2];"
               ::"r"(dst), "l"(m), "r"(bar), "r"(c0), "r"(c1), "r"(c2) : "memory");
}
__device__ __forceinline__ void tma3d_hint(uint32_t dst, const CUtensorMap* m, uint32_t bar, int c0, int c1, int c2, uint64_t pol) {
  asm volatile("cp.async.bulk.tensor.3d.shared::cluster.global.mbarrier::complete_tx::bytes.L2::cache_hint [%0], [%1, {%3, %4, %5}], [%2], %6;"
               ::"r"(dst), "l"(m), "r"(bar), "r"(c0), "r"(c1), "r"(c2), "l"(pol) : "memory");
}
__device__ __forceinline__ void tma_store2d(const CUtensorMap* m, uint32_t src, int c0, int c1) {
  asm volatile("cp.async.bulk.tensor.2d.global.shared::cta.bulk_group [%0, {%2, %3}], [%1];" ::"l"(m), "r"(src), "r"(c0), "r"(c1) : "memory");
}
__device__ __forceinline__ void bar_sync(int id, int n) { asm volatile("bar.sync %0, %1;" ::"r"(id), "r"(n) : "memory"); }
__device__ __forceinline__ void bar_arrive(int id, int n) { asm volatile("bar.arrive %0, %1;" ::"r"(id), "r"(n) : "memory"); }
__device__ __forceinline__ void bar_sync_if0(int id, int sel) {
  asm volatile("{\n.reg .pred p;\nsetp.eq.s32 p, %1, 0;\n@p bar.sync %0, 256;\n}\n" ::"r"(id), "r"(sel) : "memory");
}
__device__ __forceinline__ float ex2(float x) { float y; asm("ex2.approx.ftz.f32 %0, %1;" : "=f"(y) : "f"(x)); return y; }
__device__ __forceinline__ uint32_t pack2(float lo, float hi) { uint32_t r; asm("cvt.rn.bf16x2.f32 %0, %1, %2;" : "=r"(r) : "f"(hi), "f"(lo)); return r; }
__device__ __forceinline__ void stsm_t(uint32_t a, uint32_t r0, uint32_t r1, uint32_t r2, uint32_t r3) {
  asm volatile("stmatrix.sync.aligned.m8n8.x4.trans.shared.b16 [%0], {%1,%2,%3,%4};" ::"r"(a), "r"(r0), "r"(r1), "r"(r2), "r"(r3) : "memory");
}
__device__ __forceinline__ uint64_t evict_first_policy() {
  uint64_t pol;
  asm volatile("createpolicy.fractional.L2::evict_first.b64 %0, 1.0;" : "=l"(pol));
  return pol;
}
__device__ __forceinline__ void bulk_load_hint(uint32_t dst, const void* src, uint32_t bytes, uint32_t bar, uint64_t pol) {
  asm volatile("cp.async.bulk.shared::cluster.global.mbarrier::complete_tx::bytes.L2::cache_hint [%0], [%1], %2, [%3], %4;"
               ::"r"(dst), "l"(src), "r"(bytes), "r"(bar), "l"(pol) : "memory");
}
__device__ __forceinline__ void flag_wait(int& bud, const int* p, int target) {
  while (true) {
    int v;
    asm volatile("ld.acquire.gpu.global.s32 %0, [%1];" : "=r"(v) : "l"(p) : "memory");
    if (v - target >= 0 || --bud <= 0) break;
    __nanosleep(64);
  }
}
constexpr uint64_t DESC_SW = 0x4000004000010000ull, DESC_O = 0xC000001000800000ull;
__device__ __forceinline__ uint32_t tid_x() { uint32_t t; asm volatile("mov.u32 %0, %tid.x;" : "=r"(t)); return t; }

template <int TA, int TB, uint32_t OA, uint32_t OB>
__device__ __forceinline__ void mma160(float (&d)[80], uint64_t ba, uint32_t la, uint64_t bb, uint32_t lb) {
  asm volatile(
      "{\n.reg .pred p;\n.reg .b64 da, db;\nsetp.eq.b32 p, 0, 0;\n"
      "mad.wide.u32 da, %80, 192, %86;\nadd.s64 da, da, %84;\nmad.wide.u32 db, %81, 1, %87;\nadd.s64 db, db, %85;\n"
      "wgmma.mma_async.sync.aligned.m64n160k16.f32.bf16.bf16 {"
      "%0,%1,%2,%3,%4,%5,%6,%7,%8,%9,%10,%11,%12,%13,%14,%15,%16,%17,%18,%19,%20,%21,%22,%23,%24,%25,%26,%27,%28,%29,%30,%31,%32,%33,%34,%35,%36,"
      "%37,%38,%39,%40,%41,%42,%43,%44,%45,%46,%47,%48,%49,%50,%51,%52,%53,%54,%55,%56,%57,%58,%59,%60,%61,%62,%63,%64,%65,%66,%67,%68,%69,%70,%71,"
      "%72,%73,%74,%75,%76,%77,%78,%79"
      "}, da, db, p, 1, 1, %82, %83;\n}\n"
      :
      "+f"(d[0]),"+f"(d[1]),"+f"(d[2]),"+f"(d[3]),"+f"(d[4]),"+f"(d[5]),"+f"(d[6]),"+f"(d[7]),"+f"(d[8]),"+f"(d[9]),"+f"(d[10]),"+f"(d[11]),
      "+f"(d[12]),"+f"(d[13]),"+f"(d[14]),"+f"(d[15]),"+f"(d[16]),"+f"(d[17]),"+f"(d[18]),"+f"(d[19]),"+f"(d[20]),"+f"(d[21]),"+f"(d[22]),
      "+f"(d[23]),"+f"(d[24]),"+f"(d[25]),"+f"(d[26]),"+f"(d[27]),"+f"(d[28]),"+f"(d[29]),"+f"(d[30]),"+f"(d[31]),"+f"(d[32]),"+f"(d[33]),
      "+f"(d[34]),"+f"(d[35]),"+f"(d[36]),"+f"(d[37]),"+f"(d[38]),"+f"(d[39]),"+f"(d[40]),"+f"(d[41]),"+f"(d[42]),"+f"(d[43]),"+f"(d[44]),
      "+f"(d[45]),"+f"(d[46]),"+f"(d[47]),"+f"(d[48]),"+f"(d[49]),"+f"(d[50]),"+f"(d[51]),"+f"(d[52]),"+f"(d[53]),"+f"(d[54]),"+f"(d[55]),
      "+f"(d[56]),"+f"(d[57]),"+f"(d[58]),"+f"(d[59]),"+f"(d[60]),"+f"(d[61]),"+f"(d[62]),"+f"(d[63]),"+f"(d[64]),"+f"(d[65]),"+f"(d[66]),
      "+f"(d[67]),"+f"(d[68]),"+f"(d[69]),"+f"(d[70]),"+f"(d[71]),"+f"(d[72]),"+f"(d[73]),"+f"(d[74]),"+f"(d[75]),"+f"(d[76]),"+f"(d[77]),
      "+f"(d[78]),"+f"(d[79])
      : "r"(la), "r"(lb), "n"(TA), "n"(TB), "n"((SB + OA) >> 4), "n"(OB >> 4), "l"(ba), "l"(bb));
}

template <int TA, int TB, uint32_t OA, uint32_t OB>
__device__ __forceinline__ void mma160z(float (&d)[80], uint64_t ba, uint32_t la, uint64_t bb, uint32_t lb) {
  asm volatile(
      "{\n.reg .pred p;\n.reg .b64 da, db;\nsetp.ne.b32 p, 0, 0;\n"
      "mad.wide.u32 da, %80, 192, %86;\nadd.s64 da, da, %84;\nmad.wide.u32 db, %81, 1, %87;\nadd.s64 db, db, %85;\n"
      "wgmma.mma_async.sync.aligned.m64n160k16.f32.bf16.bf16 {"
      "%0,%1,%2,%3,%4,%5,%6,%7,%8,%9,%10,%11,%12,%13,%14,%15,%16,%17,%18,%19,%20,%21,%22,%23,%24,%25,%26,%27,%28,%29,%30,%31,%32,%33,%34,%35,%36,"
      "%37,%38,%39,%40,%41,%42,%43,%44,%45,%46,%47,%48,%49,%50,%51,%52,%53,%54,%55,%56,%57,%58,%59,%60,%61,%62,%63,%64,%65,%66,%67,%68,%69,%70,%71,"
      "%72,%73,%74,%75,%76,%77,%78,%79"
      "}, da, db, p, 1, 1, %82, %83;\n}\n"
      :
      "=f"(d[0]),"=f"(d[1]),"=f"(d[2]),"=f"(d[3]),"=f"(d[4]),"=f"(d[5]),"=f"(d[6]),"=f"(d[7]),"=f"(d[8]),"=f"(d[9]),"=f"(d[10]),"=f"(d[11]),
      "=f"(d[12]),"=f"(d[13]),"=f"(d[14]),"=f"(d[15]),"=f"(d[16]),"=f"(d[17]),"=f"(d[18]),"=f"(d[19]),"=f"(d[20]),"=f"(d[21]),"=f"(d[22]),
      "=f"(d[23]),"=f"(d[24]),"=f"(d[25]),"=f"(d[26]),"=f"(d[27]),"=f"(d[28]),"=f"(d[29]),"=f"(d[30]),"=f"(d[31]),"=f"(d[32]),"=f"(d[33]),
      "=f"(d[34]),"=f"(d[35]),"=f"(d[36]),"=f"(d[37]),"=f"(d[38]),"=f"(d[39]),"=f"(d[40]),"=f"(d[41]),"=f"(d[42]),"=f"(d[43]),"=f"(d[44]),
      "=f"(d[45]),"=f"(d[46]),"=f"(d[47]),"=f"(d[48]),"=f"(d[49]),"=f"(d[50]),"=f"(d[51]),"=f"(d[52]),"=f"(d[53]),"=f"(d[54]),"=f"(d[55]),
      "=f"(d[56]),"=f"(d[57]),"=f"(d[58]),"=f"(d[59]),"=f"(d[60]),"=f"(d[61]),"=f"(d[62]),"=f"(d[63]),"=f"(d[64]),"=f"(d[65]),"=f"(d[66]),
      "=f"(d[67]),"=f"(d[68]),"=f"(d[69]),"=f"(d[70]),"=f"(d[71]),"=f"(d[72]),"=f"(d[73]),"=f"(d[74]),"=f"(d[75]),"=f"(d[76]),"=f"(d[77]),
      "=f"(d[78]),"=f"(d[79])
      : "r"(la), "r"(lb), "n"(TA), "n"(TB), "n"((SB + OA) >> 4), "n"(OB >> 4), "l"(ba), "l"(bb));
}

template <int TA, int TB, uint32_t OA, uint32_t OB>
__device__ __forceinline__ void mma80(float (&d)[40], uint64_t ba, uint32_t la, uint64_t bb, uint32_t lb) {
  asm volatile(
      "{\n.reg .pred p;\n.reg .b64 da, db;\nsetp.eq.b32 p, 0, 0;\n"
      "mad.wide.u32 da, %40, 192, %46;\nadd.s64 da, da, %44;\nmad.wide.u32 db, %41, 1, %47;\nadd.s64 db, db, %45;\n"
      "wgmma.mma_async.sync.aligned.m64n80k16.f32.bf16.bf16 {"
      "%0,%1,%2,%3,%4,%5,%6,%7,%8,%9,%10,%11,%12,%13,%14,%15,%16,%17,%18,%19,%20,%21,%22,%23,%24,%25,%26,%27,%28,%29,%30,%31,%32,%33,%34,%35,%36,"
      "%37,%38,%39"
      "}, da, db, p, 1, 1, %42, %43;\n}\n"
      :
      "+f"(d[0]),"+f"(d[1]),"+f"(d[2]),"+f"(d[3]),"+f"(d[4]),"+f"(d[5]),"+f"(d[6]),"+f"(d[7]),"+f"(d[8]),"+f"(d[9]),"+f"(d[10]),"+f"(d[11]),
      "+f"(d[12]),"+f"(d[13]),"+f"(d[14]),"+f"(d[15]),"+f"(d[16]),"+f"(d[17]),"+f"(d[18]),"+f"(d[19]),"+f"(d[20]),"+f"(d[21]),"+f"(d[22]),
      "+f"(d[23]),"+f"(d[24]),"+f"(d[25]),"+f"(d[26]),"+f"(d[27]),"+f"(d[28]),"+f"(d[29]),"+f"(d[30]),"+f"(d[31]),"+f"(d[32]),"+f"(d[33]),
      "+f"(d[34]),"+f"(d[35]),"+f"(d[36]),"+f"(d[37]),"+f"(d[38]),"+f"(d[39])
      : "r"(la), "r"(lb), "n"(TA), "n"(TB), "n"((SB + OA) >> 4), "n"(OB >> 4), "l"(ba), "l"(bb));
}

template <int TA, int TB, uint32_t OA, uint32_t OB>
__device__ __forceinline__ void mma80z(float (&d)[40], uint64_t ba, uint32_t la, uint64_t bb, uint32_t lb) {
  asm volatile(
      "{\n.reg .pred p;\n.reg .b64 da, db;\nsetp.ne.b32 p, 0, 0;\n"
      "mad.wide.u32 da, %40, 192, %46;\nadd.s64 da, da, %44;\nmad.wide.u32 db, %41, 1, %47;\nadd.s64 db, db, %45;\n"
      "wgmma.mma_async.sync.aligned.m64n80k16.f32.bf16.bf16 {"
      "%0,%1,%2,%3,%4,%5,%6,%7,%8,%9,%10,%11,%12,%13,%14,%15,%16,%17,%18,%19,%20,%21,%22,%23,%24,%25,%26,%27,%28,%29,%30,%31,%32,%33,%34,%35,%36,"
      "%37,%38,%39"
      "}, da, db, p, 1, 1, %42, %43;\n}\n"
      :
      "=f"(d[0]),"=f"(d[1]),"=f"(d[2]),"=f"(d[3]),"=f"(d[4]),"=f"(d[5]),"=f"(d[6]),"=f"(d[7]),"=f"(d[8]),"=f"(d[9]),"=f"(d[10]),"=f"(d[11]),
      "=f"(d[12]),"=f"(d[13]),"=f"(d[14]),"=f"(d[15]),"=f"(d[16]),"=f"(d[17]),"=f"(d[18]),"=f"(d[19]),"=f"(d[20]),"=f"(d[21]),"=f"(d[22]),
      "=f"(d[23]),"=f"(d[24]),"=f"(d[25]),"=f"(d[26]),"=f"(d[27]),"=f"(d[28]),"=f"(d[29]),"=f"(d[30]),"=f"(d[31]),"=f"(d[32]),"=f"(d[33]),
      "=f"(d[34]),"=f"(d[35]),"=f"(d[36]),"=f"(d[37]),"=f"(d[38]),"=f"(d[39])
      : "r"(la), "r"(lb), "n"(TA), "n"(TB), "n"((SB + OA) >> 4), "n"(OB >> 4), "l"(ba), "l"(bb));
}

template <int TA, int TB, uint32_t OA, uint32_t OB>
__device__ __forceinline__ void mma160r(float (&d)[80], uint64_t ba, uint32_t la, uint64_t bb, uint32_t lb, int sc) {
  asm volatile(
      "{\n.reg .pred p;\n.reg .b64 da, db;\nsetp.ne.b32 p, %88, 0;\n"
      "mad.wide.u32 da, %80, 3840, %86;\nadd.s64 da, da, %84;\nmad.wide.u32 db, %81, 3840, %87;\nadd.s64 db, db, %85;\n"
      "wgmma.mma_async.sync.aligned.m64n160k16.f32.bf16.bf16 {"
      "%0,%1,%2,%3,%4,%5,%6,%7,%8,%9,%10,%11,%12,%13,%14,%15,%16,%17,%18,%19,%20,%21,%22,%23,%24,%25,%26,%27,%28,%29,%30,%31,%32,%33,%34,%35,%36,"
      "%37,%38,%39,%40,%41,%42,%43,%44,%45,%46,%47,%48,%49,%50,%51,%52,%53,%54,%55,%56,%57,%58,%59,%60,%61,%62,%63,%64,%65,%66,%67,%68,%69,%70,%71,"
      "%72,%73,%74,%75,%76,%77,%78,%79"
      "}, da, db, p, 1, 1, %82, %83;\n}\n"
      :
      "+f"(d[0]),"+f"(d[1]),"+f"(d[2]),"+f"(d[3]),"+f"(d[4]),"+f"(d[5]),"+f"(d[6]),"+f"(d[7]),"+f"(d[8]),"+f"(d[9]),"+f"(d[10]),"+f"(d[11]),
      "+f"(d[12]),"+f"(d[13]),"+f"(d[14]),"+f"(d[15]),"+f"(d[16]),"+f"(d[17]),"+f"(d[18]),"+f"(d[19]),"+f"(d[20]),"+f"(d[21]),"+f"(d[22]),
      "+f"(d[23]),"+f"(d[24]),"+f"(d[25]),"+f"(d[26]),"+f"(d[27]),"+f"(d[28]),"+f"(d[29]),"+f"(d[30]),"+f"(d[31]),"+f"(d[32]),"+f"(d[33]),
      "+f"(d[34]),"+f"(d[35]),"+f"(d[36]),"+f"(d[37]),"+f"(d[38]),"+f"(d[39]),"+f"(d[40]),"+f"(d[41]),"+f"(d[42]),"+f"(d[43]),"+f"(d[44]),
      "+f"(d[45]),"+f"(d[46]),"+f"(d[47]),"+f"(d[48]),"+f"(d[49]),"+f"(d[50]),"+f"(d[51]),"+f"(d[52]),"+f"(d[53]),"+f"(d[54]),"+f"(d[55]),
      "+f"(d[56]),"+f"(d[57]),"+f"(d[58]),"+f"(d[59]),"+f"(d[60]),"+f"(d[61]),"+f"(d[62]),"+f"(d[63]),"+f"(d[64]),"+f"(d[65]),"+f"(d[66]),
      "+f"(d[67]),"+f"(d[68]),"+f"(d[69]),"+f"(d[70]),"+f"(d[71]),"+f"(d[72]),"+f"(d[73]),"+f"(d[74]),"+f"(d[75]),"+f"(d[76]),"+f"(d[77]),
      "+f"(d[78]),"+f"(d[79])
      : "r"(la), "r"(lb), "n"(TA), "n"(TB), "n"((SB + OA) >> 4), "n"(OB >> 4), "l"(ba), "l"(bb), "r"(sc));
}

template <int TA, int TB, uint32_t OA, uint32_t OB>
__device__ __forceinline__ void mma80r(float (&d)[40], uint64_t ba, uint32_t la, uint64_t bb, uint32_t lb, int sc) {
  asm volatile(
      "{\n.reg .pred p;\n.reg .b64 da, db;\nsetp.ne.b32 p, %48, 0;\n"
      "mad.wide.u32 da, %40, 3840, %46;\nadd.s64 da, da, %44;\nmad.wide.u32 db, %41, 3840, %47;\nadd.s64 db, db, %45;\n"
      "wgmma.mma_async.sync.aligned.m64n80k16.f32.bf16.bf16 {"
      "%0,%1,%2,%3,%4,%5,%6,%7,%8,%9,%10,%11,%12,%13,%14,%15,%16,%17,%18,%19,%20,%21,%22,%23,%24,%25,%26,%27,%28,%29,%30,%31,%32,%33,%34,%35,%36,"
      "%37,%38,%39"
      "}, da, db, p, 1, 1, %42, %43;\n}\n"
      :
      "+f"(d[0]),"+f"(d[1]),"+f"(d[2]),"+f"(d[3]),"+f"(d[4]),"+f"(d[5]),"+f"(d[6]),"+f"(d[7]),"+f"(d[8]),"+f"(d[9]),"+f"(d[10]),"+f"(d[11]),
      "+f"(d[12]),"+f"(d[13]),"+f"(d[14]),"+f"(d[15]),"+f"(d[16]),"+f"(d[17]),"+f"(d[18]),"+f"(d[19]),"+f"(d[20]),"+f"(d[21]),"+f"(d[22]),
      "+f"(d[23]),"+f"(d[24]),"+f"(d[25]),"+f"(d[26]),"+f"(d[27]),"+f"(d[28]),"+f"(d[29]),"+f"(d[30]),"+f"(d[31]),"+f"(d[32]),"+f"(d[33]),
      "+f"(d[34]),"+f"(d[35]),"+f"(d[36]),"+f"(d[37]),"+f"(d[38]),"+f"(d[39])
      : "r"(la), "r"(lb), "n"(TA), "n"(TB), "n"((SB + OA) >> 4), "n"(OB >> 4), "l"(ba), "l"(bb), "r"(sc));
}

struct Ring { uint32_t o[NSLOT], m; };
__device__ __forceinline__ void ring_pos(const Ring& r, int i, uint32_t& slot8, uint32_t& ph) {
  slot8 = r.o[i % NSLOT];
  ph = r.m >> (i % (2 * NSLOT));
}
__device__ __forceinline__ void ring_advance(Ring& r, int n) {
  Ring t = r;
#pragma unroll
  for (int k = 0; k < NSLOT; k++) r.o[k] = t.o[(k + n) % NSLOT];
  r.m = ((t.m >> (n % (2 * NSLOT))) & 1023) * 1025;
}
__host__ __device__ constexpr int idxK(int j) { return j == 0 ? 10 : 9 + 2 * j; }
__host__ __device__ constexpr int idxV(int j) { return j == 7 ? 25 : 12 + 2 * j; }
__host__ __device__ constexpr int xs(int c) { return c % NSLOT; }

__device__ __forceinline__ int first_item(int cta) { return cta < N_OCTA ? (cta & 1) * 16 + (cta >> 1) : cta; }
__device__ __forceinline__ int start_delay(int cta) {
  return max(0, ((cta - N_OCTA) | (STAG_G - 1)) - STAG_A0) * STAG_SLOPE;
}
__device__ __forceinline__ char* o_slot(int item) {
  return (char*)g_o + (size_t)(item < OFRESH ? item % ORING : item - OFRESH + ORING) * O_ITEM_BYTES;
}
__device__ __forceinline__ int next_item(uint32_t a = NEXT_ITEM) {
  int v;
  asm volatile("ld.shared.s32 %0, [%1];" : "=r"(v) : "r"(a) : "memory");
  return __shfl_sync(0xffffffffu, v, 0);
}

template <int W, bool ACC>
__device__ __forceinline__ void mma_main(uint64_t ds, float (&d)[80], uint32_t la, uint32_t baddr) {
  const uint32_t lb = baddr >> 4;
  if (ACC) mma160<1, 0, W * 16384, 0>(d, ds, la, ds, lb); else mma160z<1, 0, W * 16384, 0>(d, ds, la, ds, lb);
  mma160<1, 0, W * 16384 + 1 * 2048, 1 * 32>(d, ds, la, ds, lb);
  mma160<1, 0, W * 16384 + 2 * 2048, 2 * 32>(d, ds, la, ds, lb);
  mma160<1, 0, W * 16384 + 3 * 2048, 3 * 32>(d, ds, la, ds, lb);
}
template <int W, bool ACC>
__device__ __forceinline__ void mma_mid(uint64_t ds, float (&d)[40], uint32_t la, uint32_t baddr) {
  const uint32_t lb = baddr >> 4;
  if (ACC) mma80<1, 0, 8192, W * 10240>(d, ds, la, ds, lb); else mma80z<1, 0, 8192, W * 10240>(d, ds, la, ds, lb);
  mma80<1, 0, 8192 + 1 * 2048, W * 10240 + 1 * 32>(d, ds, la, ds, lb);
  mma80<1, 0, 8192 + 2 * 2048, W * 10240 + 2 * 32>(d, ds, la, ds, lb);
  mma80<1, 0, 8192 + 3 * 2048, W * 10240 + 3 * 32>(d, ds, la, ds, lb);
}
template <int W, bool ACC>
__device__ __forceinline__ void mma_both(uint64_t ds, float (&dm)[80], float (&dh)[40], uint32_t la, uint32_t baddr) {
  mma_mid<W, ACC>(ds, dh, la, baddr);
  mma_main<W, ACC>(ds, dm, la, baddr);
}
template <int KB, bool ACC>
__device__ __forceinline__ void s_mma(uint64_t ds, float (&sacc)[80], uint32_t la) {
  const uint32_t lb = (SB + OFF_B) >> 4;
  if (ACC) mma160<0, 0, KB * 8192, KB * B_SLOT>(sacc, ds, la, ds, lb); else mma160z<0, 0, KB * 8192, KB * B_SLOT>(sacc, ds, la, ds, lb);
  mma160<0, 0, KB * 8192 + 32, KB * B_SLOT + 32>(sacc, ds, la, ds, lb);
  mma160<0, 0, KB * 8192 + 64, KB * B_SLOT + 64>(sacc, ds, la, ds, lb);
  mma160<0, 0, KB * 8192 + 96, KB * B_SLOT + 96>(sacc, ds, la, ds, lb);
}
template <int N>
__device__ __forceinline__ void store_scaled(uint32_t addr, const float (&d)[N], float sc) {
#pragma unroll
  for (int J = 0; J < N / 8; J++)
    stsm_t(addr + J * 2048, pack2(d[8 * J] * sc, d[8 * J + 1] * sc), pack2(d[8 * J + 2] * sc, d[8 * J + 3] * sc),
           pack2(d[8 * J + 4] * sc, d[8 * J + 5] * sc), pack2(d[8 * J + 6] * sc, d[8 * J + 7] * sc));
}
__device__ __forceinline__ float4 lds_f4(uint32_t a) {
  float4 v;
  asm volatile("ld.shared.v4.f32 {%0,%1,%2,%3}, [%4];" : "=f"(v.x), "=f"(v.y), "=f"(v.z), "=f"(v.w) : "r"(a) : "memory");
  return v;
}
__device__ __forceinline__ void norm_pack(uint32_t* p, const float* d, const float4& i) {
  p[0] = pack2(d[0] * i.x, d[1] * i.y); p[1] = pack2(d[4] * i.z, d[5] * i.w);
  p[2] = pack2(d[2] * i.x, d[3] * i.y); p[3] = pack2(d[6] * i.z, d[7] * i.w);
  asm volatile("" : "+r"(p[0]), "+r"(p[1]), "+r"(p[2]), "+r"(p[3])::"memory");
}
template <int W>
__device__ __forceinline__ void pack_first(uint32_t (&pk)[60], const float (&om)[80], const float (&oh)[40], uint32_t laddr) {
  float4 n0 = lds_f4(laddr + W * 80), n1 = lds_f4(laddr + W * 80 + 16);
#pragma unroll
  for (int J = 0; J < 5; J++) {
    const float4 i = n0;
    n0 = n1;
    if (J + 2 < 5) n1 = lds_f4(laddr + W * 80 + (J + 2) * 16);
    norm_pack(&pk[20 + 4 * J], &om[8 * (5 * W + J)], i);
    norm_pack(&pk[4 * J], &oh[8 * J], i);
  }
}
template <int W, int J0, int J1>
__device__ __forceinline__ void pack_second(uint32_t (&pk)[60], const float (&om)[80], uint32_t laddr) {
  float4 n[J1 - J0];
#pragma unroll
  for (int J = J0; J < J1; J++) n[J - J0] = lds_f4(laddr + (1 - W) * 80 + J * 16);
#pragma unroll
  for (int J = J0; J < J1; J++) norm_pack(&pk[40 + 4 * J], &om[8 * (5 * (1 - W) + J)], n[J - J0]);
}
__device__ __forceinline__ char* o_ptr(int item) {
  const uint32_t t = tid_x();
  return o_slot(item) + ((t & 96) * 16 + (t & 28) * 8 + ((((t >> 1) ^ (t >> 4)) & 1) << 4) + (t & 1) * 8);
}
template <int W, int G0, int G1>
__device__ __forceinline__ void store_groups(char* op, const uint32_t (&pk)[60], uint32_t on) {
#pragma unroll
  for (int G = G0; G < G1; G++) {
    const int off = (G < 5 ? 1 : 2 * W) * B_SLOT + (5 * (G < 10 ? W : 1 - W) + G % 5) * 2048;
    asm volatile("{\n.reg .pred p;\nsetp.ne.u32 p, %5, 0;\n@p st.global.v2.b32 [%0], {%1, %2};\n@p st.global.v2.b32 [%0+256], {%3, %4};\n}\n"
                 ::"l"(op + off), "r"(pk[4 * G]), "r"(pk[4 * G + 1]), "r"(pk[4 * G + 2]), "r"(pk[4 * G + 3]), "r"(on) : "memory");
  }
}
__device__ __forceinline__ void publish_generic(uint32_t bar, int lane) {
  __syncwarp();
  mbar_arrive_if0(bar, lane);
}
__device__ __forceinline__ void publish(uint32_t bar, int lane) {
  proxy_fence();
  __syncwarp();
  mbar_arrive_if0(bar, lane);
}

#define MMA_BEGIN()                                                 \
  asm volatile("add.s64 %0, %0, %1;" : "+l"(ds) : "l"(zero));       \
  wg_fence()
#define A_ADDR(s) (SB + OFF_A + (s) * A_SLOT)
#define B_ADDR(s) (SB + OFF_B + (s) * B_SLOT)
#define WAIT_CHUNK(c, ro, sA)                \
  uint32_t sA;                               \
  {                                          \
    uint32_t pA_;                            \
    ring_pos(ring, (ro) + (c), sA, pA_);     \
    mbar_wait(bud, BAR_FULLA + sA, pA_); \
  }
#define RELEASE_CHUNK(c, sA)                                  \
  mbar_arrive_if0(BAR_EMPTYA + sA, tid);                \
  if ((c) < NSLOT) mbar_arrive_if0(BAR_EMPTYB + xs(c) * 8, tid);

template <int W>
__device__ __forceinline__ int attn_consumer(uint64_t ds, const uint64_t zero, int item) {
  int bud = WAIT_BUDGET;
  const int tid = threadIdx.x & 127, lane = tid & 31;
  const uint32_t laddr = SB + OFF_L + (lane & 3) * 160;
  float om[80], oh[40], sacc[80];
  uint32_t pk[60];
#pragma unroll
  for (int i = 0; i < 40; i++) pk[i] = 0;
  zero_regs(om);
  Ring ring{{0u, 8u, 16u, 24u, 32u}, 0x3E0u * 1025};
  uint32_t par = 0;
  int prev = 0;
  const float qscale = 0.07216878364870322f * 1.4426950408889634f;
  constexpr uint32_t pown = B_ADDR(3 + W), poth = B_ADDR(4 - W);
  TL(0); TLG(62);
  {
    WAIT_CHUNK(0, 0, s0)
    MMA_BEGIN();
    mma_both<W, false>(ds, sacc, oh, s0, B_ADDR(xs(0)));
    wg_commit();
    WAIT_CHUNK(1, 0, s1)
    MMA_BEGIN();
    mma_both<W, true>(ds, sacc, oh, s1, B_ADDR(xs(1)));
    wg_commit();
    wg_wait<1>();
    RELEASE_CHUNK(0, s0)
  }
#pragma unroll 1
  for (int it = 0;; it++) {
    char* op = o_ptr(prev);
#pragma unroll
    for (int c = 2; c < 8 - W; c++) {
      WAIT_CHUNK(c, 0, sA)
      TL(40 + c);
      MMA_BEGIN();
      mma_both<W, true>(ds, sacc, oh, sA, B_ADDR(xs(c)));
      wg_commit();
      wg_wait<1>();
      uint32_t sP, pP;
      ring_pos(ring, c - 1, sP, pP);
      RELEASE_CHUNK(c - 1, sP)
      constexpr int NG = 3;
      if (c == 2) { pack_second<W, 0, 1>(pk, om, laddr); store_groups<W, 0 * NG, 1 * NG>(op, pk, it); }
      if (c == 3) { pack_second<W, 1, 2>(pk, om, laddr); store_groups<W, 1 * NG, 2 * NG>(op, pk, it); }
      if (c == 4) { pack_second<W, 2, 3>(pk, om, laddr); store_groups<W, 2 * NG, 3 * NG>(op, pk, it); }
      if (c == 5) { pack_second<W, 3, 4>(pk, om, laddr); store_groups<W, 3 * NG, 4 * NG>(op, pk, it); }
      if (c == 6) {
        pack_second<W, 4, 5>(pk, om, laddr);
        if (W == 1) {
          wg_wait<0>();
          RELEASE_CHUNK(6, sA)
          mbar_arrive_if0(BAR_XDONE, tid);
        }
        store_groups<W, 4 * NG, 15>(op, pk, it);
        __syncwarp();
        mbar_arrive_if0(BAR_OFULL, lane | (it == 0));
      }
    }
    const uint32_t t_ = tid_x(), st_off = ((t_ & 7) + ((t_ & 16) >> 1)) * 128 + (((((t_ & 96) >> 4) + ((t_ >> 3) & 1)) ^ (t_ & 7)) << 4);
    uint32_t sK0, pK0, s7, p7;
    ring_pos(ring, idxK(W), sK0, pK0);
    ring_pos(ring, 7, s7, p7);
    if (W == 1) mbar_wait(bud, BAR_FULLA + s7, p7);
    WAIT_CHUNK(8, 0, s8)
    if (W == 0) {
      MMA_BEGIN();
      mma_both<W, true>(ds, sacc, oh, s8, B_ADDR(xs(8)));
      wg_commit();
      wg_wait<1>();
      RELEASE_CHUNK(7, s7)
    }
    WAIT_CHUNK(9, 0, s9)
    TL(48);
    if (W == 0) {
      MMA_BEGIN();
      mma_mid<W, true>(ds, oh, s9, B_ADDR(xs(9)));
      wg_commit();
      mma_main<W, true>(ds, sacc, s9, B_ADDR(xs(9)));
      wg_commit();
      bar_arrive(5, 256);
      TL(49);
      wg_wait<1>();
      reg_fence(oh);
      mbar_wait(bud, BAR_XDONE, par);
      store_scaled(B_ADDR(1) + st_off, oh, qscale);
    } else {
      bar_sync(5, 256);
      MMA_BEGIN();
      mma_mid<W, true>(ds, oh, s7, B_ADDR(xs(7)));
      mma_mid<W, true>(ds, oh, s8, B_ADDR(xs(8)));
      mma_mid<W, true>(ds, oh, s9, B_ADDR(xs(9)));
      wg_commit();
      mma_main<W, true>(ds, sacc, s7, B_ADDR(xs(7)));
      wg_commit();
      mma_main<W, true>(ds, sacc, s8, B_ADDR(xs(8)));
      wg_commit();
      wg_wait<2>();
      reg_fence(oh);
      store_scaled(B_ADDR(1) + 10240 + st_off, oh, qscale);
      MMA_BEGIN();
      mma_main<W, true>(ds, sacc, s9, B_ADDR(xs(9)));
      wg_commit();
      bar_arrive(8, 256);
      TL(49);
      wg_wait<2>();
      RELEASE_CHUNK(7, s7)
      publish(BAR_QH, lane);
    }
    wg_wait<0>();
    reg_fence(sacc);
    TL(1);
    RELEASE_CHUNK(8, s8)
    RELEASE_CHUNK(9, s9)
    store_scaled(B_ADDR(2 * W) + st_off, sacc, qscale);
    if (W == 1) publish(BAR_QM, lane); else proxy_fence();
    TL(2);
    uint32_t sK = sK0, sV1 = 0;
    if (W == 0) {
      zero_regs(om); zero_regs(oh);
      reg_fence(om); reg_fence(oh);
      mbar_wait(bud, BAR_FULLA + sK0, pK0);
      bar_sync(8, 256);
      MMA_BEGIN();
      s_mma<0, false>(ds, sacc, sK);
      mbar_wait(bud, BAR_QH, par);
      TL(3);
      MMA_BEGIN();
      s_mma<1, true>(ds, sacc, sK);
      mbar_wait(bud, BAR_QM, par);
      TL(5);
      MMA_BEGIN();
      s_mma<2, true>(ds, sacc, sK);
      wg_commit();
      wg_commit();
      bar_arrive(2, 256);
    } else {
      uint32_t pV1;
      ring_pos(ring, idxV(0), sV1, pV1);
      mbar_wait(bud, BAR_FULLA + sK, pK0);
      bar_sync(2, 256);
      MMA_BEGIN();
      s_mma<0, false>(ds, sacc, sK);
      s_mma<1, true>(ds, sacc, sK);
      s_mma<2, true>(ds, sacc, sK);
      wg_commit();
      TL(6);
      mbar_wait(bud, BAR_FULLA + sV1, pV1);
      mbar_wait(bud, BAR_PFULL, 0);
      TL(7);
      MMA_BEGIN();
      mma_both<W, false>(ds, om, oh, sV1, poth);
      wg_commit();
      bar_arrive(1, 256);
    }
#pragma unroll 1
    for (int jj = 0;; jj++) {
      wg_wait<1>();
      reg_fence(sacc);
      TL(8 + jj * 7);
      mbar_arrive2_if0(BAR_EMPTYA + sK, tid);
      mbar_arrive_if0(BAR_EMPTYB + W * 8 + tid * 8, (tid >= 3 - W) | (jj != 3));
#pragma unroll
      for (int J = 0; J < 10; J++) {
        stsm_t(pown + st_off + J * 2048, pack2(ex2(sacc[8 * J]), ex2(sacc[8 * J + 1])), pack2(ex2(sacc[8 * J + 2]), ex2(sacc[8 * J + 3])),
               pack2(ex2(sacc[8 * J + 4]), ex2(sacc[8 * J + 5])), pack2(ex2(sacc[8 * J + 6]), ex2(sacc[8 * J + 7])));
        if (W == 1 && J == 5) publish_generic(BAR_PMID, lane | (jj != 3));
        if (J == 4) {
          wg_wait<0>();
          mbar_arrive_if0(BAR_EMPTYA + sV1, tid | (W == 0 && jj == 0));
        }
      }
      publish(BAR_PFULL + W * 8, lane);
      TL(10 + jj * 7);
      if (jj == 3) break;
      uint32_t sV, pV, pK, pV1;
      ring_pos(ring, idxV(W), sV, pV);
      ring_pos(ring, idxV(W) + 1, sK, pK);
      ring_pos(ring, idxV(W) + 2, sV1, pV1);
      mbar_wait(bud, BAR_FULLA + sV, pV);
      bar_sync(1 + W, 256);
      MMA_BEGIN();
      mma_both<W, true>(ds, om, oh, sV, pown);
      wg_commit();
      mbar_wait(bud, BAR_FULLA + sK, pK);
      TL(11 + jj * 7);
      MMA_BEGIN();
      s_mma<0, false>(ds, sacc, sK);
      if (W == 1) wg_commit();
      s_mma<1, true>(ds, sacc, sK);
      wg_commit();
      wg_wait<1 + W>();
      mbar_arrive_if0(BAR_EMPTYA + sV, tid);
      if (W == 1) {
        wg_wait<1>();
        mbar_arrive_if0(BAR_EMPTYB, tid | (jj != 2));
      }
      MMA_BEGIN();
      s_mma<2, true>(ds, sacc, sK);
      wg_commit();
      TL(13 + jj * 7);
      mbar_wait(bud, BAR_FULLA + sV1, pV1);
      mbar_wait(bud, BAR_PFREE + W * 8, jj & 1);
      mbar_wait(bud, BAR_PFULL + (1 - W) * 8, (jj + W) & 1);
      TL(14 + jj * 7);
      MMA_BEGIN();
      mma_both<W, true>(ds, om, oh, sV1, poth);
      wg_commit();
      bar_arrive(2 - W, 256);
      ring_advance(ring, 4);
    }
    uint32_t sV6, pV6, sV7, pV7;
    ring_pos(ring, idxV(6) - 12, sV6, pV6);
    ring_pos(ring, idxV(7) - 12, sV7, pV7);
    prev = item;
    mbar_wait(bud, BAR_FULLA + (W == 0 ? sV6 : sV7), W == 0 ? pV6 : pV7);
    if (!DEBUG_TIMEOUT) item = next_item();
    bar_sync(W == 0 ? 1 : 6, 256);
    if (DEBUG_TIMEOUT) item = next_item(NEXT_ITEM + 4);
    if (item >= NITEMS) {
      MMA_BEGIN();
      if (W == 0) {
        mma_both<0, true>(ds, om, oh, sV6, pown);
        wg_commit();
        mbar_wait(bud, BAR_FULLA + sV7, pV7);
        mbar_wait(bud, BAR_PFULL + 8, 1);
        MMA_BEGIN();
      }
      mma_both<W, true>(ds, om, oh, sV7, B_ADDR(4));
      wg_commit();
      if (W == 0) bar_arrive(6, 256);
      TL(32);
      wg_wait<0>();
      reg_fence(om); reg_fence(oh);
      TL(33);
      mbar_wait(bud, BAR_LFULL, par);
      mbar_arrive_if0(BAR_FREE, tid);
      TL(34);
      pack_first<W>(pk, om, oh, laddr);
      op = o_ptr(prev);
      store_groups<W, 0, 10>(op, pk, 1);
      pack_second<W, 0, 5>(pk, om, laddr);
      store_groups<W, 10, 15>(op, pk, 1);
      publish_generic(BAR_OFULL, lane);
      TL(35); TLG(63);
      TL_FLUSH();
      return item;
    }
    {
      MMA_BEGIN();
      mma_both<W, true>(ds, om, oh, W == 0 ? sV6 : sV7, pown);
      wg_commit();
      if (W == 0) mbar_wait(bud, BAR_FULLA + sV7, pV7);
      WAIT_CHUNK(0, 26 - 12, s0)
      TL(38);
      MMA_BEGIN();
      mma_main<W, false>(ds, sacc, s0, B_ADDR(xs(0)));
      wg_commit();
      if (W == 0) {
        wg_wait<1>();
        mbar_arrive_if0(BAR_EMPTYA + sV6, tid);
        mbar_wait(bud, BAR_PFULL + 8, 1);
        MMA_BEGIN();
        mma_both<0, true>(ds, om, oh, sV7, poth);
        wg_commit();
        bar_arrive(6, 256);
      }
      TL(32);
      WAIT_CHUNK(1, 26 - 12, s1)
      if (W == 0) wg_wait<0>(); else wg_wait<1>();
      reg_fence(om); reg_fence(oh);
      mbar_arrive_if0(BAR_EMPTYA + sV7, tid);
      TL(33);
      MMA_BEGIN();
      mma_main<W, true>(ds, sacc, s1, B_ADDR(xs(1)));
      wg_commit();
      mbar_wait(bud, BAR_LFULL, par);
      mbar_arrive_if0(BAR_EMPTYB + 24 + tid * 8, tid >= 2);
      TL(34);
      pack_first<W>(pk, om, oh, laddr);
      TL(36);
      MMA_BEGIN();
      mma_mid<W, false>(ds, oh, s0, B_ADDR(xs(0)));
      wg_commit();
      mma_mid<W, true>(ds, oh, s1, B_ADDR(xs(1)));
      wg_commit();
      TL(37);
      wg_wait<1>();
      RELEASE_CHUNK(0, s0)
      TL(35); TLG(63);
    }
    TL_FLUSH();
    TL(0); TLG(62);
    ring_advance(ring, 26 - 12);
    par ^= 1;
  }
}

__device__ __forceinline__ uint4 lds128(uint32_t a) {
  uint4 v;
  asm volatile("ld.shared.v4.b32 {%0,%1,%2,%3}, [%4];" : "=r"(v.x), "=r"(v.y), "=r"(v.z), "=r"(v.w) : "r"(a) : "memory");
  return v;
}
__device__ __forceinline__ void acc2(float& s, float& t, uint32_t w) {
  s += __uint_as_float(w << 16);
  t += __uint_as_float(w & 0xffff0000u);
}
__device__ __forceinline__ uint32_t badd2(uint32_t a, uint32_t b) { uint32_t r; asm("add.rn.bf16x2 %0, %1, %2;" : "=r"(r) : "r"(a), "r"(b)); return r; }
__device__ __forceinline__ void sum_unit(float& acc, uint32_t pb) {
  const uint4 v0 = lds128(pb), v1 = lds128(pb ^ 32), v2 = lds128(pb ^ 64), v3 = lds128(pb ^ 96);
  const uint32_t w0 = badd2(badd2(v0.x, v0.y), badd2(v0.z, v0.w));
  float s = acc + __uint_as_float(w0 << 16), t = __uint_as_float(w0 & 0xffff0000u);
  acc2(s, t, badd2(badd2(v1.x, v1.y), badd2(v1.z, v1.w)));
  acc2(s, t, badd2(badd2(v2.x, v2.y), badd2(v2.z, v2.w)));
  acc2(s, t, badd2(badd2(v3.x, v3.y), badd2(v3.z, v3.w)));
  acc = s + t;
}
__device__ __forceinline__ float bf_lo(uint32_t w) { return __uint_as_float(w << 16); }
__device__ __forceinline__ float bf_hi(uint32_t w) { return __uint_as_float(w & 0xffff0000u); }
__device__ __forceinline__ float bf_rn(float x) { return __bfloat162float(__float2bfloat16(x)); }
__device__ __forceinline__ void slow_item(const Params& p, int item, int hw) {
  const int blk = item >> 9, h = (item >> 4) & 31, b = item & 15;
#pragma unroll 1
  for (int n = hw; n < SQ; n += 3) {
    float q[6] = {0.f, 0.f, 0.f, 0.f, 0.f, 0.f};
    {
      const uint32_t* xr = (const uint32_t*)(p.xp[blk] + (size_t)(b * SQ + n) * DM);
      const uint32_t* wq = (const uint32_t*)(p.wqp[blk] + h * DH) + (tid_x() & 31);
#pragma unroll 2
      for (int k = 0; k < DM / 2; k++) {
        const uint32_t xv = xr[k];
#pragma unroll
        for (int i = 0; i < 3; i++) {
          const uint32_t w0 = wq[i * 32], w1 = wq[NH * DH / 2 + i * 32];
          q[2 * i] = fmaf(bf_lo(xv), bf_lo(w0), fmaf(bf_hi(xv), bf_lo(w1), q[2 * i]));
          q[2 * i + 1] = fmaf(bf_lo(xv), bf_hi(w0), fmaf(bf_hi(xv), bf_hi(w1), q[2 * i + 1]));
        }
        wq += NH * DH;
      }
    }
    const uint32_t q0 = pack2(q[0], q[1]), q1 = pack2(q[2], q[3]), q2 = pack2(q[4], q[5]);
    float o[6] = {0.f, 0.f, 0.f, 0.f, 0.f, 0.f}, m = -INFINITY, l = 0.f;
    const uint32_t* kg = (const uint32_t*)(p.kp[blk] + (size_t)(b * NH + h) * SK * DH) + (tid_x() & 31);
    const uint32_t* vg = (const uint32_t*)(p.vp[blk] + (size_t)(b * NH + h) * SK * DH) + (tid_x() & 31);
#pragma unroll 1
    for (int k = 0; k < SK; k++) {
      const uint32_t k0 = kg[0], k1 = kg[32], k2 = kg[64], v0 = vg[0], v1 = vg[32], v2 = vg[64];
      kg += DH / 2; vg += DH / 2;
      float sc = fmaf(bf_lo(q0), bf_lo(k0), bf_hi(q0) * bf_hi(k0));
      sc = fmaf(bf_lo(q1), bf_lo(k1), fmaf(bf_hi(q1), bf_hi(k1), sc));
      sc = fmaf(bf_lo(q2), bf_lo(k2), fmaf(bf_hi(q2), bf_hi(k2), sc));
#pragma unroll
      for (int d = 16; d; d >>= 1) sc += __shfl_xor_sync(0xffffffffu, sc, d);
      sc = bf_rn(bf_rn(sc) * 0.07216878364870322f);
      const float mn = fmaxf(m, sc), a = ex2((m - mn) * 1.4426950408889634f), pr = ex2((sc - mn) * 1.4426950408889634f);
      m = mn;
      l = fmaf(l, a, pr);
      o[0] = fmaf(o[0], a, pr * bf_lo(v0)); o[1] = fmaf(o[1], a, pr * bf_hi(v0));
      o[2] = fmaf(o[2], a, pr * bf_lo(v1)); o[3] = fmaf(o[3], a, pr * bf_hi(v1));
      o[4] = fmaf(o[4], a, pr * bf_lo(v2)); o[5] = fmaf(o[5], a, pr * bf_hi(v2));
    }
    float inv;
    asm("rcp.approx.ftz.f32 %0, %1;" : "=f"(inv) : "f"(l));
    const int lane = tid_x() & 31;
    const int r = n & 15, c = 4 * ((r & 7) >> 1) + 2 * (r >> 3) + (r & 1);
    char* on = o_slot(item) + (lane >> 2) * 256 + (lane & 3) * 64 + (n >> 4) * 2048 +
               (((c >> 3) ^ ((lane >> 1) & 1)) << 4) + (c & 7) * 2;
#pragma unroll
    for (int i = 0; i < 3; i++) {
      *(__nv_bfloat16*)(on + i * B_SLOT) = __float2bfloat16(o[2 * i] * inv);
      *(__nv_bfloat16*)(on + i * B_SLOT + 32) = __float2bfloat16(o[2 * i + 1] * inv);
    }
  }
}
__device__ __forceinline__ void attn_helper(const Params& p, int hw, int item, int epoch) {
  int bud = WAIT_BUDGET;
  if (hw == 2) {
    if (item == 0 && elect_one()) {
      *(volatile int*)&g_ticket = 0;
      asm volatile("red.release.gpu.global.add.s32 [%0], 1;" ::"l"(&g_go) : "memory");
    }
    __syncwarp();
    flag_wait(bud, &g_go, epoch + 1);
  }
  if (item < PF_N && hw < 2) {
    const char* g = (const char*)(hw ? p.vp[0] : p.kp[0]) + (size_t)(((item & 15) * NH + (item >> 4)) * SK) * DH * 2;
    const long long t0 = clock64();
#pragma unroll 1
    for (int i = 0; i < 32; i++) {
      while (clock64() - t0 < PF_WAIT + i * PF_GAP) __nanosleep(50);
      for (int k = 0; k < 6; k++) asm volatile("prefetch.global.L2 [%0];" ::"l"(g + i * 6144 + k * 1024 + (tid_x() & 31) * 32));
      __syncwarp();
    }
  }
#pragma unroll 1
  for (int it = 0; item < NITEMS; it++) {
    const uint32_t par = it & 1;
    int lane = tid_x() & 31;
    const int r = lane >> 1;
    const uint32_t a0 = B_ADDR(3) + (16 * hw + r) * 128 + (lane & 1) * 16 + ((r & 3) << 5);
    float acc[4] = {0.f, 0.f, 0.f, 0.f};
#pragma unroll 1
    for (int j = 0; j < 8; j++) {
      const uint32_t pb = a0 + (j & 1) * B_SLOT, bfull = BAR_PFULL + (j & 1) * 8, pfull = (j >> 1) & 1;
      mbar_wait(bud, j == 7 ? BAR_PMID : bfull, j == 7 ? par : pfull);
      sum_unit(acc[0], pb);
      sum_unit(acc[1], pb + 6144);
      if (j == 7) mbar_wait(bud, bfull, pfull);
      sum_unit(acc[2], pb + 2 * 6144);
      if (hw == 0) sum_unit(acc[3], pb + 3 * 6144);
      __syncwarp();
      mbar_arrive_if0(BAR_PFREE + (j & 1) * 8, lane);
      if (j == 5 && hw == 2) {
        if (lane == 0) TLP(60);
        if (item >= ORING && item < OFRESH) flag_wait(bud, &g_done[item - ORING], (epoch + 1) * 2);
        if (lane == 0) TLP(61);
      }
    }
    bool bad = false;
    const uint32_t la = SB + OFF_L + (((r & 7) >> 1) * 40 + 2 * (r >> 3) + (r & 1) + 4 * hw) * 4;
#pragma unroll
    for (int u = 0; u < 4; u++) {
      const float l = acc[u] + __shfl_xor_sync(0xffffffffu, acc[u], 1);
      if (u < 3 || hw == 0) {
        bad |= !(l >= 9.094947017729282e-13f && l <= 1.099511627776e12f);
        float inv;
        asm("rcp.approx.ftz.f32 %0, %1;" : "=f"(inv) : "f"(l));
        asm volatile("st.shared.f32 [%0], %1;" ::"r"(la + u * 48), "f"(inv) : "memory");
      }
    }
    publish_generic(BAR_LFULL, lane);
    if (lane == 0) TLP(40 + hw * 4);
    uint32_t anybad;
    asm volatile("{\n.reg .pred p, q;\nsetp.ne.u32 p, %1, 0;\nbarrier.red.or.pred q, 7, 96, p;\nselp.u32 %0, 1, 0, q;\n}\n"
                 : "=r"(anybad) : "r"((uint32_t)bad) : "memory");
    if (__any_sync(0xffffffffu, anybad)) {
      mbar_wait(bud, BAR_OFULL, par);
      slow_item(p, item, hw);
      bar_sync(7, 96);
    }
    if (hw == 1) {
      mbar_wait(bud, BAR_OFULL, par);
      if ((tid_x() & 31) == 0) {
        TLP(41 + hw * 4);
        asm volatile("red.release.gpu.global.add.s32 [%0], 1;" ::"l"(&g_ready[item]) : "memory");
        TLP(42 + hw * 4);
      }
      __syncwarp();
    }
    item = next_item();
  }
}

__device__ __forceinline__ int attn_producer(const Params& p, int item) {
  int bud = WAIT_BUDGET;
  uint32_t sa = 0, pa = 1;
  const uint64_t pol = evict_first_policy();
  const bool draws = item >= N_OCTA;
  const int delay = start_delay(item);
  {
    const long long t0 = clock64();
    while (clock64() - t0 < delay) __nanosleep(100);
  }
#pragma unroll 1
  for (int it = 0; item < NITEMS; it++) {
    const int blk = item >> 9, h = (item >> 4) & 31, b = item & 15;
    const int row0 = (b * NH + h) * SK;
    if (!(it | delay)) pa = 0;
#pragma unroll 1
    for (int c = (it | delay) ? 0 : NSLOT; c < 10; c++) {
      const uint32_t sx = c < NSLOT ? c : c - NSLOT;
      mbar_wait(bud, BAR_EMPTYA + sa * 8, pa);
      TLP(c);
      mbar_expect(BAR_FULLA + sa * 8, A_SLOT + B_SLOT);
      tma3d(A_ADDR(sa), &p.wq[blk], BAR_FULLA + sa * 8, 0, c * 64, h * 3);
      mbar_wait(bud, BAR_EMPTYB + sx * 8, c < NSLOT);
      TLP(10 + c);
      tma2d(B_ADDR(sx), &p.x[blk], BAR_FULLA + sa * 8, c * 64, b * SQ);
      if (++sa == NSLOT) { sa = 0; pa ^= 1; }
    }
#pragma unroll 1
    for (int i = 0; i < 16; i++) {
      const bool isK = (i == 0) || ((i & 1) && i < 15);
      const int j = i == 0 ? 0 : (i == 15 ? 7 : (isK ? (i + 1) >> 1 : (i - 2) >> 1));
      mbar_wait(bud, BAR_EMPTYA + sa * 8, pa);
      TLP(20 + i);
      mbar_expect(BAR_FULLA + sa * 8, A_SLOT);
      tma3d_hint(A_ADDR(sa), isK ? &p.k[blk] : &p.v[blk], BAR_FULLA + sa * 8, 0, row0 + j * 64, 0, pol);
      if (i == 12) {
        item = draws ? NCTA + atomicAdd(&g_ticket, 1) : NITEMS;
        asm volatile("st.shared.s32 [%0], %1;" ::"r"(NEXT_ITEM), "r"(item) : "memory");
      }
      if (++sa == NSLOT) { sa = 0; pa ^= 1; }
    }
  }
  return item;
}

struct OJob { int tile, part, c0, n; };
__device__ __forceinline__ OJob get_ojob(int cta, int last) {
  if (cta < N_OCTA) return OJob{cta, 0, 0, CHUNK1};
  const int u = last - NITEMS, part = 1 + (u >> 5), tile = part == 3 ? 95 - u : u & 31;
  const int c1 = CHUNK1, c2 = c1 + LEN1 - ((tile * LSLOPE1 + 16) >> 5), c3 = c2 + LEN2 - ((tile * LSLOPE2 + 16) >> 5);
  return OJob{tile, part, part == 1 ? c1 : part == 2 ? c2 : c3, part == 1 ? c2 - c1 + 1 : part == 2 ? c3 - c2 + 1 : part == 3 ? 189 - c3 + 1 : 0};
}
__device__ __forceinline__ int unperm(int c) { return 8 * ((c >> 1) & 1) + 4 * (c >> 3) + 2 * ((c >> 2) & 1) + (c & 1); }
__device__ __forceinline__ uint32_t first_stage(const OJob& job) { return job.part ? 2 : 0; }

__device__ __forceinline__ void oproj_consumer(const Params& p, const OJob job, const int W) {
  int bud = WAIT_BUDGET;
  const int tid = tid_x() & 127, lane = tid & 31, warp = tid >> 5;
  float a0[80], a1[80], ah[40];
  zero_regs(a0); zero_regs(a1); zero_regs(ah);
  const uint64_t dam = p.dsw + W * (3 * 8192 >> 4), dbh = p.dso + W * (10240 >> 4);
  int left = job.n, step = 0;
  uint32_t st = first_stage(job), ph = 0;
#pragma unroll 1
  while (left) {
    const int nc = left > 3 * NH ? 3 * NH : left;
    left -= nc;
#pragma unroll 1
    for (int c = 0; c < nc; c++) {
      mbar_wait(bud, BAR_GFULL + st * 8, (ph >> st) & 1);
      ph ^= 1 << st;
      bar_sync_if0(11, W | (c - max(nc - 2, 0)));
      wg_fence();
      const uint32_t la = st, lb = st;
#define O_STEP(ks, sc)                                                        \
  mma80r<1, 1, 2 * 8192 + ks * 2048, SB + O_AB + ks * 512>(ah, p.dsw, la, dbh, lb, sc);   \
  mma160r<1, 1, ks * 2048, SB + O_AB + ks * 512>(a0, dam, la, p.dso, lb, sc);             \
  mma160r<1, 1, 8192 + ks * 2048, SB + O_AB + ks * 512>(a1, dam, la, p.dso, lb, sc);
      O_STEP(0, c != 0) O_STEP(1, 1)
      wg_commit();
      wg_wait<1>();
      mbar_arrive_if0(BAR_GEMPTY + (st == 0 ? 2 : st - 1) * 8, tid | (c == 0));
      wg_fence();
      O_STEP(2, 1) O_STEP(3, 1)
#undef O_STEP
      wg_commit();
      if (++st == 3) {
        st = 0;
        asm volatile("{\n.reg .pred p;\nsetp.eq.u32 p, %1, 0;\n@p red.relaxed.gpu.global.add.s32 [%0], 1;\n}\n"
                     ::"l"(&g_done[(step < 2 ? step ^ (job.tile & 1) : step) * 16 + (job.tile >> 1)]), "r"(tid | job.part | W) : "memory");
        TLG(step);
        step++;
      }
    }
    if (W) bar_arrive(11, 256);
    wg_wait<0>();
    reg_fence(a0); reg_fence(a1); reg_fence(ah);
    mbar_arrive_if0(BAR_GEMPTY + (st - 1) * 8, tid | (st == 0));
    TLG(63); TL(left ? 59 : 62);
    const int prow = (lane & 7) + 8 * (lane >> 4), qrow = left ? unperm(prow) : prow;
    const uint32_t sg = SB + O_OUT + qrow * 128 + (((2 * warp + ((lane >> 3) & 1)) ^ (qrow & 7)) << 4);
    if (W) bar_arrive(3, 256); else bar_arrive(9, 256);
    bar_sync_if0(3, W);
    store_scaled(sg + W * 3 * B_SLOT, a0, 1.0f);
    publish(BAR_GOUT + W * 24, lane);
    store_scaled(sg + W * 3 * B_SLOT + B_SLOT, a1, 1.0f);
    publish(BAR_GOUT + W * 24 + 8, lane);
    bar_sync_if0(9, W - 1);
    store_scaled(sg + 2 * B_SLOT + W * 10240, ah, 1.0f);
    publish(BAR_GOUT + 16, lane);
  }
  TL_FLUSH();
  TLG(0);
  float acc[7][8];
  uint32_t in[7], blk[7], oo[7];
#pragma unroll
  for (int i = 0; i < 7; i++) {
    const int e = min(i * 256 + W * 128 + tid, 1599), r = e / 40, cc = e % 40, R = job.part * 40 + r;
    in[i] = r * 128 + (((cc ^ r) & 7) << 4);
    blk[i] = cc >> 3;
    oo[i] = ((R & ~15) + unperm(R & 15)) * (2 * DM / 8) + cc;
    asm volatile("" : "+r"(oo[i]));
#pragma unroll
    for (int k = 0; k < 8; k++) acc[i][k] = 0.f;
  }
  bar_sync(10, 256);
#pragma unroll 1
  for (int q = 0; q < 4; q++) {
    if (q) mbar_wait(bud, BAR_GRED + (q - 1) * 8, 0);
    if (q == 3) TLG(1);
    const uint32_t base = q ? SB + (q - 1) * 25600 : SB + O_OUT + job.part * 5120, bs = q ? 5120 : B_SLOT;
    uint4 v[7];
#pragma unroll
    for (int i = 0; i < 7; i++) v[i] = lds128(base + blk[i] * bs + in[i]);
#pragma unroll
    for (int i = 0; i < 7; i++) {
      acc[i][0] += bf_lo(v[i].x); acc[i][1] += bf_hi(v[i].x); acc[i][2] += bf_lo(v[i].y); acc[i][3] += bf_hi(v[i].y);
      acc[i][4] += bf_lo(v[i].z); acc[i][5] += bf_hi(v[i].z); acc[i][6] += bf_lo(v[i].w); acc[i][7] += bf_hi(v[i].w);
    }
  }
  uint4* go = (uint4*)p.outp + (job.tile >> 1) * SQ * (2 * DM / 8) + DM / 8 + (job.tile & 1) * 40;
#pragma unroll
  for (int i = 0; i < 7; i++) {
    if (i * 256 + W * 128 + tid < 1600)
      go[oo[i]] = make_uint4(pack2(acc[i][0], acc[i][1]), pack2(acc[i][2], acc[i][3]), pack2(acc[i][4], acc[i][5]), pack2(acc[i][6], acc[i][7]));
  }
  TLG(2);
  TL_FLUSH();
}

__device__ __forceinline__ void oproj_producer(const Params& p, const OJob job, int target) {
  int bud = WAIT_BUDGET;
  const uint64_t polo = evict_first_policy();
  uint32_t st = first_stage(job), ph = 7;
  int seen = -1;
#pragma unroll 1
  for (int i = 0; i < job.n; i++) {
    const int c = job.part ? (i == job.n - 1 ? 188 + job.part : job.c0 + i) : (i < 6 && (job.tile & 1) ? (i < 3 ? i + 3 : i - 3) : i), step = c / 3, kb = c - 3 * step;
    const int item = step * 16 + (job.tile >> 1);
    int v = target;
    if (step != seen) asm volatile("ld.acquire.gpu.global.s32 %0, [%1];" : "=r"(v) : "l"(&g_ready[item]) : "memory");
    const uint32_t dst = SB + st * O_STAGE, bar = BAR_GFULL + st * 8;
    const char* og = o_slot(item) + kb * B_SLOT;
    if (i == 0 && job.part) {
      for (int k = 0; k < 3; k++) mbar_wait(bud, BAR_EMPTYB + k * 8, 1);
    } else if (i < 2) {
      mbar_wait(bud, BAR_FREE, 0);
    }
    mbar_wait(bud, BAR_GEMPTY + st * 8, (ph >> st) & 1);
    ph ^= 1 << st;
    mbar_expect(bar, O_STAGE);
    tma3d(dst, &p.wo[step >> 5], bar, 0, (c - (step >> 5) * 3 * NH) * 64, (job.tile & 1) * 5);
    if (step != seen) {
      if (v - target < 0) flag_wait(bud, &g_ready[item], target);
      asm volatile("fence.proxy.async.global;" ::: "memory");
      seen = step;
    }
    bulk_load_hint(dst + O_AB, og, B_SLOT, bar, polo);
    if (++st == 3) st = 0;
  }
  mbar_wait(bud, BAR_FREE, 0);
  mbar_wait(bud, BAR_GEMPTY, ph & 1);
  mbar_wait(bud, BAR_GEMPTY + 8, (ph >> 1) & 1);
  uint32_t todo = 15 & ~(1 << job.part), dst = SB, bar = BAR_GRED;
  while (todo) {
    int v0, v1, v2, v3;
    asm volatile("ld.acquire.gpu.global.v4.s32 {%0, %1, %2, %3}, [%4];" : "=r"(v0), "=r"(v1), "=r"(v2), "=r"(v3) : "l"(&g_pcnt[job.tile * 4]) : "memory");
    const uint32_t rdy = --bud > 0 ? (v0 - target >= 0) | (v1 - target >= 0) << 1 | (v2 - target >= 0) << 2 | (v3 - target >= 0) << 3 : 15;
    if (!(rdy & todo)) continue;
    asm volatile("fence.proxy.async.global;" ::: "memory");
#pragma unroll 1
    for (int q = 0; q < 4; q++) {
      if (!(((rdy & todo) >> q) & 1)) continue;
      TLE(4 + q);
      mbar_expect(bar, 25600);
      for (int k = 0; k < 5; k++)
        tma2d(dst + k * 5120, &p.part, bar, (job.tile & 1) * 320 + k * 64, q * NB * SQ + (job.tile >> 1) * SQ + job.part * 40);
      todo &= ~(1 << q);
      dst += 25600;
      bar += 8;
    }
  }
}

__device__ __forceinline__ void oproj_storer(const Params& p, const OJob job) {
  int bud = WAIT_BUDGET;
  const int col = (job.tile & 1) * 320, row = (job.tile >> 1) * SQ;
  if (job.part == 0) {
    for (int k = 0; k < 3; k++) {
      mbar_wait(bud, BAR_GOUT + k * 8, 0);
      tma_store2d(&p.out, SB + O_OUT + k * B_SLOT, col + k * 64, row);
    }
    asm volatile("cp.async.bulk.commit_group;" ::: "memory");
    asm volatile("cp.async.bulk.wait_group.read 0;" ::: "memory");
    mbar_arrive2_if0(BAR_GEMPTY + 16, 0);
    mbar_wait(bud, BAR_GFULL + 16, 0);
    for (int k = 3; k < 5; k++) {
      mbar_wait(bud, BAR_GOUT + k * 8, 0);
      tma_store2d(&p.out, SB + O_OUT + k * B_SLOT, col + k * 64, row);
      asm volatile("cp.async.bulk.commit_group;" ::: "memory");
      asm volatile("cp.async.bulk.wait_group.read 0;" ::: "memory");
      __nanosleep(1000);
    }
  }
#pragma unroll 1
  for (int i = 0; i < 5; i++) {
    const int k = (0x21043 >> (4 * i)) & 15;
    mbar_wait(bud, BAR_GOUT + k * 8, job.part == 0);
    if (i == 0) TLE(0);
    for (int q = 1; q < 4; q++) {
      const int sh = (job.part + q) & 3;
      tma_store2d(&p.part, SB + O_OUT + k * B_SLOT + sh * 5120, col + k * 64, job.part * NB * SQ + row + sh * 40);
    }
  }
  asm volatile("cp.async.bulk.commit_group;" ::: "memory");
  TLE(1);
  asm volatile("cp.async.bulk.wait_group 0;" ::: "memory");
  TLE(2);
  asm volatile("fence.proxy.async.global;" ::: "memory");
  asm volatile("red.release.gpu.global.add.s32 [%0], 1;" ::"l"(&g_pcnt[job.tile * 4 + job.part]) : "memory");
  TLE(3);
}

__global__ void __launch_bounds__(384, 1) fused_kernel(const __grid_constant__ Params p) {
  extern __shared__ __align__(1024) char smem_raw[];
  if ((smem_u32(smem_raw) & 0xFFFFFFu) != SB) return;
  const int cta = (((blockIdx.x / PERM_G) * PERM_M) % (NCTA / PERM_G)) * PERM_G + (blockIdx.x % PERM_G);
  const int warp = __shfl_sync(0xffffffffu, threadIdx.x >> 5, 0);
  if (threadIdx.x == 0) {
    for (int i = 0; i < NSLOT; i++) { mbar_init(BAR_FULLA + i * 8, 1); mbar_init(BAR_EMPTYA + i * 8, 2); mbar_init(BAR_EMPTYB + i * 8, 2); }
    proxy_fence();
    if (start_delay(cta) == 0) {
#pragma unroll 1
      for (int c = 0; c < NSLOT; c++) {
        mbar_expect(BAR_FULLA + c * 8, A_SLOT + B_SLOT);
        tma3d(A_ADDR(c), &p.wq[0], BAR_FULLA + c * 8, 0, c * 64, (first_item(cta) >> 4) * 3);
        tma2d(B_ADDR(c), &p.x[0], BAR_FULLA + c * 8, c * 64, (first_item(cta) & 15) * SQ);
      }
    }
  }
  if (threadIdx.x == 64) {
    mbar_init(BAR_XDONE, 1); mbar_init(BAR_QH, 4); mbar_init(BAR_QM, 4);
    mbar_init(BAR_PFULL, 4); mbar_init(BAR_PFULL + 8, 4); mbar_init(BAR_PFREE, 3); mbar_init(BAR_PFREE + 8, 3);
    mbar_init(BAR_LFULL, 3); mbar_init(BAR_PMID, 4); mbar_init(BAR_OFULL, 8);
  }
  if (threadIdx.x == 96) {
    for (int i = 0; i < O_NST; i++) { mbar_init(BAR_GFULL + i * 8, 1); mbar_init(BAR_GEMPTY + i * 8, 2); }
    for (int i = 0; i < 5; i++) mbar_init(BAR_GOUT + i * 8, i == 2 ? 8 : 4);
    mbar_init(BAR_GRED, 1); mbar_init(BAR_GRED + 8, 1); mbar_init(BAR_GRED + 16, 1); mbar_init(BAR_FREE, 2);
    proxy_fence();
  }
  __syncthreads();
  if (warp >= 8) {
    asm volatile("setmaxnreg.dec.sync.aligned.u32 40;");
    if (warp == 8) {
      if (elect_one()) {
        const OJob job = get_ojob(cta, attn_producer(p, first_item(cta)));
        const int epoch = *(volatile int*)&g_epoch[cta];
        *(volatile int*)&g_epoch[cta] = epoch + 1;
        if (job.n) oproj_producer(p, job, epoch + 1);
      }
    } else {
      const int epoch = __shfl_sync(0xffffffffu, *(volatile int*)&g_epoch[cta], 0);
      attn_helper(p, warp - 9, first_item(cta), epoch);
      if (warp == 9) {
        const OJob job = get_ojob(cta, next_item());
        if (job.n && elect_one()) oproj_storer(p, job);
      }
    }
  } else {
    asm volatile("setmaxnreg.inc.sync.aligned.u32 232;");
    const OJob job = get_ojob(cta, warp < 4 ? attn_consumer<0>(p.dsw, p.zero, first_item(cta)) : attn_consumer<1>(p.dsw, p.zero, first_item(cta)));
    if (job.n) oproj_consumer(p, job, warp >> 2);
  }
}

typedef CUresult (*EncodeFn)(CUtensorMap*, CUtensorMapDataType, cuuint32_t, void*, const cuuint64_t*, const cuuint64_t*, const cuuint32_t*,
                             const cuuint32_t*, CUtensorMapInterleave, CUtensorMapSwizzle, CUtensorMapL2promotion, CUtensorMapFloatOOBfill);

void make3d(EncodeFn enc, CUtensorMap* m, const void* ptr, uint64_t rows, uint64_t cols, uint32_t box_rows, uint32_t box_blocks) {
  cuuint64_t gd[3] = {64, rows, cols / 64};
  cuuint64_t gs[2] = {cols * 2, 128};
  cuuint32_t bd[3] = {64, box_rows, box_blocks}, es[3] = {1, 1, 1};
  enc(m, CU_TENSOR_MAP_DATA_TYPE_BFLOAT16, 3, (void*)ptr, gd, gs, bd, es, CU_TENSOR_MAP_INTERLEAVE_NONE, CU_TENSOR_MAP_SWIZZLE_128B,
      CU_TENSOR_MAP_L2_PROMOTION_L2_128B, CU_TENSOR_MAP_FLOAT_OOB_FILL_NONE);
}
void make2d(EncodeFn enc, CUtensorMap* m, const void* ptr, uint64_t rows, uint64_t cols, uint32_t box_rows) {
  cuuint64_t gd[2] = {cols, rows};
  cuuint64_t gs[1] = {cols * 2};
  cuuint32_t bd[2] = {64, box_rows}, es[2] = {1, 1};
  enc(m, CU_TENSOR_MAP_DATA_TYPE_BFLOAT16, 2, (void*)ptr, gd, gs, bd, es, CU_TENSOR_MAP_INTERLEAVE_NONE, CU_TENSOR_MAP_SWIZZLE_128B,
      CU_TENSOR_MAP_L2_PROMOTION_L2_128B, CU_TENSOR_MAP_FLOAT_OOB_FILL_NONE);
}

}

extern "C" void kernel_launch(void* const* d_in, const int* in_sizes, int n_in, void* d_out, int out_size) {
  static EncodeFn enc = nullptr;
  static void* part = nullptr;
  if (!enc) {
    cudaGetSymbolAddress(&part, g_part);
    cudaDriverEntryPointQueryResult qr;
    cudaGetDriverEntryPoint("cuTensorMapEncodeTiled", (void**)&enc, cudaEnableDefault, &qr);
    cudaFuncSetAttribute(fused_kernel, cudaFuncAttributeMaxDynamicSharedMemorySize, SMEM_BYTES);
  }
  Params p;
  for (int s = 0; s < 2; s++) {
    make2d(enc, &p.x[s], d_in[5 * s + 0], NB * SQ, DM, SQ);
    make3d(enc, &p.k[s], d_in[5 * s + 1], (uint64_t)NB * NH * SK, DH, 64, 3);
    make3d(enc, &p.v[s], d_in[5 * s + 2], (uint64_t)NB * NH * SK, DH, 64, 3);
    make3d(enc, &p.wq[s], d_in[5 * s + 3], DM, NH * DH, 64, 3);
    make3d(enc, &p.wo[s], d_in[5 * s + 4], NH * DH, DM, 64, 5);
    p.xp[s] = (const __nv_bfloat16*)d_in[5 * s + 0];
    p.wqp[s] = (const __nv_bfloat16*)d_in[5 * s + 3];
    p.kp[s] = (const __nv_bfloat16*)d_in[5 * s + 1];
    p.vp[s] = (const __nv_bfloat16*)d_in[5 * s + 2];
  }
  make2d(enc, &p.out, d_out, NB * SQ, 2 * DM, SQ);
  make2d(enc, &p.part, part, 4 * NB * SQ, DM, 40);
  p.outp = (__nv_bfloat16*)d_out;
  p.dsw = DESC_SW;
  p.dso = DESC_O;
  p.zero = 0;
  fused_kernel<<<NCTA, 384, SMEM_BYTES>>>(p);
}
```
